```python
import torch

def _softmax(x, axis=-1):
    return torch.softmax(x, dim=axis)
def _gelu(x):
    return torch.nn.functional.gelu(x, approximate="tanh")
def _silu(x):
    return torch.nn.functional.silu(x)
def _sigmoid(x):
    return torch.sigmoid(x)
def _layernorm(x, axis=-1, eps=1e-5):
    m = x.mean(dim=axis, keepdim=True)
    v = x.var(dim=axis, keepdim=True, unbiased=False)
    return (x - m) / torch.sqrt(v + eps)
def _scatter_add(tgt, idx, src, axis=0):
    return tgt.clone().index_add_(axis, idx, src)
def _segment_sum(src, seg, n):
    out = torch.zeros((n,) + src.shape[1:], dtype=src.dtype)
    return out.index_add_(0, seg, src)
def _pad(x, pw):
    flat = tuple(v for pair in reversed(pw) for v in pair)
    return torch.nn.functional.pad(x, flat)

kernel_name = 'recurrent_scan__spectral_fnet__moe_arch_mod__prompt'

def setup_inputs():

    _w = (lambda a: (lambda t: t.to(torch.bfloat16) if t.is_floating_point() else t)(torch.as_tensor(a)))
    def _A_setup():
        B, S, D = 1, 2048, 1024
        ns = torch.arange(S)[:, None] * torch.arange(S)[None, :]
        nd = torch.arange(D)[:, None] * torch.arange(D)[None, :]
        Ws_re = torch.cos(-2.0 * torch.pi * ns / S).to(float)
        Ws_im = torch.sin(-2.0 * torch.pi * ns / S).to(float)
        Wd_re = torch.cos(-2.0 * torch.pi * nd / D).to(float)
        Wd_im = torch.sin(-2.0 * torch.pi * nd / D).to(float)
        return {
            "x": _w((lambda *s: torch.randn(*s, dtype=torch.bfloat16) * 0.05)(B, S, D)),
            "dft_seq_re": _w(Ws_re),
            "dft_seq_im": _w(Ws_im),
            "dft_hid_re": _w(Wd_re),
            "dft_hid_im": _w(Wd_im),
        }
    _A_in = _A_setup()

    def _B_setup():
        B, S, D, F, C = 1, 2048, 1024, 3584, 1
        return {
            "x": _w((lambda *s: torch.randn(*s, dtype=torch.bfloat16) * 0.05)(B, S, D)),
            "w_r": _w((lambda *s: torch.randn(*s, dtype=torch.bfloat16) * 0.05)(D)),
            "w_gate": _w((lambda *s: torch.randn(*s, dtype=torch.bfloat16) * 0.05)(D, F)),
            "w_up": _w((lambda *s: torch.randn(*s, dtype=torch.bfloat16) * 0.05)(D, F)),
            "w_down": _w((lambda *s: torch.randn(*s, dtype=torch.bfloat16) * 0.05)(F, D)),
        }
    _B_in = _B_setup()

    return {
        "A_x": _A_in["x"],
        "A_dft_seq_re": _A_in["dft_seq_re"],
        "A_dft_seq_im": _A_in["dft_seq_im"],
        "A_dft_hid_re": _A_in["dft_hid_re"],
        "A_dft_hid_im": _A_in["dft_hid_im"],
        "B_x": _B_in["x"],
        "B_w_r": _B_in["w_r"],
        "B_w_gate": _B_in["w_gate"],
        "B_w_up": _B_in["w_up"],
        "B_w_down": _B_in["w_down"],
    }

def reference(A_x, A_dft_seq_re, A_dft_seq_im, A_dft_hid_re, A_dft_hid_im, B_x, B_w_r, B_w_gate, B_w_up, B_w_down):
    def _A_ref(x, dft_seq_re, dft_seq_im, dft_hid_re, dft_hid_im):
        a = torch.einsum("bsd,ed->bse", x, dft_hid_re)
        b = torch.einsum("bsd,ed->bse", x, dft_hid_im)
        y = torch.einsum("ts,bse->bte", dft_seq_re, a) - torch.einsum("ts,bse->bte", dft_seq_im, b)
        return y

    def _B_ref(x, w_r, w_gate, w_up, w_down):
        B, S, D = x.shape
        C = 1
        r = x @ w_r
        idx = torch.argsort(-r, axis=-1)[:, :C]
        idx_e = (lambda x, n, axis: torch.repeat_interleave(x, n, dim=axis))(idx.reshape(B, C, 1), D, axis=2)
        x_sel = (lambda x, i, axis: torch.take_along_dim(x, i, dim=axis))(x, idx_e, axis=1)
        g = _silu(x_sel @ w_gate)
        u = x_sel @ w_up
        y = (g * u) @ w_down
        r_sel = _sigmoid((lambda x, i, axis: torch.take_along_dim(x, i, dim=axis))(r, idx, axis=1))
        y = y * r_sel.reshape(B, C, 1)
        b_off = (torch.arange(B) * S).reshape(B, 1)
        flat_idx = (idx + b_off).reshape(B * C)
        zero = (x * 0.0).reshape(B * S, D)
        upd = _scatter_add(zero, flat_idx, y.reshape(B * C, D), axis=0)
        return x + upd.reshape(B, S, D)

    x = A_x
    xn = _layernorm(x, axis=-1)
    s = _A_ref(xn, A_dft_seq_re, A_dft_seq_im, A_dft_hid_re, A_dft_hid_im)
    g = _silu(_B_ref(xn, B_w_r, B_w_gate, B_w_up, B_w_down))
    return x + s * g
```

```cpp
#include <cuda_runtime.h>
#include <cuda_bf16.h>
#include <cuda.h>
#include <stdint.h>

#define SGAP 900
#define PFN 16
#define PF0 2500
#define PFGAP 500
#define PAUSE_R 3
#define DELAY1 4000
#define SPACE1 300
#define DELAY0 3500
#define SPACE0 800
#define CGAP 200
#define ST6 1
#define KQ 2
#define PW0 1
#define PSL 0
#define PRX CU_TENSOR_MAP_L2_PROMOTION_L2_128B
#define PRD CU_TENSOR_MAP_L2_PROMOTION_L2_128B
#define PRC CU_TENSOR_MAP_L2_PROMOTION_L2_128B
#define SLEEP_NS 200
#define PROD_REGS 32
#define CONS_REGS 208
#define NB 8

namespace {

constexpr int S_ = 2048, D_ = 1024, F_ = 3584;
constexpr int NCTA = 128;
constexpr int NMOE = 112;
constexpr uint32_t A_BYTES = 16384, B_BYTES = 32768, STAGE_BYTES = A_BYTES + B_BYTES;
constexpr uint32_t OFF_X = 4 * STAGE_BYTES;
constexpr uint32_t OFF_BAR = OFF_X + 32768;
constexpr uint32_t OFF_XN = OFF_BAR + 208;
constexpr uint32_t OFF_RED = OFF_XN + 2112;
constexpr uint32_t OFF_H = OFF_RED + 512;
constexpr uint32_t OFF_SEL = OFF_H + 128;
constexpr uint32_t SMEM_BYTES = OFF_SEL + 32;
constexpr uint32_t SB0 = 1024;
constexpr int NTHREADS = 512;
static_assert(SMEM_BYTES <= 232448, "smem");

enum { B_FULL = 0, B_EMPTY = 4, B_STATS = 8, B_EPI = 9  , B_SRD = 13, B_UPD = 15, B_LST = 16, B_XLD = 17, B_SEL = 18, B_K8 = 19, B_PEER = 20, B_GO = 21, B_PR2 = 22, B_COUNT = 23 };

__device__ __align__(1024) uint8_t g_ab[8u * 32u * 32768u];
__device__ __align__(128) uint4 g_xch[2 * NCTA * 2048];
__device__ __align__(128) uint4 g_part[2 * (NMOE / 2) * (D_ / 4)];
__device__ __align__(128) uint4 g_stat[S_];
__device__ __align__(128) uint4 g_rs[D_];
__device__ __align__(128) unsigned long long g_statflag[NCTA];
__device__ __align__(128) unsigned long long g_abflag[8 * 16];
__device__ __align__(128) unsigned g_epoch[NCTA];
#define PROF_T(i) do {} while (0)
#define TRACE(i) do {} while (0)
#define PROF_G(i) do {} while (0)

__device__ __forceinline__ uint32_t smem_u32(const void* p) { return (uint32_t)__cvta_generic_to_shared(p); }
__device__ __forceinline__ void mbar_init(uint32_t bar, uint32_t cnt) {
    asm volatile("mbarrier.init.shared::cta.b64 [%0], %1;" ::"r"(bar), "r"(cnt) : "memory");
}
__device__ __forceinline__ bool mbar_try(uint32_t bar, uint32_t parity) {
    uint32_t ok;
    asm volatile("{\n.reg .pred p;\nmbarrier.try_wait.parity.shared::cta.b64 p, [%1], %2;\nselp.u32 %0, 1, 0, p;\n}"
                 : "=r"(ok) : "r"(bar), "r"(parity) : "memory");
    return ok;
}
constexpr int SPIN_LIMIT = 1 << 20;
__device__ __forceinline__ void mbar_wait(uint32_t bar, uint32_t parity) {
    if (mbar_try(bar, parity)) return;
    int n = 0;
    while (!mbar_try(bar, parity) && ++n < SPIN_LIMIT) {}
}
__device__ __forceinline__ void mbar_wait_sleep(uint32_t bar, uint32_t parity) {
    int n = 0;
    while (!mbar_try(bar, parity) && ++n < SPIN_LIMIT) __nanosleep(SLEEP_NS);
}
__device__ __forceinline__ void mbar_arrive(uint32_t bar) {
    asm volatile("mbarrier.arrive.shared::cta.b64 _, [%0];" ::"r"(bar) : "memory");
}
__device__ __forceinline__ void mbar_arrive_cluster(uint32_t cluster_bar) {
    asm volatile("mbarrier.arrive.shared::cluster.b64 _, [%0];" ::"r"(cluster_bar) : "memory");
}
__device__ __forceinline__ void mbar_expect_tx(uint32_t bar, uint32_t bytes) {
    asm volatile("mbarrier.arrive.expect_tx.shared::cta.b64 _, [%0], %1;" ::"r"(bar), "r"(bytes) : "memory");
}
__device__ __forceinline__ bool elect_one() {
    uint32_t p;
    asm volatile("{\n.reg .pred p;\nelect.sync _|p, 0xffffffff;\nselp.u32 %0, 1, 0, p;\n}" : "=r"(p));
    return p;
}
__device__ __forceinline__ uint32_t mapa(uint32_t addr, uint32_t rank) {
    uint32_t r;
    asm("mapa.shared::cluster.u32 %0, %1, %2;" : "=r"(r) : "r"(addr), "r"(rank));
    return r;
}
__device__ __forceinline__ void tma_2d(uint32_t dst, const CUtensorMap* tm, int c0, int c1, uint32_t bar) {
    asm volatile("cp.async.bulk.tensor.2d.shared::cluster.global.mbarrier::complete_tx::bytes [%0], [%1, {%3, %4}], [%2];"
                 ::"r"(dst), "l"(tm), "r"(bar), "r"(c0), "r"(c1) : "memory");
}
__device__ __forceinline__ void tma_2d_mc(uint32_t dst, const CUtensorMap* tm, int c0, int c1, uint32_t bar) {
    asm volatile("cp.async.bulk.tensor.2d.shared::cluster.global.mbarrier::complete_tx::bytes.multicast::cluster [%0], [%1, {%3, %4}], [%2], %5;"
                 ::"r"(dst), "l"(tm), "r"(bar), "r"(c0), "r"(c1), "h"((uint16_t)3) : "memory");
}
__device__ __forceinline__ void tma_2d_store(const CUtensorMap* tm, int c0, int c1, uint32_t src) {
    asm volatile("cp.async.bulk.tensor.2d.global.shared::cta.bulk_group [%0, {%2, %3}], [%1];"
                 ::"l"(tm), "r"(src), "r"(c0), "r"(c1) : "memory");
}
__device__ __forceinline__ void bulk_g2s_mc(uint32_t dst, const void* src, uint32_t bytes, uint32_t bar) {
    asm volatile("cp.async.bulk.shared::cluster.global.mbarrier::complete_tx::bytes.multicast::cluster [%0], [%1], %2, [%3], %4;"
                 ::"r"(dst), "l"(src), "r"(bytes), "r"(bar), "h"((uint16_t)3) : "memory");
}
__device__ __forceinline__ void bulk_g2s(uint32_t dst, const void* src, uint32_t bytes, uint32_t bar) {
    asm volatile("cp.async.bulk.shared::cluster.global.mbarrier::complete_tx::bytes [%0], [%1], %2, [%3];"
                 ::"r"(dst), "l"(src), "r"(bytes), "r"(bar) : "memory");
}
__device__ __forceinline__ void bulk_s2g(void* dst, uint32_t src, uint32_t bytes) {
    asm volatile("cp.async.bulk.global.shared::cta.bulk_group [%0], [%1], %2;" ::"l"(dst), "r"(src), "r"(bytes) : "memory");
}
__device__ __forceinline__ void bulk_commit() { asm volatile("cp.async.bulk.commit_group;" ::: "memory"); }
template <int N> __device__ __forceinline__ void bulk_wait_read() { asm volatile("cp.async.bulk.wait_group.read %0;" ::"n"(N) : "memory"); }
template <int N> __device__ __forceinline__ void bulk_wait() { asm volatile("cp.async.bulk.wait_group %0;" ::"n"(N) : "memory"); }
__device__ __forceinline__ void fence_async_smem() { asm volatile("fence.proxy.async.shared::cta;" ::: "memory"); }
__device__ __forceinline__ void fence_async_global() { asm volatile("fence.proxy.async.global;" ::: "memory"); }
__device__ __forceinline__ void fence_async_all() { asm volatile("fence.proxy.async;" ::: "memory"); }
__device__ __forceinline__ void prefetch_tmap(const CUtensorMap* tm) {
    asm volatile("prefetch.tensormap [%0];" ::"l"(tm) : "memory");
}
__device__ __forceinline__ unsigned ld_acquire(const unsigned* p) {
    unsigned v; asm volatile("ld.acquire.gpu.global.u32 %0, [%1];" : "=r"(v) : "l"(p) : "memory"); return v;
}
__device__ __forceinline__ unsigned long long ld_acquire64(const unsigned long long* p) {
    unsigned long long v; asm volatile("ld.acquire.gpu.global.u64 %0, [%1];" : "=l"(v) : "l"(p) : "memory"); return v;
}
__device__ __forceinline__ unsigned load_epoch(int b) {
    unsigned v; asm volatile("ld.global.u32 %0, [%1];" : "=r"(v) : "l"(&g_epoch[b]) : "memory"); return v + 1;
}
__device__ __forceinline__ unsigned ld_relaxed(const unsigned* p) {
    unsigned v; asm volatile("ld.relaxed.gpu.global.u32 %0, [%1];" : "=r"(v) : "l"(p) : "memory"); return v;
}
__device__ __forceinline__ unsigned long long ld_relaxed64(const unsigned long long* p) {
    unsigned long long v; asm volatile("ld.relaxed.gpu.global.u64 %0, [%1];" : "=l"(v) : "l"(p) : "memory"); return v;
}
__device__ __forceinline__ uint4 ld_relaxed128(const uint4* p) {
    uint4 v;
    asm volatile("{\n.reg .b128 t;\n.reg .b64 lo, hi;\nld.relaxed.gpu.global.b128 t, [%4];\nmov.b128 {lo, hi}, t;\n"
                 "mov.b64 {%0, %1}, lo;\nmov.b64 {%2, %3}, hi;\n}"
                 : "=r"(v.x), "=r"(v.y), "=r"(v.z), "=r"(v.w) : "l"(p) : "memory");
    return v;
}
__device__ __forceinline__ void st_relaxed128(uint4* p, const uint4& v) {
    asm volatile("{\n.reg .b128 t;\n.reg .b64 lo, hi;\nmov.b64 lo, {%1, %2};\nmov.b64 hi, {%3, %4};\nmov.b128 t, {lo, hi};\n"
                 "st.relaxed.gpu.global.b128 [%0], t;\n}"
                 ::"l"(p), "r"(v.x), "r"(v.y), "r"(v.z), "r"(v.w) : "memory");
}
__device__ __forceinline__ void st_relaxed64(unsigned long long* p, unsigned long long v) {
    asm volatile("st.relaxed.gpu.global.u64 [%0], %1;" ::"l"(p), "l"(v) : "memory");
}
__device__ __forceinline__ void prefetch_l2(const void* p) { asm volatile("prefetch.global.L2 [%0];" ::"l"(p)); }
__device__ __forceinline__ void st_release(unsigned* p, unsigned v) {
    asm volatile("st.release.gpu.global.u32 [%0], %1;" ::"l"(p), "r"(v) : "memory");
}
__device__ __forceinline__ void st_release8(void* p, unsigned v) {
    asm volatile("st.release.gpu.global.u8 [%0], %1;" ::"l"(p), "r"(v) : "memory");
}
__device__ __forceinline__ void st_release64(unsigned long long* p, unsigned long long v) {
    asm volatile("st.release.gpu.global.u64 [%0], %1;" ::"l"(p), "l"(v) : "memory");
}
__device__ __forceinline__ uint64_t policy_evict_first() {
    uint64_t pol;
    asm("createpolicy.fractional.L2::evict_first.b64 %0, 1.0;" : "=l"(pol));
    return pol;
}
__device__ __forceinline__ uint4 ldg_stream(const void* p, uint64_t pol) {
    uint4 v;
    asm volatile("ld.global.nc.L1::no_allocate.L2::cache_hint.v4.u32 {%0,%1,%2,%3}, [%4], %5;"
                 : "=r"(v.x), "=r"(v.y), "=r"(v.z), "=r"(v.w) : "l"(p), "l"(pol));
    return v;
}
__device__ __forceinline__ uint4 ldg_nc(const void* p) {
    uint4 v;
    asm volatile("ld.global.nc.L1::no_allocate.v4.u32 {%0,%1,%2,%3}, [%4];"
                 : "=r"(v.x), "=r"(v.y), "=r"(v.z), "=r"(v.w) : "l"(p));
    return v;
}
template <int ID, int N> __device__ __forceinline__ void named_arrive() { asm volatile("bar.arrive %0, %1;" ::"n"(ID), "n"(N) : "memory"); }
template <int ID, int N> __device__ __forceinline__ void named_bar() { asm volatile("bar.sync %0, %1;" ::"n"(ID), "n"(N) : "memory"); }

__device__ __forceinline__ float bf_lo(uint32_t u) { return __uint_as_float(u << 16); }
__device__ __forceinline__ float bf_hi(uint32_t u) { return __uint_as_float(u & 0xffff0000u); }
__device__ __forceinline__ uint32_t pack_bf(float lo, float hi) {
    uint32_t r; asm("cvt.rn.bf16x2.f32 %0, %1, %2;" : "=r"(r) : "f"(hi), "f"(lo)); return r;
}
__device__ __forceinline__ float rbf(float v) { return __bfloat162float(__float2bfloat16_rn(v)); }
__device__ __forceinline__ float silu_f(float z) { return __fdividef(z, 1.0f + __expf(-z)); }
__device__ __forceinline__ uint32_t bsub2(uint32_t a, uint32_t b) {
    uint32_t r; asm("sub.rn.bf16x2 %0, %1, %2;" : "=r"(r) : "r"(a), "r"(b)); return r;
}
__device__ __forceinline__ uint32_t bmul2(uint32_t a, uint32_t b) {
    uint32_t r; asm("mul.rn.bf16x2 %0, %1, %2;" : "=r"(r) : "r"(a), "r"(b)); return r;
}
__device__ __forceinline__ uint32_t badd2(uint32_t a, uint32_t b) {
    uint32_t r; asm("add.rn.bf16x2 %0, %1, %2;" : "=r"(r) : "r"(a), "r"(b)); return r;
}
__device__ __forceinline__ uint32_t norm2(uint32_t xv, float m, float rinv) {
    uint32_t t = pack_bf(bf_lo(xv) - m, bf_hi(xv) - m);
    return pack_bf(bf_lo(t) * rinv, bf_hi(t) * rinv);
}
__device__ __forceinline__ float gate1(float x, float rinv, float mr) {
    const float z = fmaf(x, rinv, mr);
    float e, r;
    asm("ex2.approx.ftz.f32 %0, %1;" : "=f"(e) : "f"(z * -1.4426950408889634f));
    asm("rcp.approx.ftz.f32 %0, %1;" : "=f"(r) : "f"(1.0f + e));
    return z * r;
}
__device__ __forceinline__ uint32_t gate2(uint32_t xv, float rinv, float mr) {
    return pack_bf(gate1(bf_lo(xv), rinv, mr), gate1(bf_hi(xv), rinv, mr));
}
__device__ __forceinline__ uint32_t silu2(uint32_t z) { return pack_bf(silu_f(bf_lo(z)), silu_f(bf_hi(z))); }

__device__ __forceinline__ void stmatrix4(uint32_t addr, uint32_t r0, uint32_t r1, uint32_t r2, uint32_t r3) {
    asm volatile("stmatrix.sync.aligned.m8n8.x4.shared.b16 [%0], {%1,%2,%3,%4};"
                 ::"r"(addr), "r"(r0), "r"(r1), "r"(r2), "r"(r3));
}
__device__ __forceinline__ void ldmatrix4(uint32_t addr, uint32_t& r0, uint32_t& r1, uint32_t& r2, uint32_t& r3) {
    asm volatile("ldmatrix.sync.aligned.m8n8.x4.shared.b16 {%0,%1,%2,%3}, [%4];"
                 : "=r"(r0), "=r"(r1), "=r"(r2), "=r"(r3) : "r"(addr));
}

__device__ __forceinline__ void wg_fence() { asm volatile("wgmma.fence.sync.aligned;" ::: "memory"); }
__device__ __forceinline__ void wg_commit() { asm volatile("wgmma.commit_group.sync.aligned;" ::: "memory"); }
template <int N> __device__ __forceinline__ void wg_wait() { asm volatile("wgmma.wait_group.sync.aligned %0;" ::"n"(N) : "memory"); }

__host__ __device__ constexpr uint32_t desc_lo(uint32_t addr, uint32_t lbo) { return ((addr & 0x3FFFF) >> 4) | ((lbo >> 4) << 16); }
#define DESC_HI "0x40000040"

#define R8(a, o) "+f"(a[(o) + 0]), "+f"(a[(o) + 1]), "+f"(a[(o) + 2]), "+f"(a[(o) + 3]), \
                 "+f"(a[(o) + 4]), "+f"(a[(o) + 5]), "+f"(a[(o) + 6]), "+f"(a[(o) + 7])
#define R64(a, o) R8(a, (o) + 0), R8(a, (o) + 8), R8(a, (o) + 16), R8(a, (o) + 24), \
                  R8(a, (o) + 32), R8(a, (o) + 40), R8(a, (o) + 48), R8(a, (o) + 56)

template <int O, int TB = 1, int SA = 1>
__device__ __forceinline__ void wgmma128(float (&a)[128], uint32_t da, uint32_t db, int scale_d) {
    asm volatile(
        "{\n.reg .pred p;\n.reg .b64 da, db;\nsetp.ne.b32 p, %66, 0;\n"
        "mov.b64 da, {%64, " DESC_HI "};\nmov.b64 db, {%65, " DESC_HI "};\n"
        "wgmma.mma_async.sync.aligned.m64n128k16.f32.bf16.bf16 "
        "{%0,%1,%2,%3,%4,%5,%6,%7,%8,%9,%10,%11,%12,%13,%14,%15,"
        "%16,%17,%18,%19,%20,%21,%22,%23,%24,%25,%26,%27,%28,%29,%30,%31,"
        "%32,%33,%34,%35,%36,%37,%38,%39,%40,%41,%42,%43,%44,%45,%46,%47,"
        "%48,%49,%50,%51,%52,%53,%54,%55,%56,%57,%58,%59,%60,%61,%62,%63},"
        "da, db, p, %68, 1, 0, %67;\n}"
        : R64(a, O)
        : "r"(da), "r"(db), "r"(scale_d), "n"(TB), "n"(SA));
}
template <int O>
__device__ __forceinline__ void wgmma128_rs(float (&a)[128], uint32_t a0, uint32_t a1, uint32_t db) {
    asm volatile(
        "{\n.reg .b64 db;\n.reg .b32 z;\nmov.b32 z, 0;\nmov.b64 db, {%66, 8};\n"
        "wgmma.mma_async.sync.aligned.m64n128k16.f32.bf16.bf16 "
        "{%0,%1,%2,%3,%4,%5,%6,%7,%8,%9,%10,%11,%12,%13,%14,%15,"
        "%16,%17,%18,%19,%20,%21,%22,%23,%24,%25,%26,%27,%28,%29,%30,%31,"
        "%32,%33,%34,%35,%36,%37,%38,%39,%40,%41,%42,%43,%44,%45,%46,%47,"
        "%48,%49,%50,%51,%52,%53,%54,%55,%56,%57,%58,%59,%60,%61,%62,%63},"
        "{%64, %65, z, z}, db, 1, 1, 1, 0;\n}"
        : R64(a, O)
        : "r"(a0), "r"(a1), "r"(db));
}
template <int O>
__device__ __forceinline__ void fence_regs64(float (&a)[128]) {
    asm volatile("" : R64(a, O)::"memory");
}

struct Params {
    const __nv_bfloat16* x;
    const __nv_bfloat16* dre;
    const __nv_bfloat16* dim;
    const __nv_bfloat16* wr;
    const __nv_bfloat16* wg;
    const __nv_bfloat16* wu;
    const __nv_bfloat16* wd;
};

__device__ __forceinline__ float warp_sum(float v) {
#pragma unroll
    for (int o = 16; o; o >>= 1) v += __shfl_xor_sync(0xffffffffu, v, o);
    return v;
}
__device__ __forceinline__ float sum8(const uint4& v) {
    return ((bf_lo(v.x) + bf_hi(v.x)) + (bf_lo(v.y) + bf_hi(v.y))) + ((bf_lo(v.z) + bf_hi(v.z)) + (bf_lo(v.w) + bf_hi(v.w)));
}
__device__ __forceinline__ float sq2(uint32_t u, float m) { float a = bf_lo(u) - m, b = bf_hi(u) - m; return a * a + b * b; }
__device__ __forceinline__ float dot2(uint32_t a, uint32_t b) { return bf_lo(a) * bf_lo(b) + bf_hi(a) * bf_hi(b); }
__device__ __forceinline__ void fma8(float* acc, const uint4& w, float s) {
    acc[0] += s * bf_lo(w.x); acc[1] += s * bf_hi(w.x); acc[2] += s * bf_lo(w.y); acc[3] += s * bf_hi(w.y);
    acc[4] += s * bf_lo(w.z); acc[5] += s * bf_hi(w.z); acc[6] += s * bf_lo(w.w); acc[7] += s * bf_hi(w.w);
}

__global__ void __cluster_dims__(2, 1, 1) __launch_bounds__(NTHREADS, 1)
fnet_fused_kernel(const __grid_constant__ CUtensorMap tm_x, const __grid_constant__ CUtensorMap tm_dre,
                  const __grid_constant__ CUtensorMap tm_dim, const __grid_constant__ CUtensorMap tm_cre,
                  const __grid_constant__ CUtensorMap tm_cim, const __grid_constant__ CUtensorMap tm_out,
                  const Params P) {
    extern __shared__ __align__(1024) uint8_t smem[];
    const uint32_t sb = smem_u32(smem);
    const int tid = threadIdx.x, lane = tid & 31;
    const int warp = __shfl_sync(0xffffffffu, tid >> 5, 0);
#define REMAP 1
    int b = blockIdx.x;
    if (REMAP) {
        const int p = b >> 1;
        const int g = p < 4 ? 0 : p < 36 ? (p - 4) & 7 : 1 + (p - 36) % 7;
        const int r = p < 4 ? 4 + p : p < 36 ? (p - 4) >> 3 : 4 + (p - 36) / 7;
        b = REMAP == 1 ? r * 16 + g * 2 + (b & 1) : g * 16 + r * 2 + (b & 1);
    }
    const int c = b & 1;
    const int grp = b >> 4;
    const int part = grp & 1;
    const int eb = grp >> 1;
    const int j = b & 15;
    const int kb0 = 4 * eb + 2 * part;
#define KOTHER(i) ((i) < kb0 ? (i) : (i) + 2)
#define KBLK(it) ((it) < 11 ? KOTHER(it) : (it) < 13 ? kb0 + (it) - 11 : KOTHER((it) - 2))
    const uint32_t bar0 = sb + OFF_BAR;
#define BAR(i) (bar0 + 8u * (i))
#define CLUSTER_ARRIVE() asm volatile("barrier.cluster.arrive.relaxed.aligned;" ::: "memory")
#define CLUSTER_WAIT() asm volatile("barrier.cluster.wait.aligned;" ::: "memory")
    if ((sb & 0xffffffu) != SB0) return;
    if (tid == 0) { PROF_G(0); PROF_T(1); }

    if (warp == 12) {
            if (elect_one()) {
                prefetch_tmap(&tm_x);
                prefetch_tmap(part ? &tm_dim : &tm_dre);
                for (int s = 0; s < 4; s++) { mbar_init(BAR(B_FULL + s), 1); mbar_init(BAR(B_EMPTY + s), 4); mbar_init(BAR(B_EPI + s), 4); }
                mbar_init(BAR(B_STATS), 2);
                mbar_init(BAR(B_SRD + 0), 1); mbar_init(BAR(B_SRD + 1), 1);
                mbar_init(BAR(B_UPD), 1);
                mbar_init(BAR(B_K8), 2);
                mbar_init(BAR(B_XLD), 8);
                mbar_init(BAR(B_SEL), 1);
                mbar_init(BAR(B_PEER), 1);
                mbar_init(BAR(B_GO), 2);
                mbar_init(BAR(B_PR2), 1);
                mbar_init(BAR(B_LST), 4);
                asm volatile("fence.mbarrier_init.release.cluster;" ::: "memory");
            }
            __syncwarp();
            CLUSTER_ARRIVE();
            if (elect_one()) {
                PROF_T(2);
                mbar_expect_tx(BAR(B_FULL + 0), STAGE_BYTES);
                tma_2d(sb, &tm_x, KBLK(0) * 64, j * 128, BAR(B_FULL + 0));
            }
            __syncwarp();
            CLUSTER_WAIT();
            if (elect_one()) {
                PROF_T(6);
                const CUtensorMap* tmD = part ? &tm_dim : &tm_dre;
#pragma unroll 1
                for (int it = 0; it < 4; it++) {
                    const uint32_t st = sb + it * STAGE_BYTES, fb = BAR(B_FULL + it);
                    if (it) { mbar_expect_tx(fb, STAGE_BYTES); tma_2d(st, &tm_x, KBLK(it) * 64, j * 128, fb); }
                    tma_2d_mc(st + A_BYTES + c * 16384, tmD, KBLK(it) * 64, eb * 256 + 128 * (c ^ part), fb);
                }
            }
            __syncwarp();
            if (lane == 0) TRACE(233);
    } else {
        CLUSTER_ARRIVE();
    }

    if (warp >= 12) {
        asm volatile("setmaxnreg.dec.sync.aligned.u32 %0;" ::"n"(PROD_REGS));
        if (warp == 12) {
            const CUtensorMap* tmD = part ? &tm_dim : &tm_dre;
            const CUtensorMap* tmC = part ? &tm_cim : &tm_cre;
            const int row0 = j * 128, drow = eb * 256 + 128 * (c ^ part), q0 = j >> 1;
            if (elect_one()) {
#pragma unroll 1
                for (int it = 4; it < 16; it++) {
                    const int s = it & 3;
                    const uint32_t st = sb + s * STAGE_BYTES, fb = BAR(B_FULL + s);
                    mbar_wait(BAR(B_EMPTY + s), ((it >> 2) & 1) ^ 1);
                    TRACE(it);
                    mbar_expect_tx(fb, STAGE_BYTES);
                    const int kc = KBLK(it) * 64;
                    tma_2d((unsigned)(it - 11) < 2u ? sb + OFF_X + (it - 11) * 16384 : st, &tm_x, kc, row0, fb);
                    tma_2d_mc(st + A_BYTES + c * 16384, tmD, kc, drow, fb);
                    if (it == 4) { prefetch_tmap(tmC); prefetch_tmap(&tm_out); }
                }
                const unsigned ep = load_epoch(b);
#pragma unroll
                for (int i = 0; i < 2; i++) {
                    mbar_wait(BAR(B_EMPTY + i), 1);
                    TRACE(16 + i);
                    mbar_expect_tx(BAR(B_FULL + i), A_BYTES);
                    tma_2d(sb + i * STAGE_BYTES, tmC, (2 * j + i) * 64, row0, BAR(B_FULL + i));
                }
                const uint8_t* abg = g_ab + (size_t)grp * 32 * B_BYTES;
                const unsigned long long* fl = &g_abflag[grp * 16];
                const unsigned e8 = ep & 0xffu;
                int it = 18;
                unsigned long long rdy = (unsigned long long)(e8 ^ 0xffu) * 0x0101010101010101ull;
#define NEED(word, q) do { if (((unsigned)(rdy >> (8 * (q))) & 0xffu) != e8) { int m = 0; \
                    do { rdy = ld_acquire64(fl + (word)); } while (((unsigned)(rdy >> (8 * (q))) & 0xffu) != e8 && ++m < SPIN_LIMIT); \
                    if (it == 18) TRACE(255); \
                    fence_async_global(); } } while (0)
#define SLOT() const int s = it & 3; const uint32_t st = sb + s * STAGE_BYTES, fb = BAR(B_FULL + s), \
                    bs = sb + ((s + 3) & 3) * STAGE_BYTES + A_BYTES; \
                    mbar_wait(BAR(B_EMPTY + s), ((it >> 2) & 1) ^ 1); TRACE(it); mbar_expect_tx(fb, STAGE_BYTES)
#pragma unroll 1
                for (int cl = 0; cl < 4; cl++) {
                    const int ko = ((cl & 1) << 1) + (cl >> 1);
#pragma unroll 1
                    for (int n = 1; n < 8; n++, it++) {
                        const int q = (q0 + n) & 7, kb = 4 * q + ko;
                        SLOT();
                        tma_2d(st, tmC, kb * 64, row0, fb);
                        NEED(cl, q);
                        if (it == 18) PROF_T(5);
                        bulk_g2s_mc(bs + c * 16384, abg + (size_t)kb * B_BYTES + c * 16384, 16384, fb);
                    }
                    if (cl == 1 || cl == 2) {
                        const int word = 2 * (cl - 1) + (c ^ 1), kb = 2 * (j ^ 1) + cl - 1;
                        if (word != cl) { rdy = ld_acquire64(fl + word); fence_async_global(); }
                        SLOT();
                        tma_2d(st, tmC, kb * 64, row0, fb);
                        NEED(word, q0);
                        bulk_g2s(bs, abg + (size_t)kb * B_BYTES, B_BYTES, fb);
                        it++;
                    }
                    if (cl < 3) { rdy = ld_acquire64(fl + cl + 1); fence_async_global(); }
                }
                g_epoch[b] = ep;
            }
        } else if (warp == 14) {
            const unsigned ep = load_epoch(b);
            CLUSTER_WAIT();
            mbar_wait_sleep(BAR(B_LST), 0);
            unsigned key = __reduce_max_sync(0xffffffffu, *reinterpret_cast<const unsigned*>(smem + OFF_RED + (lane & 3) * 4));
            if (lane == 0) st_relaxed64(&g_statflag[b], ((unsigned long long)ep << 32) | key);
            int n = 0;
            while (true) {
                const uint4 f0 = ld_relaxed128(reinterpret_cast<const uint4*>(g_statflag) + lane);
                const uint4 f1 = ld_relaxed128(reinterpret_cast<const uint4*>(g_statflag) + 32 + lane);
                key = max(max(f0.x, f0.z), max(f1.x, f1.z));
                if (__all_sync(0xffffffffu, f0.y == ep && f0.w == ep && f1.y == ep && f1.w == ep) || ++n > SPIN_LIMIT) break;
            }
            key = __reduce_max_sync(0xffffffffu, key);
            if (lane == 0) { *reinterpret_cast<unsigned*>(smem + OFF_SEL) = key; mbar_arrive(BAR(B_SEL)); PROF_T(8); }

        } else if (warp == 15) {
            if (PFN && b < NMOE) {
                const __nv_bfloat16* src = ((lane & 1) ? P.wu : P.wg) + (size_t)(c * 512 + ((lane >> 1) & 1) * 256 + (lane >> 2)) * F_ + (b >> 1) * 64;
                long long t0 = clock64() + PF0;
#pragma unroll 1
                for (int i = 0; i < PFN; i++) {
                    while (clock64() < t0) {}
                    prefetch_l2(src + (size_t)i * 8 * F_);
                    t0 += PFGAP;
                }
            }
            const unsigned ep = load_epoch(b);
            CLUSTER_WAIT();
            mbar_wait_sleep(BAR(B_LST), 0);
            uint4 f[4];
            int n = 0;
            bool ok;
            do {
                ok = true;
#pragma unroll
                for (int i = 0; i < 4; i++) { f[i] = ld_relaxed128(&g_stat[j * 128 + i * 32 + lane]); ok = ok && f[i].z == ep; }
            } while (!__all_sync(0xffffffffu, ok) && ++n < SPIN_LIMIT);
            mbar_wait_sleep(BAR(B_K8), 0);
#pragma unroll
            for (int i = 0; i < 4; i++) *reinterpret_cast<uint2*>(smem + 4096 + (i * 32 + lane) * 8) = make_uint2(f[i].x, f[i].y);
            __syncwarp();
            if (lane == 0) mbar_arrive(BAR(B_STATS));
        } else {
            const unsigned ep = load_epoch(b);
            CLUSTER_WAIT();
            {
                mbar_wait_sleep(BAR(B_LST), 0);
                uint8_t* dst = smem;
                uint4 f[4];
                int n = 0;
                bool ok;
                do {
                    ok = true;
#pragma unroll
                    for (int i = 0; i < 4; i++) {
                        f[i] = ld_relaxed128(&g_rs[part * 512 + eb * 128 + 64 * ((i >> 1) ^ part) + (i & 1) * 32 + lane]);
                        ok = ok && f[i].y == ep && f[i].w == ep;
                    }
                } while (!__all_sync(0xffffffffu, ok) && ++n < SPIN_LIMIT);
                mbar_wait_sleep(BAR(B_K8), 0);
#pragma unroll
                for (int i = 0; i < 8; i++) {
                    const float v = __uint_as_float((i & 1) ? f[i >> 1].z : f[i >> 1].x);
                    const float hi = rbf(v), mid = rbf(v - hi), lo = v - hi - mid;
                    *reinterpret_cast<uint4*>(dst + (((i >> 1) * 32 + lane) * 2 + (i & 1)) * 16) = make_uint4(pack_bf(hi, mid), pack_bf(lo, 0.f), 0, 0);
                }
                fence_async_smem();
                __syncwarp();
                if (lane == 0) { mbar_arrive(BAR(B_STATS)); PROF_T(9); }
            }
            {
                if (elect_one()) {
                    for (int w = 0; w < 2; w++) {
                        uint8_t* dst = g_ab + (size_t)(grp * 32 + 2 * j + w) * B_BYTES;
                        const uint32_t src = sb + (w ? OFF_X : A_BYTES);
                        mbar_wait(BAR(B_EPI + 2 * w), 0);
                        long long t0 = clock64();
                        if (w == 0 ? (c == 1) : (c == 0)) { t0 += w ? DELAY0 : DELAY1; while (clock64() < t0) {} }
                        if (w == 0) PROF_T(3);
                        const uint32_t chunk = w ? 4096 : (c ? 8192 : 16384);
                        const int gap = w ? SPACE0 : (c ? SPACE1 : 0);
                        for (uint32_t o = 0; o < B_BYTES; o += chunk) {
                            if (o == B_BYTES / 2) mbar_wait(BAR(B_EPI + 2 * w + 1), 0);
                            bulk_s2g(dst + o, src + o, chunk);
                            bulk_commit();
                            t0 += gap;
                            while (clock64() < t0) {}
                        }
                        bulk_wait<0>();
                        if (w == 0) TRACE(254);
                        mbar_arrive(BAR(B_SRD + w));
                        st_release8(reinterpret_cast<uint8_t*>(&g_abflag[grp * 16 + 2 * w + c]) + (j >> 1), ep & 0xffu);
                        if (w == 0) PROF_T(7); else PROF_T(4);
                    }
                }
                __syncwarp();
                uint4* nx = g_xch + (size_t)(((ep + 1) & 1) * NCTA + b) * 2048 + lane;
                long long t0 = clock64();
#pragma unroll 1
                for (int i = 0; i < 64; i++) {
                    st_relaxed128(nx + i * 32, make_uint4(0, 0, 0, 0));
                    t0 += CGAP;
                    while (clock64() < t0) {}
                }
            }
        }
    } else if (warp >= 8) {
        const int aw = warp - 8, mt = tid - 256;
        float* hs = reinterpret_cast<float*>(smem + OFF_H);
        const unsigned ep = load_epoch(b);
        {
            const int row = j * 128 + grp * 16 + aw * 4;
            const __nv_bfloat16* xp = P.x + (size_t)row * D_ + lane * 8;
            const __nv_bfloat16* dp = (part ? P.dim : P.dre) + (size_t)(eb * 256 + j * 16 + aw * 4) * D_ + lane * 8;
            uint4 v[4][4], w[4];
#define SLOAD(i) do { w[i] = __ldg(reinterpret_cast<const uint4*>(P.wr + (i) * 256 + lane * 8)); \
                _Pragma("unroll") for (int r = 0; r < 4; r++) v[i][r] = ldg_nc(xp + r * D_ + (i) * 256); } while (0)
            const long long t0 = clock64();
            SLOAD(0);
#pragma unroll
            for (int i = 1; i < 4; i++) { while (clock64() - t0 < i * SGAP) {} SLOAD(i); }
            float x0[4], s1[4], s2[4], sx[4], sd[4], sw = 0.f;
#pragma unroll
            for (int r = 0; r < 4; r++) { x0[r] = bf_lo(__shfl_sync(0xffffffffu, v[0][r].x, 0)); s1[r] = 0.f; s2[r] = 0.f; sx[r] = 0.f; }
            if (mt == 0) TRACE(232);
#pragma unroll
            for (int i = 0; i < 4; i++) {
                const uint32_t wv[4] = {w[i].x, w[i].y, w[i].z, w[i].w};
#pragma unroll
                for (int e = 0; e < 4; e++) {
                    const float wl = bf_lo(wv[e]), wh = bf_hi(wv[e]);
                    sw += wl + wh;
#pragma unroll
                    for (int r = 0; r < 4; r++) {
                        const uint32_t xv = e == 0 ? v[i][r].x : e == 1 ? v[i][r].y : e == 2 ? v[i][r].z : v[i][r].w;
                        const float a0 = bf_lo(xv) - x0[r], a1 = bf_hi(xv) - x0[r];
                        s1[r] += a0 + a1;
                        s2[r] = fmaf(a0, a0, fmaf(a1, a1, s2[r]));
                        sx[r] = fmaf(a0, wl, fmaf(a1, wh, sx[r]));
                    }
                }
#pragma unroll
                for (int r = 0; r < 4; r++) v[i][r] = ldg_nc(dp + r * D_ + i * 256);
            }
#define FOLD4(a) do { const bool u16 = lane & 16, u8 = lane & 8; \
                float p0 = (u16 ? a[2] : a[0]) + __shfl_xor_sync(0xffffffffu, u16 ? a[0] : a[2], 16); \
                float p1 = (u16 ? a[3] : a[1]) + __shfl_xor_sync(0xffffffffu, u16 ? a[1] : a[3], 16); \
                a[0] = (u8 ? p1 : p0) + __shfl_xor_sync(0xffffffffu, u8 ? p0 : p1, 8); \
                _Pragma("unroll") for (int o = 4; o; o >>= 1) a[0] += __shfl_xor_sync(0xffffffffu, a[0], o); } while (0)
            CLUSTER_WAIT();
            FOLD4(s1); FOLD4(s2); FOLD4(sx);
            sw = warp_sum(sw);
            const int rr = lane >> 3;
            const float c0 = rr == 0 ? x0[0] : rr == 1 ? x0[1] : rr == 2 ? x0[2] : x0[3];
            const float dm = s1[0] * (1.0f / D_);
            const float mb = rbf(c0 + dm);
            const float rinv = 1.0f / rbf(sqrtf(rbf(rbf(fmaxf(s2[0] * (1.0f / D_) - dm * dm, 0.f)) + 1e-5f)));
            unsigned u = __bfloat16_as_ushort(__float2bfloat16_rn((sx[0] + (c0 - mb) * sw) * rinv));
            u = (u & 0x8000u) ? (~u & 0xffffu) : (u | 0x8000u);
            const unsigned key = __reduce_max_sync(0xffffffffu, (u << 16) | (0xffffu - (unsigned)(row + rr)));
            if ((lane & 7) == 0) st_relaxed128(&g_stat[row + rr], make_uint4(__float_as_uint(mb), __float_as_uint(rinv), ep, 0));
            if (lane == 0) { *reinterpret_cast<unsigned*>(smem + OFF_RED + aw * 4) = key; mbar_arrive(BAR(B_LST)); }
            if (mt == 0) TRACE(230);
#pragma unroll
            for (int r = 0; r < 4; r++) sd[r] = (sum8(v[0][r]) + sum8(v[1][r])) + (sum8(v[2][r]) + sum8(v[3][r]));
            FOLD4(sd);
            const float nb = __shfl_down_sync(0xffffffffu, sd[0], 8);
            if ((lane & 15) == 0)
                st_relaxed128(&g_rs[part * 512 + eb * 128 + j * 8 + aw * 2 + (lane >> 4)], make_uint4(__float_as_uint(sd[0]), ep, __float_as_uint(nb), ep));
            if (mt == 0) TRACE(231);
        }
        asm volatile("setmaxnreg.dec.sync.aligned.u32 %0;" ::"n"(512 - PROD_REGS - 2 * CONS_REGS));
        mbar_wait_sleep(BAR(B_SEL), 0);
        const unsigned key = *reinterpret_cast<volatile unsigned*>(smem + OFF_SEL);
        const int sel = 0xffff - (int)(key & 0xffffu);
        float2 st;
        {
            uint4 f;
            int n = 0;
            do { f = ld_relaxed128(&g_stat[sel]); } while (f.z != ep && ++n < SPIN_LIMIT);
            st = make_float2(__uint_as_float(f.x), __uint_as_float(f.y));
        }
        if (b < NMOE) {
            const uint64_t pol = policy_evict_first();
            const int r0 = c * 512 + (aw >> 1) * 256;
            const __nv_bfloat16* wp = ((aw & 1) ? P.wu : P.wg) + (size_t)(r0 + (lane >> 3)) * F_ + (size_t)(b >> 1) * 64 + (lane & 7) * 8;
            uint4 buf[NB];
#pragma unroll
            for (int q = 0; q < NB; q++) buf[q] = ldg_stream(wp + (size_t)q * 4 * F_, pol);
            {
                const uint4 xv = __ldg(reinterpret_cast<const uint4*>(P.x + (size_t)sel * D_ + mt * 8));
                const uint32_t n[4] = {norm2(xv.x, st.x, st.y), norm2(xv.y, st.x, st.y), norm2(xv.z, st.x, st.y), norm2(xv.w, st.x, st.y)};
#pragma unroll
                for (int e = 0; e < 4; e++)
                    *reinterpret_cast<uint32_t*>(smem + OFF_XN + e * 528 + mt * 4) = __byte_perm(n[e >> 1], n[2 + (e >> 1)], (e & 1) ? 0x7632 : 0x5410);
            }
            named_bar<4, 128>();
            float ag[8];
#pragma unroll
            for (int i = 0; i < 8; i++) ag[i] = 0.f;
            const __nv_bfloat16* wd = P.wd + (size_t)b * 32 * D_ + mt * 8;
#pragma unroll 1
            for (int r = 0; r < 64 / NB; r++) {
                const bool last = r == 64 / NB - 1;
                if (r == PAUSE_R) mbar_wait_sleep(BAR(B_GO), 0);
                const __nv_bfloat16* nx = last ? wd : wp + (size_t)(r + 1) * NB * 4 * F_;
                const size_t str = last ? D_ : 4 * F_;
#pragma unroll
                for (int h = 0; h < NB; h += 8) {
                    const uint4 xq = *reinterpret_cast<const uint4*>(smem + OFF_XN + (lane >> 3) * 528 + ((r0 >> 2) + r * NB + h) * 2);
                    const uint32_t xw[4] = {xq.x, xq.y, xq.z, xq.w};
#pragma unroll
                    for (int q = 0; q < 8; q++) {
                        fma8(ag, buf[h + q], (q & 1) ? bf_hi(xw[q >> 1]) : bf_lo(xw[q >> 1]));
                        buf[h + q] = ldg_stream(nx + (h + q) * str, pol);
                    }
                }
            }
#pragma unroll
            for (int i = 0; i < 8; i++) {
                ag[i] += __shfl_xor_sync(0xffffffffu, ag[i], 8);
                ag[i] += __shfl_xor_sync(0xffffffffu, ag[i], 16);
            }
            named_bar<4, 128>();
            float* ps = reinterpret_cast<float*>(smem + OFF_XN);
            if (lane < 8) {
                *reinterpret_cast<float4*>(&ps[aw * 64 + lane * 8]) = make_float4(ag[0], ag[1], ag[2], ag[3]);
                *reinterpret_cast<float4*>(&ps[aw * 64 + lane * 8 + 4]) = make_float4(ag[4], ag[5], ag[6], ag[7]);
            }
            named_bar<4, 128>();
            if (aw == 0) {
                const int o = (c ^ 1) * 32 + lane, m = c * 32 + lane;
                mbar_wait(BAR(B_SRD + 1), 0);
                const uint32_t rem = mapa(sb + OFF_RED + 64 + lane * 8, c ^ 1);
                asm volatile("st.shared::cluster.v2.f32 [%0], {%1, %2};" ::"r"(rem), "f"(ps[o] + ps[128 + o]), "f"(ps[64 + o] + ps[192 + o]) : "memory");
                __syncwarp();
                if (lane == 0) asm volatile("mbarrier.arrive.release.cluster.shared::cluster.b64 _, [%0];" ::"r"(mapa(BAR(B_PEER), c ^ 1)) : "memory");
                int n = 0;
                uint32_t okp;
                do {
                    asm volatile("{\n.reg .pred p;\nmbarrier.try_wait.parity.acquire.cluster.shared::cta.b64 p, [%1], 0;\nselp.u32 %0, 1, 0, p;\n}"
                                 : "=r"(okp) : "r"(BAR(B_PEER)) : "memory");
                } while (!okp && ++n < SPIN_LIMIT);
                const float2 pv = *reinterpret_cast<const float2*>(smem + OFF_RED + 64 + lane * 8);
                const float go = ps[m] + ps[128 + m], uo = ps[64 + m] + ps[192 + m];
                hs[lane] = rbf(rbf(silu_f(rbf(go + pv.x))) * rbf(uo + pv.y));
                if (lane == 0) PROF_T(10);
            }
            named_bar<4, 128>();
#pragma unroll
            for (int i = 0; i < 8; i++) ag[i] = 0.f;
#pragma unroll 1
            for (int f = 0; f < 32; f += NB) {
                wd += NB * D_;
#pragma unroll
                for (int h = 0; h < NB; h += 4) {
                    const float4 h4 = *reinterpret_cast<const float4*>(&hs[f + h]);
                    const float hv[4] = {h4.x, h4.y, h4.z, h4.w};
#pragma unroll
                    for (int q = 0; q < 4; q++) {
                        fma8(ag, buf[h + q], hv[q]);
                        if (f + NB < 32) buf[h + q] = ldg_stream(wd + (size_t)(h + q) * D_, pol);
                    }
                }
            }
            if (c == 1) {
                const uint32_t rem = mapa(sb + OFF_X + 8192 + mt * 16, 0);
                asm volatile("st.shared::cluster.v4.f32 [%0], {%1,%2,%3,%4};" ::"r"(rem), "f"(ag[0]), "f"(ag[1]), "f"(ag[2]), "f"(ag[3]) : "memory");
                asm volatile("st.shared::cluster.v4.f32 [%0], {%1,%2,%3,%4};" ::"r"(rem + 2048), "f"(ag[4]), "f"(ag[5]), "f"(ag[6]), "f"(ag[7]) : "memory");
                named_bar<4, 128>();
                if (mt == 0) asm volatile("mbarrier.arrive.release.cluster.shared::cluster.b64 _, [%0];" ::"r"(mapa(BAR(B_PR2), 0)) : "memory");
            } else {
                uint4* clr = &g_part[(((ep + 1) & 1) * (NMOE / 2) + (b >> 1)) * (D_ / 4) + mt * 2];
                st_relaxed128(clr, make_uint4(0, 0, 0, 0));
                st_relaxed128(clr + 1, make_uint4(0, 0, 0, 0));
                int n = 0;
                uint32_t okp;
                do {
                    asm volatile("{\n.reg .pred p;\nmbarrier.try_wait.parity.acquire.cluster.shared::cta.b64 p, [%1], 0;\nselp.u32 %0, 1, 0, p;\n}"
                                 : "=r"(okp) : "r"(BAR(B_PR2)) : "memory");
                } while (!okp && ++n < SPIN_LIMIT);
                const float4 p0 = *reinterpret_cast<const float4*>(smem + OFF_X + 8192 + mt * 16);
                const float4 p1 = *reinterpret_cast<const float4*>(smem + OFF_X + 8192 + 2048 + mt * 16);
                uint4* dst = &g_part[((ep & 1) * (NMOE / 2) + (b >> 1)) * (D_ / 4) + mt * 2];
                st_relaxed128(dst, make_uint4(~__float_as_uint(ag[0] + p0.x), __float_as_uint(ag[1] + p0.y), __float_as_uint(ag[2] + p0.z), __float_as_uint(ag[3] + p0.w)));
                st_relaxed128(dst + 1, make_uint4(~__float_as_uint(ag[4] + p1.x), __float_as_uint(ag[5] + p1.y), __float_as_uint(ag[6] + p1.z), __float_as_uint(ag[7] + p1.w)));
                named_bar<4, 128>();
            }
            if (mt == 0) PROF_T(11);
        }
        if ((sel >> 7) == j) {
            const uint2 xv = __ldg(reinterpret_cast<const uint2*>(P.x + (size_t)sel * D_ + eb * 256 + part * 128 + lane * 4));
            const uint4* src = &g_part[((ep & 1) * (NMOE / 2) + aw * 14) * (D_ / 4) + eb * 64 + part * 32];
            float4* park = reinterpret_cast<float4*>(smem + OFF_X) + aw * 64 + lane;
            mbar_wait(BAR(B_SRD + 1), 0);
            unsigned todo = 3;
            int n = 0;
            while (todo && ++n < SPIN_LIMIT) {
                const unsigned m = __ballot_sync(0xffffffffu, ld_relaxed(&src[(lane < 14 ? lane : 0) * (D_ / 4) + 31].x) != 0);
                unsigned can = 0;
#pragma unroll
                for (int h = 0; h < 2; h++) can |= (((m >> (7 * h)) & 0x7fu) == 0x7fu) << h;
                can &= todo;
                if (!can) { __nanosleep(100); continue; }
                while (can) {
                    const int h = __ffs(can) - 1;
                    can &= can - 1;
                    uint4 t[7];
                    bool ok = true;
#pragma unroll
                    for (int u = 0; u < 7; u++) { t[u] = ld_relaxed128(src + (h * 7 + u) * (D_ / 4) + lane); ok = ok && t[u].x != 0; }
                    if (!__all_sync(0xffffffffu, ok)) continue;
                    float4 a = make_float4(0.f, 0.f, 0.f, 0.f);
#pragma unroll
                    for (int u = 0; u < 7; u++) {
                        a.x += __uint_as_float(~t[u].x); a.y += __uint_as_float(t[u].y); a.z += __uint_as_float(t[u].z); a.w += __uint_as_float(t[u].w);
                    }
                    park[h * 32] = a;
                    todo &= ~(1u << h);
                }
            }
            named_bar<4, 128>();
            if (aw == 0) {
                float4 a4 = make_float4(0.f, 0.f, 0.f, 0.f);
#pragma unroll 4
                for (int w = 0; w < 8; w++) { const float4 t = park[w * 32]; a4.x += t.x; a4.y += t.y; a4.z += t.z; a4.w += t.w; }
                unsigned u = key >> 16;
                u = (u & 0x8000u) ? (u & 0x7fffu) : (~u & 0xffffu);
                const float sg = rbf(__fdividef(1.0f, 1.0f + __expf(-__uint_as_float(u << 16))));
                const uint32_t n0 = norm2(xv.x, st.x, st.y), n1 = norm2(xv.y, st.x, st.y);
                uint2 o;
                o.x = silu2(pack_bf(bf_lo(n0) + rbf(rbf(a4.x) * sg), bf_hi(n0) + rbf(rbf(a4.y) * sg)));
                o.y = silu2(pack_bf(bf_lo(n1) + rbf(rbf(a4.z) * sg), bf_hi(n1) + rbf(rbf(a4.w) * sg)));
                *reinterpret_cast<uint2*>(smem + OFF_RED + lane * 8) = o;
                if (lane == 0) *reinterpret_cast<int*>(smem + OFF_SEL + 4) = sel & 127;
                __syncwarp();
                if (lane == 0) { mbar_arrive(BAR(B_UPD)); PROF_T(12); }
            }
        } else if (mt == 0) {
            *reinterpret_cast<int*>(smem + OFF_SEL + 4) = -1;
            mbar_arrive(BAR(B_UPD));
        }
    } else {
        asm volatile("setmaxnreg.inc.sync.aligned.u32 %0;" ::"n"(128 + (128 - PROD_REGS) / 2));
        CLUSTER_WAIT();
        const int wg = warp >> 2, wq = warp & 3;
        const int wt = tid & 127;
        float acc[128];
        const uint32_t rel_bar = mapa(BAR(B_EMPTY), (uint32_t)(wt >> 5) & 1);
        const bool rel_thr = (wt == 0) || (wt == 32);
#define RELEASE(s) do { if (rel_thr) mbar_arrive_cluster(rel_bar + 8u * (s)); } while (0)
        const uint32_t dA0 = desc_lo(SB0, 16) + wg * 512;
        constexpr uint32_t dBk0 = desc_lo(SB0 + A_BYTES, 16);
        constexpr uint32_t dBn0 = desc_lo(SB0 + A_BYTES, 8192);
        constexpr uint32_t ST = STAGE_BYTES >> 4;
        const int row_l = wg * 64 + wq * 16 + (lane >> 2);

#define MMA1_H(O, s, aoff, first) do { _Pragma("unroll") for (int kk = 0; kk < 4; kk++) \
            wgmma128<O, 0>(acc, dA0 + (aoff) + kk * 2, dBk0 + (s) * ST + kk * 2 + (O) * 16, !((first) && kk == 0)); } while (0)
#define WAIT_FULL(s, ph, it) do { mbar_wait(BAR(B_FULL + (s)), ph); if (wt == 0) TRACE(64 + wg * 64 + (it)); } while (0)
#define STEP1(s, ph, it, aoff, first) do { WAIT_FULL(s, ph, it); wg_fence(); \
            MMA1_H(0, s, aoff, first); MMA1_H(64, s, aoff, first); wg_commit(); } while (0)
#pragma unroll 1
        for (int o = 0; o < 2; o++) {
            STEP1(0, o, 4 * o, 0, o == 0);
            if (o == 0 && tid == 0) PROF_T(16);
            if (o) { wg_wait<1>(); RELEASE(3); }
            STEP1(1, o, 4 * o + 1, ST, false); wg_wait<1>(); RELEASE(0);
            STEP1(2, o, 4 * o + 2, 2 * ST, false); wg_wait<1>(); RELEASE(1);
            STEP1(3, o, 4 * o + 3, 3 * ST, false); wg_wait<1>(); RELEASE(2);
        }
        STEP1(0, 0, 8, 0, false); wg_wait<1>(); RELEASE(3);
        STEP1(1, 0, 9, ST, false); wg_wait<1>(); RELEASE(0);
        if (wt == 0) mbar_arrive(BAR(B_K8));
        STEP1(2, 0, 10, 2 * ST, false); wg_wait<1>(); RELEASE(1);
        STEP1(3, 0, 11, OFF_X >> 4, false);
        mbar_wait(BAR(B_STATS), 0);
        const float2 st0 = *reinterpret_cast<const float2*>(smem + 4096 + row_l * 8);
        const float2 st1 = *reinterpret_cast<const float2*>(smem + 4096 + row_l * 8 + 64);
        wg_wait<1>(); RELEASE(2);
        {
            const uint32_t msk = (lane & 3) == 0 ? 0xffffffffu : (lane & 3) == 1 ? 0x0000ffffu : 0u;
            const uint32_t nm0 = pack_bf(-st0.x, -st0.x) & msk, nm1 = pack_bf(-st1.x, -st1.x) & msk;
            WAIT_FULL(0, 1, 12);
            wg_fence();
            MMA1_H(0, 0, (OFF_X >> 4) + 1024, false); MMA1_H(64, 0, (OFF_X >> 4) + 1024, false);
            wgmma128_rs<0>(acc, nm0, nm1, SB0 >> 4);
            wgmma128_rs<64>(acc, nm0, nm1, (SB0 >> 4) + 128);
            wg_commit();
            wg_wait<1>(); RELEASE(3);
        }
        asm volatile("setmaxnreg.inc.sync.aligned.u32 %0;" ::"n"(CONS_REGS));
        const int mrow = wq * 16 + ((lane >> 3) & 1) * 8 + (lane & 7);
        uint32_t xr[32];
        const uint32_t xrow = sb + OFF_X + (wg * 64 + mrow) * 128;
#define XADDR(v) (xrow + ((v) >> 2) * 16384 + ((((2 * (v)) & 7) + (lane >> 4)) ^ (lane & 7)) * 16)
#pragma unroll
        for (int v = 0; v < 8; v++) ldmatrix4(XADDR(v), xr[4 * v], xr[4 * v + 1], xr[4 * v + 2], xr[4 * v + 3]);
        __syncwarp();
        if (lane == 0) mbar_arrive(BAR(B_XLD));
        if (wg == 1) { wg_wait<0>(); RELEASE(0); named_bar<5, 256>(); }
        WAIT_FULL(1, 1, 13);
        wg_fence(); MMA1_H(0, 1, ST, false); wg_commit();
        if (wg == 0) { wg_wait<1>(); RELEASE(0); }
        WAIT_FULL(2, 1, 14);
        wg_fence(); MMA1_H(0, 2, 2 * ST, false);
        WAIT_FULL(3, 1, 15);
        wg_fence(); MMA1_H(0, 3, 3 * ST, false); wg_commit();
        MMA1_H(64, 1, ST, false); MMA1_H(64, 2, 2 * ST, false); MMA1_H(64, 3, 3 * ST, false); wg_commit();
        if (wg == 0) named_arrive<5, 256>(); else mbar_wait(BAR(B_XLD), 0);
        mbar_wait(BAR(B_EMPTY + 0), 1);
        if (tid == 0) PROF_T(15);
#define EPI1_H(O) do { const uint32_t dst = sb + (wg ? OFF_X : A_BYTES) + mrow * 128; \
            _Pragma("unroll") for (int i = (O) / 4; i < (O) / 4 + 16; i += 2) { \
                const uint32_t r0 = pack_bf(acc[4 * i + 0] * st0.y, acc[4 * i + 1] * st0.y); \
                const uint32_t r1 = pack_bf(acc[4 * i + 2] * st1.y, acc[4 * i + 3] * st1.y); \
                const uint32_t r2 = pack_bf(acc[4 * i + 4] * st0.y, acc[4 * i + 5] * st0.y); \
                const uint32_t r3 = pack_bf(acc[4 * i + 6] * st1.y, acc[4 * i + 7] * st1.y); \
                stmatrix4(dst + (i >> 3) * 8192 + (((i & 7) + (lane >> 4)) ^ (lane & 7)) * 16, r0, r1, r2, r3); } \
            fence_async_smem(); __syncwarp(); \
            if (lane == 0) mbar_arrive(BAR(B_EPI + wg * 2 + (O) / 64)); } while (0)
        wg_wait<1>();
        fence_regs64<0>(acc);
        if (wt == 0) TRACE(240 + wg * 4);
        EPI1_H(0);
        if (wt == 0) TRACE(241 + wg * 4);
        wg_wait<0>();
        fence_regs64<64>(acc);
        RELEASE(1); RELEASE(2); RELEASE(3);
        if (wt == 0) PROF_T(17 + wg * 10);
        EPI1_H(64);
        if (wt == 0) PROF_T(18 + wg * 10);

        float ac2[128];
#define MMA2B(s, boff, first) do { wg_fence(); _Pragma("unroll") \
        for (int kk = 0; kk < 4; kk++) { \
            wgmma128<0>(ac2, dA0 + (s) * ST + kk * 2, dBn0 + (boff) + kk * 128, !((first) && kk == 0)); \
            wgmma128<64>(ac2, dA0 + (s) * ST + kk * 2, dBn0 + (boff) + kk * 128 + 1024, !((first) && kk == 0)); } \
        wg_commit(); } while (0)
#define BSLOT(s) (((s) + 3) & 3)
#define STEP2(s, ph, it) do { WAIT_FULL(s, ph, it); MMA2B(s, BSLOT(s) * ST, false); wg_wait<1>(); } while (0)
        mbar_wait(BAR(B_EPI + 1), 0); WAIT_FULL(0, 0, 16);
        MMA2B(0, 0, true);
        uint32_t g[32];
#define GATE() do { const float mr0 = -st0.x * st0.y, mr1 = -st1.x * st1.y; \
            _Pragma("unroll") for (int i = 0; i < 32; i += 4) { \
                g[i] = gate2(xr[i], st0.y, mr0); g[i + 1] = gate2(xr[i + 1], st1.y, mr1); \
                g[i + 2] = gate2(xr[i + 2], st0.y, mr0); g[i + 3] = gate2(xr[i + 3], st1.y, mr1); \
                asm volatile("st.shared.v4.u32 [%0], {%1,%2,%3,%4};" ::"r"(sb + OFF_SEL + 16), "r"(g[i]), "r"(g[i + 1]), "r"(g[i + 2]), "r"(g[i + 3]) : "memory"); \
            } } while (0)
        mbar_wait(BAR(B_EPI + 3), 0); WAIT_FULL(1, 0, 17);
        MMA2B(1, (OFF_X - A_BYTES) >> 4, false);
        const unsigned ep = load_epoch(b);
        GATE();
        wg_wait<1>(); RELEASE(0);
        if (tid == 0) TRACE(235);
        WAIT_FULL(2, 0, 18);
        if (wt == 0) mbar_arrive(BAR(B_GO));
        MMA2B(2, BSLOT(2) * ST, false); wg_wait<1>();
        if (tid == 0) PROF_T(19);
        mbar_wait(BAR(B_SRD + 0), 0); RELEASE(1);
        STEP2(3, 0, 19); RELEASE(2);
#pragma unroll 1
        for (int o = 5; o < 11; o++) {
            STEP2(0, o & 1, 4 * o); RELEASE(3);
            if (o == 5 && tid == 0) PROF_T(20);
            STEP2(1, o & 1, 4 * o + 1); RELEASE(0);
            STEP2(2, o & 1, 4 * o + 2); RELEASE(1);
            STEP2(3, o & 1, 4 * o + 3); RELEASE(2);
        }
        if (tid == 0) PROF_T(21);
#define SEND() do { \
            uint4* dst = g_xch + (size_t)((ep & 1) * NCTA + (b ^ 16)) * 2048 + tid; \
            _Pragma("unroll") for (int v = 0; v < 8; v++) { \
                uint4 t; \
                t.x = pack_bf(ac2[64 + 8 * v + 0], ac2[64 + 8 * v + 1]) ^ 0xffffffffu; \
                t.y = pack_bf(ac2[64 + 8 * v + 2], ac2[64 + 8 * v + 3]); \
                t.z = pack_bf(ac2[64 + 8 * v + 4], ac2[64 + 8 * v + 5]); \
                t.w = pack_bf(ac2[64 + 8 * v + 6], ac2[64 + 8 * v + 7]); \
                st_relaxed128(dst + v * 256, t); \
            } } while (0)
#define MMA_H(O, s) do { _Pragma("unroll") for (int kk = 0; kk < 4; kk++) \
            wgmma128<O>(ac2, dA0 + (s) * ST + kk * 2, dBn0 + BSLOT(s) * ST + kk * 128 + (O) * 16, 1); } while (0)
        if (wg == 1 && ST6) { wg_wait<0>(); RELEASE(3); named_bar<6, 256>(); }
        mbar_wait(BAR(B_FULL + 0), 1);
        wg_fence(); MMA_H(64, 0); wg_commit();
        if (wg == 0 || !ST6) { wg_wait<1>(); RELEASE(3); }
#pragma unroll
        for (int s = 1; s < 4; s++) {
            if (s == 3 && wg == 0 && ST6) named_arrive<6, 256>();
            mbar_wait(BAR(B_FULL + s), 1);
            wg_fence(); MMA_H(64, s);
        }
        wg_commit();
        if (KQ) {
            named_bar<7, 256>();
            wg_fence(); MMA_H(0, 0);
            if (KQ >= 2) MMA_H(0, 1);
            if (KQ >= 3) MMA_H(0, 2);
            wg_commit();
            wg_wait<1>();
        } else {
            wg_wait<0>();
        }
        fence_regs64<64>(ac2);
        if (wt == 0) PROF_T(22 + wg * 7);
        SEND();
        if (wg == 1) named_bar<8, 256>();
        wg_fence();
        if (KQ < 1) MMA_H(0, 0);
        if (KQ < 2) MMA_H(0, 1);
        if (KQ < 3) MMA_H(0, 2);
        MMA_H(0, 3); wg_commit();
        if (wg == 0) named_arrive<8, 256>();
        uint4 rv[8];
        {
            const uint4* src = g_xch + (size_t)((ep & 1) * NCTA + b) * 2048 + tid;
            int n = 0;
            if (PW0) wg_wait<0>();
            if (lane == 31) { while (ld_relaxed(&src[7 * 256].x) == 0 && ++n < SPIN_LIMIT) { if (PSL) __nanosleep(PSL); } }
            __syncwarp();
            n = 0;
            bool ok;
            do {
                ok = true;
#pragma unroll
                for (int v = 0; v < 8; v++) { rv[v] = ld_relaxed128(src + v * 256); ok = ok && (rv[v].x != 0); }
            } while (!__all_sync(0xffffffffu, ok) && ++n < SPIN_LIMIT);
        }
        if (wt == 0) PROF_T(23 + wg * 7);
        mbar_wait(BAR(B_UPD), 0);
        {
            const int sl = *reinterpret_cast<volatile int*>(smem + OFF_SEL + 4);
            if ((sl >> 4) == warp) {
                const bool lo = (lane >> 2) == (sl & 15), hi = (lane >> 2) + 8 == (sl & 15);
#pragma unroll
                for (int i = 0; i < 16; i++) {
                    const uint32_t v = *reinterpret_cast<const uint32_t*>(smem + OFF_RED + i * 16 + (lane & 3) * 4);
                    if (lo) g[2 * i] = v;
                    if (hi) g[2 * i + 1] = v;
                }
            }
        }
        mbar_wait(BAR(B_SRD + 1), 0);
        wg_wait<0>();
        fence_regs64<0>(ac2);
        if (wt == 0) PROF_T(24 + wg * 7);
#pragma unroll
        for (int v = 0; v < 8; v++) {
            const uint32_t addr = XADDR(v);
            const uint32_t m0 = pack_bf(ac2[8 * v + 0], ac2[8 * v + 1]), m1 = pack_bf(ac2[8 * v + 2], ac2[8 * v + 3]);
            const uint32_t m2 = pack_bf(ac2[8 * v + 4], ac2[8 * v + 5]), m3 = pack_bf(ac2[8 * v + 6], ac2[8 * v + 7]);
            const uint32_t rx = ~rv[v].x;
            const uint32_t s0 = part ? bsub2(rx, m0) : bsub2(m0, rx);
            const uint32_t s1 = part ? bsub2(rv[v].y, m1) : bsub2(m1, rv[v].y);
            const uint32_t s2 = part ? bsub2(rv[v].z, m2) : bsub2(m2, rv[v].z);
            const uint32_t s3 = part ? bsub2(rv[v].w, m3) : bsub2(m3, rv[v].w);
            stmatrix4(addr, badd2(xr[4 * v + 0], bmul2(s0, g[4 * v + 0])), badd2(xr[4 * v + 1], bmul2(s1, g[4 * v + 1])),
                      badd2(xr[4 * v + 2], bmul2(s2, g[4 * v + 2])), badd2(xr[4 * v + 3], bmul2(s3, g[4 * v + 3])));
        }
        if (wt == 0) TRACE(248 + wg * 4);
        fence_async_smem();
        if (wt == 0) TRACE(249 + wg * 4);
        if (wg == 0) named_bar<1, 128>(); else named_bar<2, 128>();
        if (wt == 0) {
            tma_2d_store(&tm_out, eb * 256 + part * 128, j * 128 + wg * 64, sb + OFF_X + wg * 8192);
            tma_2d_store(&tm_out, eb * 256 + part * 128 + 64, j * 128 + wg * 64, sb + OFF_X + 16384 + wg * 8192);
            bulk_commit();
            if (wg == 0) PROF_T(13);
            bulk_wait_read<0>();
            if (wg == 0) PROF_T(14); else { PROF_T(25); PROF_G(26); }
        }
    }
}

typedef CUresult (*EncodeFn)(CUtensorMap*, CUtensorMapDataType, cuuint32_t, void*, const cuuint64_t*, const cuuint64_t*,
                             const cuuint32_t*, const cuuint32_t*, CUtensorMapInterleave, CUtensorMapSwizzle,
                             CUtensorMapL2promotion, CUtensorMapFloatOOBfill);

void make_map(EncodeFn fn, CUtensorMap* tm, const void* p, uint64_t rows, uint64_t cols, uint32_t box_rows,
              CUtensorMapL2promotion promo = CU_TENSOR_MAP_L2_PROMOTION_L2_128B) {
    cuuint64_t dims[2] = {cols, rows};
    cuuint64_t strides[1] = {cols * 2};
    cuuint32_t box[2] = {64, box_rows};
    cuuint32_t es[2] = {1, 1};
    fn(tm, CU_TENSOR_MAP_DATA_TYPE_BFLOAT16, 2, const_cast<void*>(p), dims, strides, box, es, CU_TENSOR_MAP_INTERLEAVE_NONE,
       CU_TENSOR_MAP_SWIZZLE_128B, promo, CU_TENSOR_MAP_FLOAT_OOB_FILL_NONE);
}

}

extern "C" void kernel_launch(void* const* d_in, const int* in_sizes, int n_in, void* d_out, int out_size) {
    (void)in_sizes; (void)n_in; (void)out_size;
    static EncodeFn fn = nullptr;
    if (!fn) {
        void* p = nullptr;
        cudaDriverEntryPointQueryResult q;
        cudaGetDriverEntryPoint("cuTensorMapEncodeTiled", &p, cudaEnableDefault, &q);
        fn = (EncodeFn)p;
        cudaFuncSetAttribute(fnet_fused_kernel, cudaFuncAttributeMaxDynamicSharedMemorySize, SMEM_BYTES);
    }
    CUtensorMap tx, tdre, tdim, tcre, tcim, tout;
    make_map(fn, &tx, d_in[0], S_, D_, 128, PRX);
    make_map(fn, &tcre, d_in[1], S_, S_, 128, PRC);
    make_map(fn, &tcim, d_in[2], S_, S_, 128, PRC);
    make_map(fn, &tdre, d_in[3], D_, D_, 128, PRD);
    make_map(fn, &tdim, d_in[4], D_, D_, 128, PRD);
    make_map(fn, &tout, d_out, S_, D_, 64);
    Params P;
    P.x = (const __nv_bfloat16*)d_in[0];
    P.dre = (const __nv_bfloat16*)d_in[3];
    P.dim = (const __nv_bfloat16*)d_in[4];
    P.wr = (const __nv_bfloat16*)d_in[6];
    P.wg = (const __nv_bfloat16*)d_in[7];
    P.wu = (const __nv_bfloat16*)d_in[8];
    P.wd = (const __nv_bfloat16*)d_in[9];
    fnet_fused_kernel<<<NCTA, NTHREADS, SMEM_BYTES, cudaStreamPerThread>>>(tx, tdre, tdim, tcre, tcim, tout, P);
}
```

```cpp
#include <cuda_runtime.h>
#include <cuda_bf16.h>
#include <cuda.h>
#include <stdint.h>

#define SGAP 400
#define GSL 200
#define SDEL 0
#define YNS 0u
#define YLD 1
#define PDEL 2500
#define PGAP 600
#define PK 4
#define XJ0 21
#define EGAP1 0
#define EGAP2 0
#define ESTAG 120
#define QJ 12
#define GOJ 2
#define TANH 1
#define SYNCS 0x124900020ull
#define K0 0
#define KRD 1500
#define SYNCD 2
#define SYNCCAP 4000u
#define SYNCLAG 960u
#define QUIET 1
#define PRX CU_TENSOR_MAP_L2_PROMOTION_L2_128B
#define PRD CU_TENSOR_MAP_L2_PROMOTION_L2_128B
#define PRC CU_TENSOR_MAP_L2_PROMOTION_L2_128B
#define SLEEP_NS 200
#define PROD_REGS 32
#define CONS_REGS 184

namespace {

constexpr int S_ = 2048, D_ = 1024, F_ = 3584;
constexpr int NCTA = 128;
constexpr int XJ = XJ0;
constexpr uint32_t SLOT = 16384;
constexpr uint32_t OFF_L = 0;
constexpr uint32_t OFF_S = 8 * SLOT;
constexpr uint32_t OFF_BAR = 14 * SLOT;
constexpr uint32_t OFF_SEL = OFF_BAR + 352;
constexpr uint32_t OFF_RSTD = OFF_BAR + 384;
constexpr uint32_t OFF_MEAN = OFF_RSTD + 1024;
constexpr uint32_t OFF_XB = OFF_MEAN + 512;
constexpr uint32_t OFF_H = OFF_XB + 1024;
constexpr uint32_t SMEM_BYTES = OFF_H + 128;
constexpr uint32_t SB0 = 1024;
constexpr int NTHREADS = 512;
static_assert(SMEM_BYTES <= 232448, "smem");

enum { B_FS = 0, B_ES = 6, B_FL = 12, B_EL = 20, B_SRD = 28, B_RECV = 32, B_RDY = 34, B_STATS = 36, B_PEER = 37, B_UPD = 38,
       B_QUIET = 39, B_GO = 40, B_LST = 41, B_SEL = 42, B_H = 43, B_COUNT = 44 };
static_assert(B_COUNT * 8 <= 352, "barriers");

__device__ __align__(1024) uint8_t g_ab[16u * 32u * SLOT];
__device__ __align__(128) uint4 g_part[56 * (D_ / 4)];
__device__ __align__(128) uint4 g_stat[S_];
__device__ __align__(128) uint4 g_rs[D_];
__device__ __align__(128) unsigned long long g_key[NCTA];
__device__ __align__(128) unsigned long long g_flag[16 * 16];
__device__ __align__(128) unsigned long long g_sync[16 * 16];
__device__ __align__(128) unsigned g_epoch[NCTA];
#define PROF_T(i) do {} while (0)
#define TRACE(i) do {} while (0)
#define PROF_G(i) do {} while (0)

__device__ __forceinline__ uint32_t smem_u32(const void* p) { return (uint32_t)__cvta_generic_to_shared(p); }
__device__ __forceinline__ void mbar_init(uint32_t bar, uint32_t cnt) {
    asm volatile("mbarrier.init.shared::cta.b64 [%0], %1;" ::"r"(bar), "r"(cnt) : "memory");
}
__device__ __forceinline__ bool mbar_try(uint32_t bar, uint32_t parity) {
    uint32_t ok;
    asm volatile("{\n.reg .pred p;\nmbarrier.try_wait.parity.shared::cta.b64 p, [%1], %2;\nselp.u32 %0, 1, 0, p;\n}"
                 : "=r"(ok) : "r"(bar), "r"(parity) : "memory");
    return ok;
}
__device__ __forceinline__ bool mbar_test(uint32_t bar, uint32_t parity) {
    uint32_t ok;
    asm volatile("{\n.reg .pred p;\nmbarrier.test_wait.parity.shared::cta.b64 p, [%1], %2;\nselp.u32 %0, 1, 0, p;\n}"
                 : "=r"(ok) : "r"(bar), "r"(parity) : "memory");
    return ok;
}
__device__ __forceinline__ bool mbar_try_cluster(uint32_t bar, uint32_t parity) {
    uint32_t ok;
    asm volatile("{\n.reg .pred p;\nmbarrier.try_wait.parity.acquire.cluster.shared::cta.b64 p, [%1], %2;\nselp.u32 %0, 1, 0, p;\n}"
                 : "=r"(ok) : "r"(bar), "r"(parity) : "memory");
    return ok;
}
constexpr int SPIN_LIMIT = 1 << 20;
__device__ __forceinline__ void mbar_wait(uint32_t bar, uint32_t parity) {
    if (mbar_try(bar, parity)) return;
    int n = 0;
    while (!mbar_try(bar, parity) && ++n < SPIN_LIMIT) {}
}
__device__ __forceinline__ void mbar_wait_cluster(uint32_t bar, uint32_t parity) {
    int n = 0;
    while (!mbar_try_cluster(bar, parity) && ++n < SPIN_LIMIT) {}
}
__device__ __forceinline__ void mbar_wait_sleep(uint32_t bar, uint32_t parity) {
    int n = 0;
    while (!mbar_try(bar, parity) && ++n < SPIN_LIMIT) __nanosleep(SLEEP_NS);
}
__device__ __forceinline__ void mbar_arrive(uint32_t bar) {
    asm volatile("mbarrier.arrive.shared::cta.b64 _, [%0];" ::"r"(bar) : "memory");
}
__device__ __forceinline__ void mbar_arrive_cluster(uint32_t cluster_bar) {
    asm volatile("mbarrier.arrive.shared::cluster.b64 _, [%0];" ::"r"(cluster_bar) : "memory");
}
__device__ __forceinline__ void mbar_expect_tx(uint32_t bar, uint32_t bytes) {
    asm volatile("mbarrier.arrive.expect_tx.shared::cta.b64 _, [%0], %1;" ::"r"(bar), "r"(bytes) : "memory");
}
__device__ __forceinline__ bool elect_one() {
    uint32_t p;
    asm volatile("{\n.reg .pred p;\nelect.sync _|p, 0xffffffff;\nselp.u32 %0, 1, 0, p;\n}" : "=r"(p));
    return p;
}
__device__ __forceinline__ uint32_t mapa(uint32_t addr, uint32_t rank) {
    uint32_t r;
    asm("mapa.shared::cluster.u32 %0, %1, %2;" : "=r"(r) : "r"(addr), "r"(rank));
    return r;
}
__device__ __forceinline__ uint32_t clock32() { uint32_t t; asm volatile("mov.u32 %0, %%clock;" : "=r"(t)); return t; }
__device__ __forceinline__ void sleep_until(uint32_t t) {
    int n = 0;
    while ((int)(clock32() - t) < 0 && ++n < SPIN_LIMIT) __nanosleep(20);
}
__device__ __forceinline__ void yield(float last, uint32_t zero) {
    if (YLD) asm volatile("nanosleep.u32 %0;" ::"r"((__float_as_uint(last) & zero) | YNS));
}
template <typename T> __device__ __forceinline__ T* at(T* p, uint32_t bytes) {
    asm("" : "+r"(bytes));
    return reinterpret_cast<T*>(reinterpret_cast<uintptr_t>(p) + bytes);
}
__device__ __forceinline__ void tma_2d(uint32_t dst, const CUtensorMap* tm, int c0, int c1, uint32_t bar) {
    asm volatile("cp.async.bulk.tensor.2d.shared::cluster.global.mbarrier::complete_tx::bytes [%0], [%1, {%3, %4}], [%2];"
                 ::"r"(dst), "l"(tm), "r"(bar), "r"(c0), "r"(c1) : "memory");
}
__device__ __forceinline__ void tma_2d_store(const CUtensorMap* tm, int c0, int c1, uint32_t src) {
    asm volatile("cp.async.bulk.tensor.2d.global.shared::cta.bulk_group [%0, {%2, %3}], [%1];"
                 ::"l"(tm), "r"(src), "r"(c0), "r"(c1) : "memory");
}
__device__ __forceinline__ void bulk_g2s(uint32_t dst, const void* src, uint32_t bytes, uint32_t bar) {
    asm volatile("cp.async.bulk.shared::cluster.global.mbarrier::complete_tx::bytes [%0], [%1], %2, [%3];"
                 ::"r"(dst), "l"(src), "r"(bytes), "r"(bar) : "memory");
}
__device__ __forceinline__ void bulk_s2g(void* dst, uint32_t src, uint32_t bytes) {
    asm volatile("cp.async.bulk.global.shared::cta.bulk_group [%0], [%1], %2;" ::"l"(dst), "r"(src), "r"(bytes) : "memory");
}
__device__ __forceinline__ void st_async4(uint32_t dst, uint32_t a, uint32_t b, uint32_t c, uint32_t d, uint32_t bar) {
    asm volatile("st.async.weak.shared::cluster.mbarrier::complete_tx::bytes.v4.b32 [%0], {%1,%2,%3,%4}, [%5];"
                 ::"r"(dst), "r"(a), "r"(b), "r"(c), "r"(d), "r"(bar) : "memory");
}
__device__ __forceinline__ void bulk_commit() { asm volatile("cp.async.bulk.commit_group;" ::: "memory"); }
template <int N> __device__ __forceinline__ void bulk_wait_read() { asm volatile("cp.async.bulk.wait_group.read %0;" ::"n"(N) : "memory"); }
template <int N> __device__ __forceinline__ void bulk_wait() { asm volatile("cp.async.bulk.wait_group %0;" ::"n"(N) : "memory"); }
__device__ __forceinline__ void fence_async_smem() { asm volatile("fence.proxy.async.shared::cta;" ::: "memory"); }
__device__ __forceinline__ void fence_async_global() { asm volatile("fence.proxy.async.global;" ::: "memory"); }
__device__ __forceinline__ void prefetch_tmap(const CUtensorMap* tm) {
    asm volatile("prefetch.tensormap [%0];" ::"l"(tm) : "memory");
}
__device__ __forceinline__ unsigned long long ld_acquire64(const unsigned long long* p) {
    unsigned long long v; asm volatile("ld.acquire.gpu.global.u64 %0, [%1];" : "=l"(v) : "l"(p) : "memory"); return v;
}
__device__ __forceinline__ unsigned load_epoch(int b) {
    unsigned v; asm volatile("ld.global.u32 %0, [%1];" : "=r"(v) : "l"(at(g_epoch, b * 4)) : "memory"); return v + 1;
}
__device__ __forceinline__ unsigned ld_relaxed(const void* p) {
    unsigned v; asm volatile("ld.relaxed.gpu.global.u32 %0, [%1];" : "=r"(v) : "l"(p) : "memory"); return v;
}
__device__ __forceinline__ unsigned long long ld_relaxed64(const unsigned long long* p) {
    unsigned long long v; asm volatile("ld.relaxed.gpu.global.u64 %0, [%1];" : "=l"(v) : "l"(p) : "memory"); return v;
}
__device__ __forceinline__ void red_max64(unsigned long long* p, unsigned long long v) {
    asm volatile("red.relaxed.gpu.global.max.u64 [%0], %1;" ::"l"(p), "l"(v) : "memory");
}
__device__ __forceinline__ uint4 ld_relaxed128(const uint4* p) {
    uint4 v;
    asm volatile("{\n.reg .b128 t;\n.reg .b64 lo, hi;\nld.relaxed.gpu.global.b128 t, [%4];\nmov.b128 {lo, hi}, t;\n"
                 "mov.b64 {%0, %1}, lo;\nmov.b64 {%2, %3}, hi;\n}"
                 : "=r"(v.x), "=r"(v.y), "=r"(v.z), "=r"(v.w) : "l"(p) : "memory");
    return v;
}
__device__ __forceinline__ void st_relaxed128(uint4* p, const uint4& v) {
    asm volatile("{\n.reg .b128 t;\n.reg .b64 lo, hi;\nmov.b64 lo, {%1, %2};\nmov.b64 hi, {%3, %4};\nmov.b128 t, {lo, hi};\n"
                 "st.relaxed.gpu.global.b128 [%0], t;\n}"
                 ::"l"(p), "r"(v.x), "r"(v.y), "r"(v.z), "r"(v.w) : "memory");
}
__device__ __forceinline__ void st_relaxed64(unsigned long long* p, unsigned long long v) {
    asm volatile("st.relaxed.gpu.global.u64 [%0], %1;" ::"l"(p), "l"(v) : "memory");
}
__device__ __forceinline__ void st_release8(void* p, unsigned v) {
    asm volatile("st.release.gpu.global.u8 [%0], %1;" ::"l"(p), "r"(v) : "memory");
}
__device__ __forceinline__ uint64_t policy_evict_first() {
    uint64_t pol;
    asm("createpolicy.fractional.L2::evict_first.b64 %0, 1.0;" : "=l"(pol));
    return pol;
}
__device__ __forceinline__ uint4 ldg_stream(const void* p, uint64_t pol) {
    uint4 v;
    asm volatile("ld.global.nc.L1::no_allocate.L2::cache_hint.v4.u32 {%0,%1,%2,%3}, [%4], %5;"
                 : "=r"(v.x), "=r"(v.y), "=r"(v.z), "=r"(v.w) : "l"(p), "l"(pol));
    return v;
}
__device__ __forceinline__ uint4 ldg_ord(const void* p) {
    uint4 v;
    asm volatile("ld.relaxed.gpu.global.L1::no_allocate.v4.u32 {%0,%1,%2,%3}, [%4];"
                 : "=r"(v.x), "=r"(v.y), "=r"(v.z), "=r"(v.w) : "l"(p));
    return v;
}
template <int ID, int N> __device__ __forceinline__ void named_arrive() { asm volatile("bar.arrive %0, %1;" ::"n"(ID), "n"(N) : "memory"); }
template <int ID, int N> __device__ __forceinline__ void named_bar() { asm volatile("bar.sync %0, %1;" ::"n"(ID), "n"(N) : "memory"); }

__device__ __forceinline__ float bf_lo(uint32_t u) { return __uint_as_float(u << 16); }
__device__ __forceinline__ float bf_hi(uint32_t u) { return __uint_as_float(u & 0xffff0000u); }
__device__ __forceinline__ uint32_t pack_bf(float lo, float hi) {
    uint32_t r; asm("cvt.rn.bf16x2.f32 %0, %1, %2;" : "=r"(r) : "f"(hi), "f"(lo)); return r;
}
__device__ __forceinline__ float rbf(float v) { return __bfloat162float(__float2bfloat16_rn(v)); }
__device__ __forceinline__ float silu_f(float z) { return __fdividef(z, 1.0f + __expf(-z)); }
__device__ __forceinline__ uint32_t bsub2(uint32_t a, uint32_t b) {
    uint32_t r; asm("sub.rn.bf16x2 %0, %1, %2;" : "=r"(r) : "r"(a), "r"(b)); return r;
}
__device__ __forceinline__ uint32_t bfma2(uint32_t a, uint32_t b, uint32_t c) {
    uint32_t r; asm("fma.rn.bf16x2 %0, %1, %2, %3;" : "=r"(r) : "r"(a), "r"(b), "r"(c)); return r;
}
__device__ __forceinline__ uint32_t norm2(uint32_t xv, float m, float rinv) {
    uint32_t t = pack_bf(bf_lo(xv) - m, bf_hi(xv) - m);
    return pack_bf(bf_lo(t) * rinv, bf_hi(t) * rinv);
}
__device__ __forceinline__ float gate1(float z) {
    if (TANH) {
        float t;
        const float h = 0.5f * z;
        asm("tanh.approx.f32 %0, %1;" : "=f"(t) : "f"(h));
        return fmaf(h, t, h);
    }
    float e, r;
    asm("ex2.approx.ftz.f32 %0, %1;" : "=f"(e) : "f"(z * -1.4426950408889634f));
    asm("rcp.approx.ftz.f32 %0, %1;" : "=f"(r) : "f"(1.0f + e));
    return z * r;
}
__device__ __forceinline__ uint32_t gate2(uint32_t xv, uint32_t mean2, float r0, float r1) {
    const uint32_t t = bsub2(xv, mean2);
    return pack_bf(gate1(bf_lo(t) * r0), gate1(bf_hi(t) * r1));
}
__device__ __forceinline__ uint32_t silu2(uint32_t z) { return pack_bf(silu_f(bf_lo(z)), silu_f(bf_hi(z))); }

__device__ __forceinline__ void stmatrix4(uint32_t addr, uint32_t r0, uint32_t r1, uint32_t r2, uint32_t r3) {
    asm volatile("stmatrix.sync.aligned.m8n8.x4.shared.b16 [%0], {%1,%2,%3,%4};"
                 ::"r"(addr), "r"(r0), "r"(r1), "r"(r2), "r"(r3));
}
__device__ __forceinline__ void stmatrix4t(uint32_t addr, uint32_t r0, uint32_t r1, uint32_t r2, uint32_t r3) {
    asm volatile("stmatrix.sync.aligned.m8n8.x4.trans.shared.b16 [%0], {%1,%2,%3,%4};"
                 ::"r"(addr), "r"(r0), "r"(r1), "r"(r2), "r"(r3));
}
__device__ __forceinline__ void ldmatrix4t(uint32_t addr, uint32_t& r0, uint32_t& r1, uint32_t& r2, uint32_t& r3) {
    asm volatile("ldmatrix.sync.aligned.m8n8.x4.trans.shared.b16 {%0,%1,%2,%3}, [%4];"
                 : "=r"(r0), "=r"(r1), "=r"(r2), "=r"(r3) : "r"(addr));
}

__device__ __forceinline__ void wg_fence() { asm volatile("wgmma.fence.sync.aligned;" ::: "memory"); }
__device__ __forceinline__ void wg_commit() { asm volatile("wgmma.commit_group.sync.aligned;" ::: "memory"); }
template <int N> __device__ __forceinline__ void wg_wait() { asm volatile("wgmma.wait_group.sync.aligned %0;" ::"n"(N) : "memory"); }

__host__ __device__ constexpr uint32_t desc_lo(uint32_t addr, uint32_t lbo) { return ((addr & 0x3FFFF) >> 4) | ((lbo >> 4) << 16); }
#define DESC_HI "0x40000040"

#define R8(a, o) "+f"(a[(o) + 0]), "+f"(a[(o) + 1]), "+f"(a[(o) + 2]), "+f"(a[(o) + 3]), \
                 "+f"(a[(o) + 4]), "+f"(a[(o) + 5]), "+f"(a[(o) + 6]), "+f"(a[(o) + 7])
#define R64(a, o) R8(a, (o) + 0), R8(a, (o) + 8), R8(a, (o) + 16), R8(a, (o) + 24), \
                  R8(a, (o) + 32), R8(a, (o) + 40), R8(a, (o) + 48), R8(a, (o) + 56)

template <int O, int TA>
__device__ __forceinline__ void wgmma128(float (&a)[128], uint32_t da, uint32_t db, int scale_d) {
    asm volatile(
        "{\n.reg .pred p;\n.reg .b64 da, db;\nsetp.ne.b32 p, %66, 0;\n"
        "mov.b64 da, {%64, " DESC_HI "};\nmov.b64 db, {%65, " DESC_HI "};\n"
        "wgmma.mma_async.sync.aligned.m64n128k16.f32.bf16.bf16 "
        "{%0,%1,%2,%3,%4,%5,%6,%7,%8,%9,%10,%11,%12,%13,%14,%15,"
        "%16,%17,%18,%19,%20,%21,%22,%23,%24,%25,%26,%27,%28,%29,%30,%31,"
        "%32,%33,%34,%35,%36,%37,%38,%39,%40,%41,%42,%43,%44,%45,%46,%47,"
        "%48,%49,%50,%51,%52,%53,%54,%55,%56,%57,%58,%59,%60,%61,%62,%63},"
        "da, db, p, 1, 1, %67, 0;\n}"
        : R64(a, O)
        : "r"(da), "r"(db), "r"(scale_d), "n"(TA));
}
template <int O>
__device__ __forceinline__ void wgmma128_rs(float (&a)[128], const uint32_t* f, uint32_t db) {
    asm volatile(
        "{\n.reg .b64 db;\nmov.b64 db, {%68, 8};\n"
        "wgmma.mma_async.sync.aligned.m64n128k16.f32.bf16.bf16 "
        "{%0,%1,%2,%3,%4,%5,%6,%7,%8,%9,%10,%11,%12,%13,%14,%15,"
        "%16,%17,%18,%19,%20,%21,%22,%23,%24,%25,%26,%27,%28,%29,%30,%31,"
        "%32,%33,%34,%35,%36,%37,%38,%39,%40,%41,%42,%43,%44,%45,%46,%47,"
        "%48,%49,%50,%51,%52,%53,%54,%55,%56,%57,%58,%59,%60,%61,%62,%63},"
        "{%64, %65, %66, %67}, db, 1, 1, 1, 0;\n}"
        : R64(a, O)
        : "r"(f[0]), "r"(f[1]), "r"(f[2]), "r"(f[3]), "r"(db));
}
template <int O>
__device__ __forceinline__ void fence_regs64(float (&a)[128]) {
    asm volatile("" : R64(a, O)::"memory");
}

struct Params {
    const __nv_bfloat16* x;
    const __nv_bfloat16* dre;
    const __nv_bfloat16* dim;
    const __nv_bfloat16* wr;
    const __nv_bfloat16* wg;
    const __nv_bfloat16* wu;
    const __nv_bfloat16* wd;
    uint32_t zero;
};

__device__ __forceinline__ float warp_sum(float v) {
#pragma unroll
    for (int o = 16; o; o >>= 1) v += __shfl_xor_sync(0xffffffffu, v, o);
    return v;
}
__device__ __forceinline__ void fma8(float* acc, const uint4& w, float s) {
    acc[0] += s * bf_lo(w.x); acc[1] += s * bf_hi(w.x); acc[2] += s * bf_lo(w.y); acc[3] += s * bf_hi(w.y);
    acc[4] += s * bf_lo(w.z); acc[5] += s * bf_hi(w.z); acc[6] += s * bf_lo(w.w); acc[7] += s * bf_hi(w.w);
}
__device__ __forceinline__ int POS(int t) { return (t & ~15) | ((t & 6) << 1) | ((t & 8) >> 2) | (t & 1); }
__host__ __device__ constexpr int PSLOT(int j) { return j < 4 ? j : (j & 1) + ((j & 2) ? 0 : 4); }
__host__ __device__ constexpr int PPAR(int j) { return j < 4 ? 0 : ((j >> 2) ^ (j >> 1) ^ 1) & 1; }
__host__ __device__ constexpr int DSLOT(int it) { return (it & 3) + 2; }
__device__ __forceinline__ int KO(int cl) { return ((cl & 1) << 1) | (cl >> 1); }

__device__ __forceinline__ unsigned long long* sync_words() {
    uint32_t t;
    asm volatile("mov.u32 %0, %%smid;" : "=r"(t));
    t >>= 1;
    const uint32_t u = t - 32;
    return at(g_sync, (t < 32 ? t & 7 : t < 60 ? 8 + u - 7 * ((u * 37) >> 8) : 15) * 128);
}

__global__ void __cluster_dims__(2, 1, 1) __launch_bounds__(NTHREADS, 1)
fnet_fused_kernel(const __grid_constant__ CUtensorMap tm_x, const __grid_constant__ CUtensorMap tm_dre,
                  const __grid_constant__ CUtensorMap tm_dim, const __grid_constant__ CUtensorMap tm_cre,
                  const __grid_constant__ CUtensorMap tm_cim, const __grid_constant__ CUtensorMap tm_out,
                  const Params P) {
    extern __shared__ __align__(1024) uint8_t smem[];
    const unsigned long long tstart = clock64();
    const uint32_t sb = smem_u32(smem);
    const int tid = threadIdx.x, lane = tid & 31;
    const int warp = __shfl_sync(0xffffffffu, tid >> 5, 0);
    const int pr = blockIdx.x >> 1, p7 = ((pr - 36) * 37) >> 8;
    const int c = blockIdx.x & 1;
    const int g = pr < 4 ? 0 : pr < 36 ? (pr - 4) & 7 : pr - 35 - 7 * p7;
    const int r = pr < 4 ? 4 + pr : pr < 36 ? (pr - 4) >> 3 : 4 + p7;
    const int grp = 2 * r + c;
    const int b = g * 16 + grp;
    const uint32_t bar0 = sb + OFF_BAR;
    const uint32_t zero = P.zero;
#define BAR(i) (bar0 + 8u * (i))
#define CLUSTER_ARRIVE() asm volatile("barrier.cluster.arrive.relaxed.aligned;" ::: "memory")
#define CLUSTER_WAIT() asm volatile("barrier.cluster.wait.aligned;" ::: "memory")
    if ((sb & 0xffffffu) != SB0) return;

    if (warp == 12) {
        const CUtensorMap* tmD = c ? &tm_dim : &tm_dre;
#define LOAD0(it) do { \
            mbar_expect_tx(BAR(B_FS + DSLOT(it)), SLOT); tma_2d(sb + OFF_S + DSLOT(it) * SLOT, tmD, (it) * 64, r * 128, BAR(B_FS + DSLOT(it))); \
            mbar_expect_tx(BAR(B_FL + (it)), SLOT); tma_2d(sb + OFF_L + (it) * SLOT, &tm_x, (it) * 64, g * 256, BAR(B_FL + (it))); \
            mbar_expect_tx(BAR(B_FL + 4 + (it)), SLOT); tma_2d(sb + OFF_L + (4 + (it)) * SLOT, &tm_x, (it) * 64, g * 256 + 128, BAR(B_FL + 4 + (it))); \
        } while (0)
        if (elect_one()) {
            prefetch_tmap(tmD); prefetch_tmap(&tm_x);
            mbar_init(BAR(B_FS + 2), 1); mbar_init(BAR(B_FL), 1); mbar_init(BAR(B_FL + 4), 1);
            fence_async_smem();
            LOAD0(0);
#pragma unroll
            for (int i = 0; i < B_COUNT; i++)
                if (i != B_FS + 2 && i != B_FL && i != B_FL + 4)
                    mbar_init(BAR(i), (i >= B_ES && i < B_FL) || i == B_GO ? 2 : i == B_STATS || i == B_LST ? 4 : 1);
            mbar_expect_tx(BAR(B_RECV), SLOT); mbar_expect_tx(BAR(B_RECV + 1), SLOT);
            mbar_expect_tx(BAR(B_PEER), 1024); mbar_expect_tx(BAR(B_H), 128);
            *reinterpret_cast<volatile uint32_t*>(smem + OFF_SEL + 20) = 0;
            asm volatile("fence.mbarrier_init.release.cluster;" ::: "memory");
            fence_async_smem();
        }
        __syncwarp();
        CLUSTER_ARRIVE();
        if (elect_one()) {
#pragma unroll 1
            for (int it = 1; it < 4; it++) LOAD0(it);
        }
        __syncwarp();
    } else {
        CLUSTER_ARRIVE();
        if (K0 && tid == 13 * 32) red_max64(sync_words(), tstart);
    }

    if (warp >= 12) {
        asm volatile("setmaxnreg.dec.sync.aligned.u32 %0;" ::"n"(PROD_REGS));
        CLUSTER_WAIT();
        if (warp == 12) {
            if (elect_one()) {
                const CUtensorMap* tmD = c ? &tm_dim : &tm_dre;
#pragma unroll 1
                for (int it = 4; it < 16; it++) {
                    const int s = DSLOT(it);
                    mbar_wait(BAR(B_ES + s), ((it >> 2) & 1) ^ 1);
                    TRACE(it);
                    mbar_expect_tx(BAR(B_FS + s), SLOT);
                    tma_2d(sb + OFF_S + s * SLOT, tmD, it * 64, r * 128, BAR(B_FS + s));
                }
                const unsigned ep = load_epoch(b), e8 = ep & 0xffu;
                const uint8_t* abg = at(g_ab, grp * 32 * SLOT);
                const unsigned long long* fl = at(g_flag, grp * 128);
                mbar_wait(BAR(B_SRD), 0);
                st_release8(at(g_flag, grp * 128 + g), e8);
                PROF_T(7);
                int j = 4;
#pragma unroll 1
                for (int cl = 0; cl < 4; cl++) {
                    unsigned long long rdy = ld_acquire64(fl + cl);
                    fence_async_global();
#pragma unroll 1
                    for (int n = 1; n < 8; n++, j++) {
                        const int q = (g + n) & 7, s = (j & 1) + ((j & 2) ? 0 : 4);
                        mbar_wait(BAR(B_ES + s), ((j >> 2) ^ (j >> 1)) & 1);
                        if (j == 7) mbar_wait(BAR(B_SRD + 1), 0);
                        if (((unsigned)(rdy >> (8 * q)) & 0xffu) != e8) {
                            int m = 0;
                            do { rdy = ld_acquire64(fl + cl); } while (((unsigned)(rdy >> (8 * q)) & 0xffu) != e8 && ++m < SPIN_LIMIT);
                            fence_async_global();
                        }
                        TRACE(16 + j);
                        mbar_expect_tx(BAR(B_FS + s), SLOT);
                        bulk_g2s(sb + OFF_S + s * SLOT, at(abg, (4 * q + KO(cl)) * SLOT), SLOT, BAR(B_FS + s));
                    }
                }
                *at(g_epoch, b * 4) = ep;
            }
        } else if (warp < 15) {
            if (elect_one()) {
                const int w = warp - 13, row0 = g * 256 + w * 128;
                const CUtensorMap* tmC = c ? &tm_cim : &tm_cre;
                const uint32_t fb = BAR(B_FL + 4 * w), eb = BAR(B_EL + 4 * w), dst = sb + OFF_L + w * 4 * SLOT;
                prefetch_tmap(w ? &tm_out : tmC);
                int it = 4;
                unsigned long long* sy = sync_words();
#define ADOPT(ph, lag) do { const unsigned long long v = ld_relaxed64(sy++); \
                    if (v - (ph) < SYNCCAP) *reinterpret_cast<volatile uint32_t*>(smem + OFF_SEL + 20) = (uint32_t)v - (lag); } while (0)
                if (w == 0 && K0) { sleep_until((uint32_t)tstart + KRD); ADOPT(tstart, 0u - K0); }
#define LOADL(tm, kb) do { const int s = it & 3; \
                    mbar_wait(eb + 8 * s, ((it >> 2) & 1) ^ 1); \
                    const unsigned long long ph = clock64() - 1024u * (it - 4); \
                    TRACE(64 + w * 64 + it - 4); \
                    mbar_expect_tx(fb + 8 * s, SLOT); \
                    tma_2d(dst + s * SLOT, tm, (kb) * 64, row0, fb + 8 * s); \
                    if (w == 0) { \
                        if (((SYNCS << 4) >> it) & 1) red_max64(sy, ph); \
                        if (((SYNCS << (4 + SYNCD)) >> it) & 1) ADOPT(ph, SYNCLAG); \
                    } \
                    it++; } while (0)
#pragma unroll 1
                while (it < 16) LOADL(&tm_x, it);
#pragma unroll 1
                for (int cl = 0; cl < 4; cl++) LOADL(tmC, 4 * g + KO(cl));
#pragma unroll 1
                for (int cl = 0; cl < 4; cl++) {
#pragma unroll 1
                    for (int n = 1; n < 8; n++) LOADL(tmC, 4 * ((g + n) & 7) + KO(cl));
                }
            }
        } else {
            const unsigned ep = load_epoch(b);
            uint4 f[4];
#define GATHER(ptr, cnt, valid) do { int n = 0; bool ok; do { ok = true; \
                _Pragma("unroll") for (int i = 0; i < (cnt); i++) { f[i] = ld_relaxed128((ptr) + i * 32); ok = ok && (valid); } \
                if (__all_sync(0xffffffffu, ok)) break; \
                __nanosleep(GSL); \
            } while (++n < SPIN_LIMIT); } while (0)
            {
                sleep_until((uint32_t)tstart + 5000); mbar_wait(BAR(B_LST), 0);
                f[0] = *reinterpret_cast<const uint4*>(smem + OFF_XB);
                if (lane == 0) st_relaxed64(at(g_key, b * 8), ((unsigned long long)ep << 32) | max(max(f[0].x, f[0].y), max(f[0].z, f[0].w)));
                GATHER(at(reinterpret_cast<const uint4*>(g_key), lane * 16), 2, f[i].y == ep && f[i].w == ep);
                const unsigned key = __reduce_max_sync(0xffffffffu, max(max(f[0].x, f[0].z), max(f[1].x, f[1].z)));
                if (lane == 0) { *reinterpret_cast<unsigned*>(smem + OFF_SEL) = key; mbar_arrive(BAR(B_SEL)); PROF_T(8); }
            }
            if (elect_one()) {
#pragma unroll 1
                for (int cl = 0; cl < 4; cl++) {
                    uint8_t* dst = at(g_ab, (grp * 32 + 4 * g + KO(cl)) * SLOT);
                    const uint32_t src = sb + OFF_S + cl * SLOT, chunk = cl ? 4096 : SLOT;
                    mbar_wait(BAR(B_FS + cl), 0);
                    if (cl == 0) PROF_T(3);
                    uint32_t t0 = clock32() + (cl == 1 ? PDEL : 0);
#pragma unroll 1
                    for (uint32_t o = 0; o < SLOT; o += chunk) {
                        sleep_until(t0);
                        bulk_s2g(dst + o, src + o, chunk);
                        bulk_commit();
                        t0 += PGAP;
                    }
                    bulk_wait<0>();
                    TRACE(252 + cl);
                    if (cl < 2) mbar_arrive(BAR(B_SRD + cl));
                    else {
                        mbar_wait(BAR(B_ES + cl), 0);
                        mbar_expect_tx(BAR(B_FS + cl), SLOT);
                        tma_2d(src, &tm_x, grp * 64, g * 256 + (cl - 2) * 128, BAR(B_FS + cl));
                    }
                    if (cl) st_release8(at(g_flag, grp * 128 + cl * 8 + g), ep & 0xffu);
                    if (cl == 1) PROF_T(5);
                    if (cl == 3) PROF_T(4);
                }
            }
        }
    } else if (warp >= 8) {
        asm volatile("setmaxnreg.dec.sync.aligned.u32 %0;" ::"n"(512 - PROD_REGS - 2 * CONS_REGS));
        const int aw = warp - 8, mt = tid - 256;
        const unsigned ep = load_epoch(b);
        {
            const int row = b * 16 + aw * 4;
            const __nv_bfloat16* xp = at(P.x, (row * D_ + lane * 8) * 2);
            const __nv_bfloat16* dp = at(c ? P.dim : P.dre, ((r * 128 + g * 16 + aw * 4) * D_ + lane * 8) * 2);
            const __nv_bfloat16* wr = at(P.wr, lane * 16);
            uint4 v[4][4], w[4];
#define SLOAD(i) do { w[i] = ldg_ord(wr + (i) * 256); \
                _Pragma("unroll") for (int k = 0; k < 4; k++) v[i][k] = ldg_ord(xp + k * D_ + (i) * 256); } while (0)
            if (SDEL) __nanosleep(SDEL);
            SLOAD(0);
            __nanosleep(SGAP);
            SLOAD(1);
            __nanosleep(0);
            float x0[4], s1[4], s2[4], sx[4], sd[4], sw = 0.f;
#pragma unroll
            for (int k = 0; k < 4; k++) { x0[k] = bf_lo(v[0][k].x); s1[k] = 0.f; s2[k] = 0.f; sx[k] = 0.f; }
#pragma unroll
            for (int i = 0; i < 4; i++) {
                const float wf[8] = {bf_lo(w[i].x), bf_hi(w[i].x), bf_lo(w[i].y), bf_hi(w[i].y), bf_lo(w[i].z), bf_hi(w[i].z), bf_lo(w[i].w), bf_hi(w[i].w)};
                sw += ((wf[0] + wf[1]) + (wf[2] + wf[3])) + ((wf[4] + wf[5]) + (wf[6] + wf[7]));
#pragma unroll
                for (int k = 0; k < 4; k++) {
                    x0[k] = __shfl_sync(0xffffffffu, x0[k], 0);
                    const uint32_t xv[4] = {v[i][k].x, v[i][k].y, v[i][k].z, v[i][k].w};
#pragma unroll
                    for (int e = 0; e < 4; e++) {
                        const float a0 = bf_lo(xv[e]) - x0[k], a1 = bf_hi(xv[e]) - x0[k];
                        s1[k] += a0 + a1;
                        s2[k] = fmaf(a0, a0, fmaf(a1, a1, s2[k]));
                        sx[k] = fmaf(a0, wf[2 * e], fmaf(a1, wf[2 * e + 1], sx[k]));
                    }
                    yield(sx[k], zero);
                    if (k == 0 && i < 2) { SLOAD(i + 2); __nanosleep(0); }
                    if (i >= 2) v[i - 2][k] = ldg_ord(dp + k * D_ + (i - 2) * 256);
                }
            }
#pragma unroll
            for (int k = 0; k < 8; k++) v[2 + (k >> 2)][k & 3] = ldg_ord(dp + (k & 3) * D_ + (2 + (k >> 2)) * 256);
#define FOLD4(a) do { const bool u16 = lane & 16, u8 = lane & 8; \
                float p0 = (u16 ? a[2] : a[0]) + __shfl_xor_sync(0xffffffffu, u16 ? a[0] : a[2], 16); \
                float p1 = (u16 ? a[3] : a[1]) + __shfl_xor_sync(0xffffffffu, u16 ? a[1] : a[3], 16); \
                a[0] = (u8 ? p1 : p0) + __shfl_xor_sync(0xffffffffu, u8 ? p0 : p1, 8); \
                _Pragma("unroll") for (int o = 4; o; o >>= 1) a[0] += __shfl_xor_sync(0xffffffffu, a[0], o); } while (0)
            FOLD4(s1); FOLD4(s2); FOLD4(sx);
            sw = warp_sum(sw);
            const int rr = lane >> 3;
            const float c0 = rr == 0 ? x0[0] : rr == 1 ? x0[1] : rr == 2 ? x0[2] : x0[3];
            const float dm = s1[0] * (1.0f / D_);
            const float mb = rbf(c0 + dm);
            const float rinv = 1.0f / rbf(sqrtf(rbf(rbf(fmaxf(s2[0] * (1.0f / D_) - dm * dm, 0.f)) + 1e-5f)));
            unsigned u = __bfloat16_as_ushort(__float2bfloat16_rn((sx[0] + (c0 - mb) * sw) * rinv));
            u = (u & 0x8000u) ? (~u & 0xffffu) : (u | 0x8000u);
            u = (u << 16) | (0xffffu - (unsigned)(row + rr));
            const uint4 rec = make_uint4(__float_as_uint(mb), __float_as_uint(rinv), ep, u);
            if ((lane & 7) == 0) st_relaxed128(at(g_stat, (row + rr) * 16), rec);
            CLUSTER_WAIT();
            u = __reduce_max_sync(0xffffffffu, u);
            if (lane == 0) { *reinterpret_cast<unsigned*>(smem + OFF_XB + aw * 4) = u; mbar_arrive(BAR(B_LST)); }
            if (mt == 0) PROF_T(2);
            float run = 0.f;
#pragma unroll
            for (int k = 0; k < 4; k++) {
                run = __uint_as_float(__float_as_uint(run) & zero);
#pragma unroll
                for (int i = 0; i < 4; i++) {
                    const uint32_t dv[4] = {v[i][k].x, v[i][k].y, v[i][k].z, v[i][k].w};
#pragma unroll
                    for (int e = 0; e < 4; e++) run = (run + bf_lo(dv[e])) + bf_hi(dv[e]);
                }
                sd[k] = run;
            }
            FOLD4(sd);
            const float nb = __shfl_down_sync(0xffffffffu, sd[0], 8);
            if ((lane & 15) == 0)
                st_relaxed128(at(g_rs, (grp * 64 + g * 8 + aw * 2 + (lane >> 4)) * 16), make_uint4(__float_as_uint(sd[0]), ep, __float_as_uint(nb), ep));
            if (mt == 0) PROF_T(6);
            uint4 f[4];
            if (aw < 2) {
                const int t = aw * 128 + lane;
                GATHER(at(g_stat, (g * 256 + t) * 16), 4, f[i].z == ep);
#pragma unroll
                for (int i = 0; i < 4; i++) {
                    *reinterpret_cast<uint32_t*>(smem + OFF_RSTD + (POS(t) + i * 32) * 4) = f[i].y;
                    *reinterpret_cast<uint16_t*>(smem + OFF_MEAN + (POS(t) + i * 32) * 2) = (uint16_t)(f[i].x >> 16);
                }
            } else {
                const int e2 = (aw - 2) * 32 + lane;
                GATHER(at(g_rs, (grp * 64 + e2) * 16), 1, f[i].y == ep && f[i].w == ep);
#pragma unroll
                for (int i = 0; i < 2; i++) {
                    const float v = __uint_as_float(i ? f[0].z : f[0].x);
                    const float hi = rbf(v), mid = rbf(v - hi), lo = v - hi - mid;
                    *reinterpret_cast<uint4*>(smem + OFF_S + SLOT + (e2 * 2 + i) * 16) = make_uint4(pack_bf(hi, mid), pack_bf(lo, 0.f), 0, 0);
                }
            }
            fence_async_smem();
            __syncwarp();
            if (lane == 0) mbar_arrive(BAR(B_STATS));
            if (mt == 127) PROF_T(9);
        }
        const int pair = g * 7 + r;
        if (r < 7) {
            const uint64_t pol = policy_evict_first();
            const __nv_bfloat16* wp = at((aw & 1) ? P.wu : P.wg, ((c * 512 + (aw >> 1) * 256 + (lane >> 3) * 8) * F_ + pair * 64 + (lane & 7) * 8) * 2);
            uint4 b0[8], b1[8];
#define FILL(buf, str) do { _Pragma("unroll") for (int q = 0; q < 8; q++) buf[q] = ldg_stream(wp + q * (str), pol); } while (0)
            FILL(b0, F_);
            mbar_wait(BAR(B_SEL), 0);
            uint4 xn;
            {
                const int sel = 0xffff - (int)(*reinterpret_cast<volatile unsigned*>(smem + OFF_SEL) & 0xffffu);
                xn = __ldg(reinterpret_cast<const uint4*>(at(P.x, (sel * D_ + c * 512 + (aw >> 1) * 256 + (lane & 7) * 32 + (lane >> 3) * 8) * 2)));
                uint4 f[1];
                GATHER(at(g_stat, sel * 16), 1, f[i].z == ep);
                const float m = __uint_as_float(f[0].x), ri = __uint_as_float(f[0].y);
                xn = make_uint4(norm2(xn.x, m, ri), norm2(xn.y, m, ri), norm2(xn.z, m, ri), norm2(xn.w, m, ri));
            }
            float ag[8];
#pragma unroll
            for (int i = 0; i < 8; i++) ag[i] = 0.f;
            const uint32_t stag = (aw * 4 + (grp & 3)) * ESTAG;
            uint32_t te = clock32() + stag;
            bool paused = !QUIET;
#define ROUND(cur, nxt, rd) do { \
                if (!paused && mbar_test(BAR(B_QUIET), 0)) { mbar_wait_sleep(BAR(B_GO), 0); te = clock32() + stag; paused = true; } \
                sleep_until(te); \
                te = clock32() + (paused ? EGAP2 : EGAP1); \
                if (lane == 0) TRACE(192 + aw * 12 + (rd)); \
                if ((rd) == 7) wp = at(P.wd - 16 * D_, ((pair * 64 + (lane >> 4) * 8) * D_ + c * 512 + aw * 128 + (lane & 15) * 8) * 2); \
                wp = at(wp, ((rd) < 7 ? 64 * F_ : 32 * D_) + (cur[7].x & zero)); \
                if ((rd) < 7) FILL(nxt, F_); else if ((rd) != 8 && (rd) < 11) FILL(nxt, D_); \
                _Pragma("unroll") for (int q = 0; q < 8; q += 2) { \
                    const uint32_t xw = __shfl_sync(0xffffffffu, q == 0 ? xn.x : q == 2 ? xn.y : q == 4 ? xn.z : xn.w, (lane & 24) | ((rd) & 7)); \
                    fma8(ag, cur[q], bf_lo(xw)); \
                    fma8(ag, cur[q + 1], bf_hi(xw)); \
                    if (q < 6) yield(ag[7], zero); \
                } } while (0)
#pragma unroll 1
            for (int rd = 0; rd < 12; rd += 2) {
                ROUND(b0, b1, rd);
                ROUND(b1, b0, rd + 1);
                if (rd == 6) { wp += 16 * D_; FILL(b1, D_); wp -= 16 * D_; }
                if (rd == 6 || rd == 10) {
#pragma unroll
                    for (int i = 0; i < 8; i++) ag[i] += __shfl_xor_sync(0xffffffffu, ag[i], 16);
                }
                if (rd == 6) {
#pragma unroll
                    for (int i = 0; i < 8; i++) ag[i] += __shfl_xor_sync(0xffffffffu, ag[i], 8);
                    if (lane < 8) {
                        const uint32_t dst = mapa(sb + OFF_XB + (c * 4 + aw) * 128 + (lane & 3) * 32, lane >> 2), pb = mapa(BAR(B_PEER), lane >> 2);
                        st_async4(dst, __float_as_uint(ag[0]), __float_as_uint(ag[1]), __float_as_uint(ag[2]), __float_as_uint(ag[3]), pb);
                        st_async4(dst + 16, __float_as_uint(ag[4]), __float_as_uint(ag[5]), __float_as_uint(ag[6]), __float_as_uint(ag[7]), pb);
                    }
                    if (aw == 3) {
                        mbar_wait_cluster(BAR(B_PEER), 0);
                        const float* ps = reinterpret_cast<const float*>(smem + OFF_XB) + lane;
                        const float go = (ps[0] + ps[64]) + (ps[128] + ps[192]), uo = (ps[32] + ps[96]) + (ps[160] + ps[224]);
                        const float h = rbf(silu_f(rbf(go))) * rbf(uo), ho = __shfl_xor_sync(0xffffffffu, h, 1);
                        asm volatile("st.async.weak.shared::cluster.mbarrier::complete_tx::bytes.b32 [%0], %1, [%2];"
                                     ::"r"(mapa(sb + OFF_H + c * 64 + (lane >> 1) * 4, lane & 1)), "r"((lane & 1) ? pack_bf(ho, h) : pack_bf(h, ho)),
                                       "r"(mapa(BAR(B_H), lane & 1)) : "memory");
                    }
                    mbar_wait_cluster(BAR(B_H), 0);
                    xn = *reinterpret_cast<const uint4*>(smem + OFF_H + (lane & 3) * 32 + (lane >> 4) * 16);
#pragma unroll
                    for (int i = 0; i < 8; i++) ag[i] = 0.f;
                    if (mt == 0) PROF_T(10);
                }
            }
            const int hi = lane >> 4;
            st_relaxed128(at(g_part, pair * 4096 + (c * 8 + aw * 2 + ((lane >> 3) & 1)) * 256 + hi * 128 + (lane & 7) * 16),
                          make_uint4((__float_as_uint(hi ? ag[4] : ag[0]) & ~15u) | (ep & 15u), __float_as_uint(hi ? ag[5] : ag[1]),
                                     __float_as_uint(hi ? ag[6] : ag[2]), __float_as_uint(hi ? ag[7] : ag[3])));
            if (mt == 0) PROF_T(11);
        } else {
            mbar_wait_sleep(BAR(B_SEL), 0);
        }
        const int sel = 0xffff - (int)(*reinterpret_cast<volatile unsigned*>(smem + OFF_SEL) & 0xffffu);
        if ((sel >> 8) == g) {
            const int col = (lane & 7) * 8 + ((lane >> 3) & 1) * 4;
            const uint2 xv = __ldg(reinterpret_cast<const uint2*>(at(P.x, (sel * D_ + grp * 64 + col) * 2)));
            uint4 f[1];
            GATHER(at(g_stat, sel * 16), 1, f[i].z == ep);
            const uint4 rec = f[0];
            const uint4* src = at(g_part, (aw * 14 + (lane >> 4)) * 4096 + grp * 256 + (lane & 15) * 16);
            if (r == 7) {
                int n = 0;
                while (((ld_relaxed(src) ^ ep) & 15u) != 0 && ++n < SPIN_LIMIT) __nanosleep(500);
            }
            uint4 t[7];
            int n = 0;
            bool ok;
            do {
                ok = true;
#pragma unroll
                for (int u = 0; u < 7; u++) { t[u] = ld_relaxed128(src + u * 512); ok = ok && ((t[u].x ^ ep) & 15u) == 0; }
            } while (!__all_sync(0xffffffffu, ok) && ++n < SPIN_LIMIT);
            float4 a = make_float4(0.f, 0.f, 0.f, 0.f);
#pragma unroll
            for (int u = 0; u < 7; u++) {
                a.x += __uint_as_float(t[u].x & ~15u); a.y += __uint_as_float(t[u].y); a.z += __uint_as_float(t[u].z); a.w += __uint_as_float(t[u].w);
            }
            a.x += __shfl_xor_sync(0xffffffffu, a.x, 16); a.y += __shfl_xor_sync(0xffffffffu, a.y, 16);
            a.z += __shfl_xor_sync(0xffffffffu, a.z, 16); a.w += __shfl_xor_sync(0xffffffffu, a.w, 16);
            float4* park = reinterpret_cast<float4*>(smem + OFF_XB) + (lane & 15);
            if (lane < 16) park[aw * 16] = a;
            named_bar<4, 128>();
            if (aw == 0) {
                const float4 p1 = park[16], p2 = park[32], p3 = park[48];
                a.x = (a.x + p1.x) + (p2.x + p3.x); a.y = (a.y + p1.y) + (p2.y + p3.y);
                a.z = (a.z + p1.z) + (p2.z + p3.z); a.w = (a.w + p1.w) + (p2.w + p3.w);
                unsigned u = rec.w >> 16;
                u = (u & 0x8000u) ? (u & 0x7fffu) : (~u & 0xffffu);
                const float sg = rbf(__fdividef(1.0f, 1.0f + __expf(-__uint_as_float(u << 16))));
                const float m = __uint_as_float(rec.x), ri = __uint_as_float(rec.y);
                const uint32_t n0 = norm2(xv.x, m, ri), n1 = norm2(xv.y, m, ri);
                uint2 o;
                o.x = silu2(pack_bf(bf_lo(n0) + rbf(rbf(a.x) * sg), bf_hi(n0) + rbf(rbf(a.y) * sg)));
                o.y = silu2(pack_bf(bf_lo(n1) + rbf(rbf(a.z) * sg), bf_hi(n1) + rbf(rbf(a.w) * sg)));
                if (lane < 16) *reinterpret_cast<uint2*>(smem + OFF_H + col * 2) = o;
                if (lane == 0) *reinterpret_cast<int*>(smem + OFF_SEL + 16) = sel & 255;
                __syncwarp();
                if (lane == 0) { mbar_arrive(BAR(B_UPD)); PROF_T(12); }
            }
        } else if (mt == 0) {
            *reinterpret_cast<int*>(smem + OFF_SEL + 16) = -1;
            mbar_arrive(BAR(B_UPD));
        }
    } else {
        asm volatile("setmaxnreg.inc.sync.aligned.u32 %0;" ::"n"(CONS_REGS));
        CLUSTER_WAIT();
        const int wg = warp >> 2, wq = warp & 3;
        const int wt = tid & 127;
        float acc[128];
        const uint32_t fL = BAR(B_FL + 4 * wg), eL = BAR(B_EL + 4 * wg);
        const uint32_t dL = desc_lo(SB0 + OFF_L, 16) + wg * 4096;
        constexpr uint32_t dS = desc_lo(SB0 + OFF_S, 16);
        constexpr uint32_t SL = SLOT >> 4;
#define RELEASE(ls, ss) do { if (wt == 0) { mbar_arrive(eL + 8u * (ls)); mbar_arrive(BAR(B_ES + (ss))); } } while (0)
#define WAIT_FULL(ls, lph, ss, sph) do { mbar_wait(BAR(B_FS + (ss)), sph); mbar_wait(fL + 8u * (ls), lph); } while (0)
#define TURN() do { if (wg) named_bar<6, 256>(); else named_bar<5, 256>(); } while (0)
#define PASS() do { if (wg) named_arrive<5, 256>(); else named_arrive<6, 256>(); } while (0)
#define WG_BAR() do { if (wg) named_bar<2, 128>(); else named_bar<1, 128>(); } while (0)
        uint32_t held = 0;
#define HOLD(step) do { if (wg == 0) { const uint32_t t = *reinterpret_cast<volatile uint32_t*>(smem + OFF_SEL + 20); \
            if (t != held) { held = t; sleep_until(t + 1024u * (step) - 100u); \
                int n = 0; while ((int)(clock32() - t - 1024u * (step)) < 0 && ++n < SPIN_LIMIT) {} } } } while (0)
        if (wg == 1) PASS();

#define MMA1_P(O, s, first, pass) do { _Pragma("unroll") for (int kk = 0; kk < 4; kk++) { if (kk == PK && (pass)) PASS(); \
            wgmma128<O, 0>(acc, dL + (s) * SL + kk * 2 + (O) * 8, dS + DSLOT(s) * SL + kk * 2, !((first) && kk == 0)); } \
            if (PK == 4 && (pass)) PASS(); } while (0)
#define MMA1_H(O, s, first) MMA1_P(O, s, first, false)
#define WAIT1(s, ph) WAIT_FULL(s, ph, DSLOT(s), ph)
#define REL1(s) RELEASE(s, DSLOT(s))
#pragma unroll 1
        for (int it = 0; it < 12; it++) {
            const int s = it & 3;
            WAIT1(s, (it >> 2) & 1);
            if (it < 8 && wt == 0) TRACE(176 + wg * 8 + it);
            HOLD(it);
            TURN();
            if (it) { wg_wait<0>(); REL1((it - 1) & 3); }
            wg_fence(); MMA1_H(0, s, it == 0); MMA1_P(64, s, it == 0, true); wg_commit();
            if (it == QJ && tid == 0) { mbar_arrive(BAR(B_QUIET)); PROF_T(15); }
            if (it == 0 && tid == 0) PROF_T(16);
        }
        mbar_wait(BAR(B_STATS), 0);
        float rs[4];
        uint32_t nm[8];
        {
            const int p0 = POS(wg * 128 + wq * 16 + (lane >> 2));
            const uint32_t msk = (lane & 3) == 0 ? 0xffffffffu : (lane & 3) == 1 ? 0x0000ffffu : 0u;
#pragma unroll
            for (int i = 0; i < 4; i++) {
                const int p = p0 + (i & 1) * 2 + (i >> 1) * 64;
                rs[i] = *reinterpret_cast<const float*>(smem + OFF_RSTD + p * 4);
                const uint32_t m = *reinterpret_cast<const uint16_t*>(smem + OFF_MEAN + p * 2) ^ 0x8000u;
                nm[i + (i & 2)] = (m | (m << 16)) & msk;
                nm[i + (i & 2) + 2] = 0;
            }
            asm volatile("" : "+r"(nm[0]), "+r"(nm[1]), "+r"(nm[2]), "+r"(nm[3]), "+r"(nm[4]), "+r"(nm[5]), "+r"(nm[6]), "+r"(nm[7])::"memory");
        }
        WAIT1(0, 1);
        wg_wait<0>(); REL1(3);
        TURN();
        wg_fence();
        wgmma128_rs<0>(acc, nm, (SB0 + OFF_S + SLOT) >> 4);
        wgmma128_rs<64>(acc, nm + 4, (SB0 + OFF_S + SLOT) >> 4);
        MMA1_H(0, 0, false);
        if (QJ == 12 && tid == 0) { mbar_arrive(BAR(B_QUIET)); PROF_T(15); }
#pragma unroll
        for (int s = 1; s < 4; s++) { WAIT1(s, 1); wg_fence(); MMA1_P(0, s, false, s == 3); }
        wg_commit();
        const int mrow = wq * 16 + ((lane >> 3) & 1) * 8 + (lane & 7);
#define EPI1(O, slot, FREE) do { const uint32_t dst = sb + OFF_S + (slot) * SLOT + mrow * 128; \
            uint32_t pk[32]; \
            _Pragma("unroll") for (int i = 0; i < 32; i += 4) { \
                _Pragma("unroll") for (int k = 0; k < 4; k++) \
                    pk[i + k] = pack_bf(acc[(O) + 2 * (i + k)] * rs[(O) / 32 + (k & 1)], acc[(O) + 2 * (i + k) + 1] * rs[(O) / 32 + (k & 1)]); \
                if (i == EF) { FREE; } \
                if (i >= EF) { _Pragma("unroll") for (int v = (i == EF ? 0 : i); v <= i; v += 4) \
                    stmatrix4(dst + ((v >> 4) ^ c ^ 1) * 8192 + ((((v >> 1) & 7) + (lane >> 4)) ^ (lane & 7)) * 16, pk[v], pk[v + 1], pk[v + 2], pk[v + 3]); } } \
            fence_async_smem(); WG_BAR(); \
            if (wt == 0) mbar_arrive(BAR(B_FS + (slot))); } while (0)
        wg_wait<0>();
        fence_regs64<0>(acc);
        if (wt == 0) TRACE(240 + wg * 4);
        {
            constexpr int EF = 0;
            EPI1(0, wg, if (wg) mbar_wait(BAR(B_FS), 0));
        }
        if (wt == 0) TRACE(241 + wg * 4);
        TURN();
        wg_fence();
        MMA1_H(64, 0, false); wg_commit();
        MMA1_H(64, 1, false); wg_commit();
        MMA1_H(64, 2, false); wg_commit();
        wg_wait<2>(); REL1(0);
        MMA1_P(64, 3, false, true); wg_commit();
        wg_wait<2>(); REL1(1);
        wg_wait<1>(); REL1(2);
        wg_wait<0>(); REL1(3);
        fence_regs64<64>(acc);
        if (wt == 0) PROF_T(17 + wg * 10);
        {
            constexpr int EF = 12;
            EPI1(64, 2 + wg, mbar_wait(BAR(B_ES + 2 + wg), 1));
        }
        if (wt == 0) PROF_T(18 + wg * 10);

        float ac2[128];
#define MMA2_P(O, ls, ss, first, pass) do { _Pragma("unroll") for (int kk = 0; kk < 4; kk++) { if (kk == PK && (pass)) PASS(); \
            wgmma128<O, 1>(ac2, dS + (ss) * SL + kk * 128 + (O) * 8, dL + (ls) * SL + kk * 2, !((first) && kk == 0)); } \
            if (PK == 4 && (pass)) PASS(); } while (0)
#define MMA2_H(O, ls, ss, first) MMA2_P(O, ls, ss, first, false)
#define WAIT2(j) WAIT_FULL((j) & 3, ((j) >> 2) & 1, PSLOT(j), PPAR(j))
#define MMA2(j, pass) do { wg_fence(); MMA2_H(0, (j) & 3, PSLOT(j), (j) == 0); MMA2_P(64, (j) & 3, PSLOT(j), (j) == 0, pass); wg_commit(); } while (0)
#define REL2(j) RELEASE((j) & 3, PSLOT(j))
        if (GOJ == 0 && wt == 0) mbar_arrive(BAR(B_GO));
        WAIT2(0); TURN(); MMA2(0, false);
        WAIT2(1); MMA2(1, true);
        wg_wait<1>(); REL2(0);
        {
            uint32_t sp = 1;
#pragma unroll 1
            for (int j = 2; j < XJ; j++) {
                const uint32_t ss = PSLOT(j);
                WAIT_FULL(j & 3, (j >> 2) & 1, ss, PPAR(j));
                HOLD(16 + j);
                TURN();
                wg_wait<0>(); RELEASE((j - 1) & 3, sp);
                wg_fence(); MMA2_H(0, j & 3, ss, false); MMA2_P(64, j & 3, ss, false, true); wg_commit();
                if (j == GOJ && wt == 0) { mbar_arrive(BAR(B_GO)); if (wg == 0) PROF_T(19); }
                sp = ss;
            }
        }
        if (tid == 0) PROF_T(20);
        uint32_t gt[32];
        const uint32_t xrow = sb + OFF_S + (2 + wg) * SLOT + ((lane >> 4) * 8 + (lane & 7)) * 128 + (((2 * wq + ((lane >> 3) & 1)) ^ (lane & 7)) << 4);
        const uint32_t gsign = c ? 0x80008000u : 0u;
        mbar_wait(BAR(B_FS + 2 + wg), 1);
#pragma unroll
        for (int v = 0; v < 29 - XJ; v++) {
            WAIT2(XJ + v); TURN(); wg_wait<0>(); REL2(XJ + v - 1); MMA2(XJ + v, true);
            constexpr int NS = 8 / (29 - XJ);
#pragma unroll
            for (int u = v * NS; u < (v + 1) * NS; u++) {
                uint32_t* o = &gt[4 * u];
                ldmatrix4t(xrow + u * 2048, o[0], o[1], o[2], o[3]);
                const float4 r4 = *reinterpret_cast<const float4*>(smem + OFF_RSTD + (wg * 128 + u * 16 + (lane & 3) * 4) * 4);
                const uint2 m2 = *reinterpret_cast<const uint2*>(smem + OFF_MEAN + (wg * 128 + u * 16 + (lane & 3) * 4) * 2);
                o[0] = gate2(o[0], m2.x, r4.x, r4.y) ^ gsign;
                o[1] = gate2(o[1], m2.x, r4.x, r4.y) ^ gsign;
                o[2] = gate2(o[2], m2.y, r4.z, r4.w) ^ gsign;
                o[3] = gate2(o[3], m2.y, r4.z, r4.w) ^ gsign;
                asm volatile("st.shared.v2.u32 [%0], {%1,%2};" ::"r"(sb + OFF_SEL + 24), "r"(o[0] ^ o[1]), "r"(o[2] ^ o[3]) : "memory");
            }
        }
        if (tid == 0) PROF_T(21);
        WAIT2(29);
        wg_wait<0>();
        if (wt == 0) mbar_arrive_cluster(mapa(BAR(B_RDY + wg), c ^ 1));
        TURN();
#pragma unroll
        for (int j = 29; j < 32; j++) { if (j > 29) WAIT2(j); wg_fence(); MMA2_P(0, j & 3, PSLOT(j), false, j == 31); }
        wg_commit();
        mbar_wait(BAR(B_RDY + wg), 0);
        wg_wait<0>();
        fence_regs64<0>(ac2);
        if (wt == 0) PROF_T(22 + wg * 7);
        {
            const uint32_t dst = mapa(sb + OFF_L + wg * 4 * SLOT + wt * 16, c ^ 1), rb = mapa(BAR(B_RECV + wg), c ^ 1);
#pragma unroll
            for (int v = 0; v < 8; v++)
                st_async4(dst + v * 2048, pack_bf(ac2[8 * v + 0], ac2[8 * v + 1]), pack_bf(ac2[8 * v + 2], ac2[8 * v + 3]),
                          pack_bf(ac2[8 * v + 4], ac2[8 * v + 5]), pack_bf(ac2[8 * v + 6], ac2[8 * v + 7]), rb);
        }
        TURN();
        wg_fence();
#pragma unroll
        for (int j = 29; j < 32; j++) MMA2_P(64, j & 3, PSLOT(j), false, j == 31 && wg == 0);
        wg_commit();
        uint32_t xr[32];
#pragma unroll
        for (int v = 0; v < 8; v++) ldmatrix4t(xrow + v * 2048, xr[4 * v], xr[4 * v + 1], xr[4 * v + 2], xr[4 * v + 3]);
        mbar_wait(BAR(B_UPD), 0);
        {
            const int sl = *reinterpret_cast<volatile int*>(smem + OFF_SEL + 16);
            if ((sl >> 7) == wg) {
                const uint32_t v0 = *reinterpret_cast<const uint16_t*>(smem + OFF_H + (wq * 16 + (lane >> 2)) * 2) ^ gsign;
                const uint32_t v1 = *reinterpret_cast<const uint16_t*>(smem + OFF_H + (wq * 16 + (lane >> 2)) * 2 + 16) ^ gsign;
                const uint32_t pick = (lane & 3) != ((sl >> 1) & 3) ? 0x3210u : (sl & 1) ? 0x5410u : 0x3254u;
#pragma unroll
                for (int i = 0; i < 16; i++) {
                    const uint32_t sel = ((sl >> 3) & 15) == i ? pick : 0x3210u;
                    gt[2 * i] = __byte_perm(gt[2 * i], v0, sel);
                    gt[2 * i + 1] = __byte_perm(gt[2 * i + 1], v1, sel);
                }
            }
        }
        mbar_wait_cluster(BAR(B_RECV + wg), 0);
        if (wt == 0) PROF_T(23 + wg * 7);
        uint4 rv[8];
#pragma unroll
        for (int v = 0; v < 8; v++) rv[v] = *reinterpret_cast<const uint4*>(smem + OFF_L + wg * 4 * SLOT + v * 2048 + wt * 16);
        wg_wait<0>();
        fence_regs64<64>(ac2);
        if (wt == 0) PROF_T(24 + wg * 7);
#pragma unroll
        for (int v = 0; v < 8; v++) {
            const float* a = &ac2[64 + 8 * v];
            stmatrix4t(xrow + v * 2048,
                       bfma2(bsub2(pack_bf(a[0], a[1]), rv[v].x), gt[4 * v + 0], xr[4 * v + 0]),
                       bfma2(bsub2(pack_bf(a[2], a[3]), rv[v].y), gt[4 * v + 1], xr[4 * v + 1]),
                       bfma2(bsub2(pack_bf(a[4], a[5]), rv[v].z), gt[4 * v + 2], xr[4 * v + 2]),
                       bfma2(bsub2(pack_bf(a[6], a[7]), rv[v].w), gt[4 * v + 3], xr[4 * v + 3]));
            if ((v & 3) == 3) {
                fence_async_smem();
                WG_BAR();
                if (wt == 0) {
                    tma_2d_store(&tm_out, grp * 64, g * 256 + wg * 128 + (v >> 2) * 64, sb + OFF_S + (2 + wg) * SLOT + (v >> 2) * 8192);
                    bulk_commit();
                }
            }
        }
        if (wt == 0) {
            if (wg == 0) PROF_T(13);
            bulk_wait_read<0>();
            if (wg == 0) PROF_T(14); else { PROF_T(25); PROF_G(26); }
        }
    }
}

typedef CUresult (*EncodeFn)(CUtensorMap*, CUtensorMapDataType, cuuint32_t, void*, const cuuint64_t*, const cuuint64_t*,
                             const cuuint32_t*, const cuuint32_t*, CUtensorMapInterleave, CUtensorMapSwizzle,
                             CUtensorMapL2promotion, CUtensorMapFloatOOBfill);

void make_map(EncodeFn fn, CUtensorMap* tm, const void* p, uint64_t rows, uint64_t cols, uint32_t box_rows,
              CUtensorMapL2promotion promo = CU_TENSOR_MAP_L2_PROMOTION_L2_128B) {
    cuuint64_t dims[2] = {cols, rows};
    cuuint64_t strides[1] = {cols * 2};
    cuuint32_t box[2] = {64, box_rows};
    cuuint32_t es[2] = {1, 1};
    fn(tm, CU_TENSOR_MAP_DATA_TYPE_BFLOAT16, 2, const_cast<void*>(p), dims, strides, box, es, CU_TENSOR_MAP_INTERLEAVE_NONE,
       CU_TENSOR_MAP_SWIZZLE_128B, promo, CU_TENSOR_MAP_FLOAT_OOB_FILL_NONE);
}

}

extern "C" void kernel_launch(void* const* d_in, const int* in_sizes, int n_in, void* d_out, int out_size) {
    (void)in_sizes; (void)n_in; (void)out_size;
    static EncodeFn fn = nullptr;
    if (!fn) {
        void* p = nullptr;
        cudaDriverEntryPointQueryResult q;
        cudaGetDriverEntryPoint("cuTensorMapEncodeTiled", &p, cudaEnableDefault, &q);
        fn = (EncodeFn)p;
        cudaFuncSetAttribute(fnet_fused_kernel, cudaFuncAttributeMaxDynamicSharedMemorySize, SMEM_BYTES);
    }
    CUtensorMap tx, tdre, tdim, tcre, tcim, tout;
    make_map(fn, &tx, d_in[0], S_, D_, 128, PRX);
    make_map(fn, &tcre, d_in[1], S_, S_, 128, PRC);
    make_map(fn, &tcim, d_in[2], S_, S_, 128, PRC);
    make_map(fn, &tdre, d_in[3], D_, D_, 128, PRD);
    make_map(fn, &tdim, d_in[4], D_, D_, 128, PRD);
    make_map(fn, &tout, d_out, S_, D_, 64);
    Params P;
    P.x = (const __nv_bfloat16*)d_in[0];
    P.dre = (const __nv_bfloat16*)d_in[3];
    P.dim = (const __nv_bfloat16*)d_in[4];
    P.wr = (const __nv_bfloat16*)d_in[6];
    P.wg = (const __nv_bfloat16*)d_in[7];
    P.wu = (const __nv_bfloat16*)d_in[8];
    P.wd = (const __nv_bfloat16*)d_in[9];
    P.zero = 0;
    fnet_fused_kernel<<<NCTA, NTHREADS, SMEM_BYTES, cudaStreamPerThread>>>(tx, tdre, tdim, tcre, tcim, tout, P);
}
```

```cpp
#include <cuda_runtime.h>
#include <cuda_bf16.h>
#include <cuda.h>
#include <stdint.h>

#define SGAP 400
#define GSL 200
#define SDEL 0
#define YNS 0u
#define YLD 1
#define PDEL 2500
#define PGAP 600
#define PK 4
#define KQ 6
#define OP 4
#define XJ0 20
#define EGAP1 0
#define EGAP2 0
#define ESTAG 120
#define QJ 12
#define GOJ 2
#define TANH 1
#define SYNCS 0x22200020ull
#define K0 0
#define KRD 1500
#define SYNCD 2
#define SYNCCAP 4000u
#define SYNCMIN 24u
#define SYNCLAG 820u
#define QUIET 1
#define PRX CU_TENSOR_MAP_L2_PROMOTION_L2_128B
#define PRD CU_TENSOR_MAP_L2_PROMOTION_L2_128B
#define PRC CU_TENSOR_MAP_L2_PROMOTION_L2_128B
#define SLEEP_NS 200
#define PROD_REGS 32
#define CONS_REGS 184

namespace {

constexpr int S_ = 2048, D_ = 1024, F_ = 3584;
constexpr int NCTA = 128;
constexpr int XJ = XJ0;
constexpr uint32_t SLOT = 16384;
constexpr uint32_t OFF_L = 0;
constexpr uint32_t OFF_S = 8 * SLOT;
constexpr uint32_t OFF_BAR = 14 * SLOT;
constexpr uint32_t OFF_SEL = OFF_BAR + 360;
constexpr uint32_t OFF_RSTD = OFF_BAR + 384;
constexpr uint32_t OFF_MEAN = OFF_RSTD + 1024;
constexpr uint32_t OFF_XB = OFF_MEAN + 512;
constexpr uint32_t OFF_H = OFF_XB + 1024;
constexpr uint32_t SMEM_BYTES = OFF_H + 128;
constexpr uint32_t SB0 = 1024;
constexpr int NTHREADS = 512;
static_assert(SMEM_BYTES <= 232448, "smem");

enum { B_FS = 0, B_ES = 6, B_FL = 12, B_EL = 20, B_SRD = 28, B_RECV = 32, B_RDY = 34, B_STATS = 36, B_PEER = 37, B_UPD = 38,
       B_QUIET = 39, B_GO = 40, B_LST = 41, B_SEL = 42, B_H = 43, B_COUNT = 44 };
static_assert(B_COUNT * 8 <= 360, "barriers");

__device__ __align__(1024) uint8_t g_ab[16u * 32u * SLOT];
__device__ __align__(128) uint4 g_part[56 * (D_ / 4)];
__device__ __align__(128) uint4 g_stat[S_];
__device__ __align__(128) uint4 g_rs[D_];
__device__ __align__(128) unsigned long long g_key[NCTA];
__device__ __align__(128) unsigned long long g_flag[16 * 16];
__device__ __align__(128) unsigned long long g_sync[16 * 16];
__device__ __align__(128) unsigned g_epoch[NCTA];
#define PROF_T(i) do {} while (0)
#define TRACE(i) do {} while (0)
#define PROF_G(i) do {} while (0)
#define TS(i) do {} while (0)

__device__ __forceinline__ uint32_t smem_u32(const void* p) { return (uint32_t)__cvta_generic_to_shared(p); }
__device__ __forceinline__ void mbar_init(uint32_t bar, uint32_t cnt) {
    asm volatile("mbarrier.init.shared::cta.b64 [%0], %1;" ::"r"(bar), "r"(cnt) : "memory");
}
__device__ __forceinline__ bool mbar_try(uint32_t bar, uint32_t parity) {
    uint32_t ok;
    asm volatile("{\n.reg .pred p;\nmbarrier.try_wait.parity.shared::cta.b64 p, [%1], %2;\nselp.u32 %0, 1, 0, p;\n}"
                 : "=r"(ok) : "r"(bar), "r"(parity) : "memory");
    return ok;
}
__device__ __forceinline__ bool mbar_test(uint32_t bar, uint32_t parity) {
    uint32_t ok;
    asm volatile("{\n.reg .pred p;\nmbarrier.test_wait.parity.shared::cta.b64 p, [%1], %2;\nselp.u32 %0, 1, 0, p;\n}"
                 : "=r"(ok) : "r"(bar), "r"(parity) : "memory");
    return ok;
}
__device__ __forceinline__ bool mbar_try_cluster(uint32_t bar, uint32_t parity) {
    uint32_t ok;
    asm volatile("{\n.reg .pred p;\nmbarrier.try_wait.parity.acquire.cluster.shared::cta.b64 p, [%1], %2;\nselp.u32 %0, 1, 0, p;\n}"
                 : "=r"(ok) : "r"(bar), "r"(parity) : "memory");
    return ok;
}
constexpr int SPIN_LIMIT = 1 << 20;
__device__ __forceinline__ void mbar_wait(uint32_t bar, uint32_t parity) {
    if (mbar_try(bar, parity)) return;
    int n = 0;
    while (!mbar_try(bar, parity) && ++n < SPIN_LIMIT) {}
}
__device__ __forceinline__ void mbar_wait_cluster(uint32_t bar, uint32_t parity) {
    int n = 0;
    while (!mbar_try_cluster(bar, parity) && ++n < SPIN_LIMIT) {}
}
__device__ __forceinline__ void mbar_wait_sleep(uint32_t bar, uint32_t parity) {
    int n = 0;
    while (!mbar_try(bar, parity) && ++n < SPIN_LIMIT) __nanosleep(SLEEP_NS);
}
__device__ __forceinline__ void mbar_arrive(uint32_t bar) {
    asm volatile("mbarrier.arrive.shared::cta.b64 _, [%0];" ::"r"(bar) : "memory");
}
__device__ __forceinline__ void mbar_arrive_cluster(uint32_t cluster_bar) {
    asm volatile("mbarrier.arrive.shared::cluster.b64 _, [%0];" ::"r"(cluster_bar) : "memory");
}
__device__ __forceinline__ void mbar_expect_tx(uint32_t bar, uint32_t bytes) {
    asm volatile("mbarrier.arrive.expect_tx.shared::cta.b64 _, [%0], %1;" ::"r"(bar), "r"(bytes) : "memory");
}
__device__ __forceinline__ bool elect_one() {
    uint32_t p;
    asm volatile("{\n.reg .pred p;\nelect.sync _|p, 0xffffffff;\nselp.u32 %0, 1, 0, p;\n}" : "=r"(p));
    return p;
}
__device__ __forceinline__ uint32_t mapa(uint32_t addr, uint32_t rank) {
    uint32_t r;
    asm("mapa.shared::cluster.u32 %0, %1, %2;" : "=r"(r) : "r"(addr), "r"(rank));
    return r;
}
__device__ __forceinline__ uint32_t clock32() { uint32_t t; asm volatile("mov.u32 %0, %%clock;" : "=r"(t)); return t; }
__device__ __forceinline__ void sleep_until(uint32_t t) {
    int n = 0;
    while ((int)(clock32() - t) < 0 && ++n < SPIN_LIMIT) __nanosleep(20);
}
__device__ __forceinline__ void yield(float last, uint32_t zero) {
    if (YLD) asm volatile("nanosleep.u32 %0;" ::"r"((__float_as_uint(last) & zero) | YNS));
}
template <typename T> __device__ __forceinline__ T* at(T* p, uint32_t bytes) {
    asm("" : "+r"(bytes));
    return reinterpret_cast<T*>(reinterpret_cast<uintptr_t>(p) + bytes);
}
__device__ __forceinline__ void tma_2d(uint32_t dst, const CUtensorMap* tm, int c0, int c1, uint32_t bar) {
    asm volatile("cp.async.bulk.tensor.2d.shared::cluster.global.mbarrier::complete_tx::bytes [%0], [%1, {%3, %4}], [%2];"
                 ::"r"(dst), "l"(tm), "r"(bar), "r"(c0), "r"(c1) : "memory");
}
__device__ __forceinline__ void tma_2d_store(const CUtensorMap* tm, int c0, int c1, uint32_t src) {
    asm volatile("cp.async.bulk.tensor.2d.global.shared::cta.bulk_group [%0, {%2, %3}], [%1];"
                 ::"l"(tm), "r"(src), "r"(c0), "r"(c1) : "memory");
}
__device__ __forceinline__ void bulk_g2s(uint32_t dst, const void* src, uint32_t bytes, uint32_t bar) {
    asm volatile("cp.async.bulk.shared::cluster.global.mbarrier::complete_tx::bytes [%0], [%1], %2, [%3];"
                 ::"r"(dst), "l"(src), "r"(bytes), "r"(bar) : "memory");
}
__device__ __forceinline__ void bulk_s2g(void* dst, uint32_t src, uint32_t bytes) {
    asm volatile("cp.async.bulk.global.shared::cta.bulk_group [%0], [%1], %2;" ::"l"(dst), "r"(src), "r"(bytes) : "memory");
}
__device__ __forceinline__ void st_async4(uint32_t dst, uint32_t a, uint32_t b, uint32_t c, uint32_t d, uint32_t bar) {
    asm volatile("st.async.weak.shared::cluster.mbarrier::complete_tx::bytes.v4.b32 [%0], {%1,%2,%3,%4}, [%5];"
                 ::"r"(dst), "r"(a), "r"(b), "r"(c), "r"(d), "r"(bar) : "memory");
}
__device__ __forceinline__ void bulk_commit() { asm volatile("cp.async.bulk.commit_group;" ::: "memory"); }
template <int N> __device__ __forceinline__ void bulk_wait_read() { asm volatile("cp.async.bulk.wait_group.read %0;" ::"n"(N) : "memory"); }
template <int N> __device__ __forceinline__ void bulk_wait() { asm volatile("cp.async.bulk.wait_group %0;" ::"n"(N) : "memory"); }
__device__ __forceinline__ void fence_async_smem() { asm volatile("fence.proxy.async.shared::cta;" ::: "memory"); }
__device__ __forceinline__ void fence_async_global() { asm volatile("fence.proxy.async.global;" ::: "memory"); }
__device__ __forceinline__ void prefetch_tmap(const CUtensorMap* tm) {
    asm volatile("prefetch.tensormap [%0];" ::"l"(tm) : "memory");
}
__device__ __forceinline__ unsigned long long ld_acquire64(const unsigned long long* p) {
    unsigned long long v; asm volatile("ld.acquire.gpu.global.u64 %0, [%1];" : "=l"(v) : "l"(p) : "memory"); return v;
}
__device__ __forceinline__ unsigned load_epoch(int b) {
    unsigned v; asm volatile("ld.global.u32 %0, [%1];" : "=r"(v) : "l"(at(g_epoch, b * 4)) : "memory"); return v + 1;
}
__device__ __forceinline__ unsigned ld_relaxed(const void* p) {
    unsigned v; asm volatile("ld.relaxed.gpu.global.u32 %0, [%1];" : "=r"(v) : "l"(p) : "memory"); return v;
}
__device__ __forceinline__ unsigned long long ld_relaxed64(const unsigned long long* p) {
    unsigned long long v; asm volatile("ld.relaxed.gpu.global.u64 %0, [%1];" : "=l"(v) : "l"(p) : "memory"); return v;
}
__device__ __forceinline__ void red_max64(unsigned long long* p, unsigned long long v) {
    asm volatile("red.relaxed.gpu.global.max.u64 [%0], %1;" ::"l"(p), "l"(v) : "memory");
}
__device__ __forceinline__ uint4 ld_relaxed128(const uint4* p) {
    uint4 v;
    asm volatile("{\n.reg .b128 t;\n.reg .b64 lo, hi;\nld.relaxed.gpu.global.b128 t, [%4];\nmov.b128 {lo, hi}, t;\n"
                 "mov.b64 {%0, %1}, lo;\nmov.b64 {%2, %3}, hi;\n}"
                 : "=r"(v.x), "=r"(v.y), "=r"(v.z), "=r"(v.w) : "l"(p) : "memory");
    return v;
}
__device__ __forceinline__ void st_relaxed128(uint4* p, const uint4& v) {
    asm volatile("{\n.reg .b128 t;\n.reg .b64 lo, hi;\nmov.b64 lo, {%1, %2};\nmov.b64 hi, {%3, %4};\nmov.b128 t, {lo, hi};\n"
                 "st.relaxed.gpu.global.b128 [%0], t;\n}"
                 ::"l"(p), "r"(v.x), "r"(v.y), "r"(v.z), "r"(v.w) : "memory");
}
__device__ __forceinline__ void st_relaxed64(unsigned long long* p, unsigned long long v) {
    asm volatile("st.relaxed.gpu.global.u64 [%0], %1;" ::"l"(p), "l"(v) : "memory");
}
__device__ __forceinline__ void st_release8(void* p, unsigned v) {
    asm volatile("st.release.gpu.global.u8 [%0], %1;" ::"l"(p), "r"(v) : "memory");
}
__device__ __forceinline__ uint64_t policy_evict_first() {
    uint64_t pol;
    asm("createpolicy.fractional.L2::evict_first.b64 %0, 1.0;" : "=l"(pol));
    return pol;
}
__device__ __forceinline__ uint4 ldg_stream(const void* p, uint64_t pol) {
    uint4 v;
    asm volatile("ld.global.nc.L1::no_allocate.L2::cache_hint.v4.u32 {%0,%1,%2,%3}, [%4], %5;"
                 : "=r"(v.x), "=r"(v.y), "=r"(v.z), "=r"(v.w) : "l"(p), "l"(pol));
    return v;
}
__device__ __forceinline__ uint4 ldg_ord(const void* p) {
    uint4 v;
    asm volatile("ld.relaxed.gpu.global.L1::no_allocate.v4.u32 {%0,%1,%2,%3}, [%4];"
                 : "=r"(v.x), "=r"(v.y), "=r"(v.z), "=r"(v.w) : "l"(p));
    return v;
}
template <int ID, int N> __device__ __forceinline__ void named_arrive() { asm volatile("bar.arrive %0, %1;" ::"n"(ID), "n"(N) : "memory"); }
template <int ID, int N> __device__ __forceinline__ void named_bar() { asm volatile("bar.sync %0, %1;" ::"n"(ID), "n"(N) : "memory"); }

__device__ __forceinline__ float bf_lo(uint32_t u) { return __uint_as_float(u << 16); }
__device__ __forceinline__ float bf_hi(uint32_t u) { return __uint_as_float(u & 0xffff0000u); }
__device__ __forceinline__ uint32_t pack_bf(float lo, float hi) {
    uint32_t r; asm("cvt.rn.bf16x2.f32 %0, %1, %2;" : "=r"(r) : "f"(hi), "f"(lo)); return r;
}
__device__ __forceinline__ float rbf(float v) { return __bfloat162float(__float2bfloat16_rn(v)); }
__device__ __forceinline__ float silu_f(float z) { return __fdividef(z, 1.0f + __expf(-z)); }
__device__ __forceinline__ uint32_t bsub2(uint32_t a, uint32_t b) {
    uint32_t r; asm("sub.rn.bf16x2 %0, %1, %2;" : "=r"(r) : "r"(a), "r"(b)); return r;
}
__device__ __forceinline__ uint32_t bfma2(uint32_t a, uint32_t b, uint32_t c) {
    uint32_t r; asm("fma.rn.bf16x2 %0, %1, %2, %3;" : "=r"(r) : "r"(a), "r"(b), "r"(c)); return r;
}
__device__ __forceinline__ uint32_t norm2(uint32_t xv, float m, float rinv) {
    uint32_t t = pack_bf(bf_lo(xv) - m, bf_hi(xv) - m);
    return pack_bf(bf_lo(t) * rinv, bf_hi(t) * rinv);
}
__device__ __forceinline__ float gate1(float z) {
    if (TANH) {
        float t;
        const float h = 0.5f * z;
        asm("tanh.approx.f32 %0, %1;" : "=f"(t) : "f"(h));
        return fmaf(h, t, h);
    }
    float e, r;
    asm("ex2.approx.ftz.f32 %0, %1;" : "=f"(e) : "f"(z * -1.4426950408889634f));
    asm("rcp.approx.ftz.f32 %0, %1;" : "=f"(r) : "f"(1.0f + e));
    return z * r;
}
__device__ __forceinline__ uint32_t gate2(uint32_t xv, uint32_t mean2, float r0, float r1) {
    const uint32_t t = bsub2(xv, mean2);
    return pack_bf(gate1(bf_lo(t) * r0), gate1(bf_hi(t) * r1));
}
__device__ __forceinline__ uint32_t silu2(uint32_t z) { return pack_bf(silu_f(bf_lo(z)), silu_f(bf_hi(z))); }

__device__ __forceinline__ void stmatrix4(uint32_t addr, uint32_t r0, uint32_t r1, uint32_t r2, uint32_t r3) {
    asm volatile("stmatrix.sync.aligned.m8n8.x4.shared.b16 [%0], {%1,%2,%3,%4};"
                 ::"r"(addr), "r"(r0), "r"(r1), "r"(r2), "r"(r3));
}
__device__ __forceinline__ void stmatrix4t(uint32_t addr, uint32_t r0, uint32_t r1, uint32_t r2, uint32_t r3) {
    asm volatile("stmatrix.sync.aligned.m8n8.x4.trans.shared.b16 [%0], {%1,%2,%3,%4};"
                 ::"r"(addr), "r"(r0), "r"(r1), "r"(r2), "r"(r3));
}
__device__ __forceinline__ void ldmatrix4t(uint32_t addr, uint32_t& r0, uint32_t& r1, uint32_t& r2, uint32_t& r3) {
    asm volatile("ldmatrix.sync.aligned.m8n8.x4.trans.shared.b16 {%0,%1,%2,%3}, [%4];"
                 : "=r"(r0), "=r"(r1), "=r"(r2), "=r"(r3) : "r"(addr));
}

__device__ __forceinline__ void wg_fence() { asm volatile("wgmma.fence.sync.aligned;" ::: "memory"); }
__device__ __forceinline__ void wg_commit() { asm volatile("wgmma.commit_group.sync.aligned;" ::: "memory"); }
template <int N> __device__ __forceinline__ void wg_wait() { asm volatile("wgmma.wait_group.sync.aligned %0;" ::"n"(N) : "memory"); }

__host__ __device__ constexpr uint32_t desc_lo(uint32_t addr, uint32_t lbo) { return ((addr & 0x3FFFF) >> 4) | ((lbo >> 4) << 16); }
#define DESC_HI "0x40000040"

#define R8(a, o) "+f"(a[(o) + 0]), "+f"(a[(o) + 1]), "+f"(a[(o) + 2]), "+f"(a[(o) + 3]), \
                 "+f"(a[(o) + 4]), "+f"(a[(o) + 5]), "+f"(a[(o) + 6]), "+f"(a[(o) + 7])
#define R64(a, o) R8(a, (o) + 0), R8(a, (o) + 8), R8(a, (o) + 16), R8(a, (o) + 24), \
                  R8(a, (o) + 32), R8(a, (o) + 40), R8(a, (o) + 48), R8(a, (o) + 56)

template <int O, int TA>
__device__ __forceinline__ void wgmma128(float (&a)[128], uint32_t da, uint32_t db, int scale_d) {
    asm volatile(
        "{\n.reg .pred p;\n.reg .b64 da, db;\nsetp.ne.b32 p, %66, 0;\n"
        "mov.b64 da, {%64, " DESC_HI "};\nmov.b64 db, {%65, " DESC_HI "};\n"
        "wgmma.mma_async.sync.aligned.m64n128k16.f32.bf16.bf16 "
        "{%0,%1,%2,%3,%4,%5,%6,%7,%8,%9,%10,%11,%12,%13,%14,%15,"
        "%16,%17,%18,%19,%20,%21,%22,%23,%24,%25,%26,%27,%28,%29,%30,%31,"
        "%32,%33,%34,%35,%36,%37,%38,%39,%40,%41,%42,%43,%44,%45,%46,%47,"
        "%48,%49,%50,%51,%52,%53,%54,%55,%56,%57,%58,%59,%60,%61,%62,%63},"
        "da, db, p, 1, 1, %67, 0;\n}"
        : R64(a, O)
        : "r"(da), "r"(db), "r"(scale_d), "n"(TA));
}
template <int O>
__device__ __forceinline__ void wgmma128_rs(float (&a)[128], const uint32_t* f, uint32_t db) {
    asm volatile(
        "{\n.reg .b64 db;\nmov.b64 db, {%68, 8};\n"
        "wgmma.mma_async.sync.aligned.m64n128k16.f32.bf16.bf16 "
        "{%0,%1,%2,%3,%4,%5,%6,%7,%8,%9,%10,%11,%12,%13,%14,%15,"
        "%16,%17,%18,%19,%20,%21,%22,%23,%24,%25,%26,%27,%28,%29,%30,%31,"
        "%32,%33,%34,%35,%36,%37,%38,%39,%40,%41,%42,%43,%44,%45,%46,%47,"
        "%48,%49,%50,%51,%52,%53,%54,%55,%56,%57,%58,%59,%60,%61,%62,%63},"
        "{%64, %65, %66, %67}, db, 1, 1, 1, 0;\n}"
        : R64(a, O)
        : "r"(f[0]), "r"(f[1]), "r"(f[2]), "r"(f[3]), "r"(db));
}
template <int O>
__device__ __forceinline__ void fence_regs64(float (&a)[128]) {
    asm volatile("" : R64(a, O)::"memory");
}

struct Params {
    const __nv_bfloat16* x;
    const __nv_bfloat16* dre;
    const __nv_bfloat16* dim;
    const __nv_bfloat16* wr;
    const __nv_bfloat16* wg;
    const __nv_bfloat16* wu;
    const __nv_bfloat16* wd;
    uint32_t zero;
};

__device__ __forceinline__ float warp_sum(float v) {
#pragma unroll
    for (int o = 16; o; o >>= 1) v += __shfl_xor_sync(0xffffffffu, v, o);
    return v;
}
__device__ __forceinline__ void fma8(float* acc, const uint4& w, float s) {
    acc[0] += s * bf_lo(w.x); acc[1] += s * bf_hi(w.x); acc[2] += s * bf_lo(w.y); acc[3] += s * bf_hi(w.y);
    acc[4] += s * bf_lo(w.z); acc[5] += s * bf_hi(w.z); acc[6] += s * bf_lo(w.w); acc[7] += s * bf_hi(w.w);
}
__device__ __forceinline__ int POS(int t) { return (t & ~15) | ((t & 6) << 1) | ((t & 8) >> 2) | (t & 1); }
__host__ __device__ constexpr int PSLOT(int j) { return j < 4 ? j : (j & 1) + ((j & 2) ? 0 : 4); }
__host__ __device__ constexpr int PPAR(int j) { return j < 4 ? 0 : ((j >> 2) ^ (j >> 1) ^ 1) & 1; }
__host__ __device__ constexpr int DSLOT(int it) { return (it & 3) + 2; }
__device__ __forceinline__ int KO(int cl) { return ((cl & 1) << 1) | (cl >> 1); }

__device__ __forceinline__ unsigned long long* sync_words() {
    uint32_t t;
    asm volatile("mov.u32 %0, %%smid;" : "=r"(t));
    t >>= 1;
    const uint32_t u = t - 32;
    return at(g_sync, (t < 32 ? t & 7 : t < 60 ? 8 + u - 7 * ((u * 37) >> 8) : 15) * 128);
}

__global__ void __cluster_dims__(2, 1, 1) __launch_bounds__(NTHREADS, 1)
fnet_fused_kernel(const __grid_constant__ CUtensorMap tm_x, const __grid_constant__ CUtensorMap tm_dre,
                  const __grid_constant__ CUtensorMap tm_dim, const __grid_constant__ CUtensorMap tm_cre,
                  const __grid_constant__ CUtensorMap tm_cim, const __grid_constant__ CUtensorMap tm_out,
                  const Params P) {
    extern __shared__ __align__(1024) uint8_t smem[];
    const unsigned long long tstart = clock64();
    const uint32_t sb = smem_u32(smem);
    const int tid = threadIdx.x, lane = tid & 31;
    const int warp = __shfl_sync(0xffffffffu, tid >> 5, 0);
    const int pr = blockIdx.x >> 1, p7 = ((pr - 36) * 37) >> 8;
    const int c = blockIdx.x & 1;
    const int g = pr < 4 ? 0 : pr < 36 ? (pr - 4) & 7 : pr - 35 - 7 * p7;
    const int r = pr < 4 ? 4 + pr : pr < 36 ? (pr - 4) >> 3 : 4 + p7;
    const int grp = 2 * r + c;
    const int b = g * 16 + grp;
    const uint32_t bar0 = sb + OFF_BAR;
    const uint32_t zero = P.zero;
#define BAR(i) (bar0 + 8u * (i))
#define CLUSTER_ARRIVE() asm volatile("barrier.cluster.arrive.relaxed.aligned;" ::: "memory")
#define CLUSTER_WAIT() asm volatile("barrier.cluster.wait.aligned;" ::: "memory")
    if ((sb & 0xffffffu) != SB0) return;

    if (warp == 12) {
        const CUtensorMap* tmD = c ? &tm_dim : &tm_dre;
#define LOAD0(it) do { \
            mbar_expect_tx(BAR(B_FS + DSLOT(it)), SLOT); tma_2d(sb + OFF_S + DSLOT(it) * SLOT, tmD, (it) * 64, r * 128, BAR(B_FS + DSLOT(it))); \
            mbar_expect_tx(BAR(B_FL + (it)), SLOT); tma_2d(sb + OFF_L + (it) * SLOT, &tm_x, (it) * 64, g * 256, BAR(B_FL + (it))); \
            mbar_expect_tx(BAR(B_FL + 4 + (it)), SLOT); tma_2d(sb + OFF_L + (4 + (it)) * SLOT, &tm_x, (it) * 64, g * 256 + 128, BAR(B_FL + 4 + (it))); \
        } while (0)
        if (elect_one()) {
            prefetch_tmap(tmD); prefetch_tmap(&tm_x);
            mbar_init(BAR(B_FS + 2), 1); mbar_init(BAR(B_FL), 1); mbar_init(BAR(B_FL + 4), 1);
            fence_async_smem();
            LOAD0(0);
#pragma unroll
            for (int i = 0; i < B_COUNT; i++)
                if (i != B_FS + 2 && i != B_FL && i != B_FL + 4)
                    mbar_init(BAR(i), (i >= B_ES && i < B_FL) || i == B_GO ? 2 : i == B_STATS || i == B_LST ? 4 : 1);
            mbar_expect_tx(BAR(B_RECV), SLOT); mbar_expect_tx(BAR(B_RECV + 1), SLOT);
            mbar_expect_tx(BAR(B_PEER), 1024); mbar_expect_tx(BAR(B_H), 128);
            *reinterpret_cast<volatile uint32_t*>(smem + OFF_SEL + 8) = 0;
            asm volatile("fence.mbarrier_init.release.cluster;" ::: "memory");
            fence_async_smem();
        }
        __syncwarp();
        CLUSTER_ARRIVE();
        if (elect_one()) {
#pragma unroll 1
            for (int it = 1; it < 4; it++) LOAD0(it);
        }
        __syncwarp();
    } else {
        CLUSTER_ARRIVE();
        if (K0 && tid == 13 * 32) red_max64(sync_words(), tstart);
    }

    if (warp >= 12) {
        asm volatile("setmaxnreg.dec.sync.aligned.u32 %0;" ::"n"(PROD_REGS));
        CLUSTER_WAIT();
        if (warp == 12) {
            if (elect_one()) {
                const CUtensorMap* tmD = c ? &tm_dim : &tm_dre;
#pragma unroll 1
                for (int it = 4; it < 16; it++) {
                    const int s = DSLOT(it);
                    mbar_wait(BAR(B_ES + s), ((it >> 2) & 1) ^ 1);
                    TRACE(it);
                    mbar_expect_tx(BAR(B_FS + s), SLOT);
                    tma_2d(sb + OFF_S + s * SLOT, tmD, it * 64, r * 128, BAR(B_FS + s));
                }
                const unsigned ep = load_epoch(b), e8 = ep & 0xffu;
                const uint8_t* abg = at(g_ab, grp * 32 * SLOT);
                const unsigned long long* fl = at(g_flag, grp * 128);
                unsigned long long rdy = ld_acquire64(fl);
                mbar_wait(BAR(B_SRD), 0);
                st_release8(at(g_flag, grp * 128 + g), e8);
                PROF_T(7);
                int j = 4;
#pragma unroll 1
                for (int cl = 0; cl < 4; cl++) {
                    if (cl) rdy = ld_acquire64(fl + cl);
                    fence_async_global();
#pragma unroll 1
                    for (int n = 1; n < 8; n++, j++) {
                        const int q = (g + n) & 7, s = (j & 1) + ((j & 2) ? 0 : 4);
                        mbar_wait(BAR(B_ES + s), ((j >> 2) ^ (j >> 1)) & 1);
                        if (j == 7) mbar_wait(BAR(B_SRD + 1), 0);
                        if (((unsigned)(rdy >> (8 * q)) & 0xffu) != e8) {
                            int m = 0;
                            do { rdy = ld_acquire64(fl + cl); } while (((unsigned)(rdy >> (8 * q)) & 0xffu) != e8 && ++m < SPIN_LIMIT);
                            fence_async_global();
                        }
                        TRACE(16 + j);
                        mbar_expect_tx(BAR(B_FS + s), SLOT);
                        bulk_g2s(sb + OFF_S + s * SLOT, at(abg, (4 * q + KO(cl)) * SLOT), SLOT, BAR(B_FS + s));
                    }
                }
                *at(g_epoch, b * 4) = ep;
            }
        } else if (warp < 15) {
            if (elect_one()) {
                const int w = warp - 13, row0 = g * 256 + w * 128;
                const CUtensorMap* tmC = c ? &tm_cim : &tm_cre;
                const uint32_t fb = BAR(B_FL + 4 * w), eb = BAR(B_EL + 4 * w), dst = sb + OFF_L + w * 4 * SLOT;
                prefetch_tmap(w ? &tm_out : tmC);
                int it = 4;
                unsigned long long* sy = sync_words();
#define ADOPT(ph, lag) do { const unsigned long long v = ld_relaxed64(sy++); \
                    if (v - (ph) - SYNCMIN < SYNCCAP) *reinterpret_cast<volatile uint32_t*>(smem + OFF_SEL + 8) = (uint32_t)v - (lag); } while (0)
                if (w == 0 && K0) { sleep_until((uint32_t)tstart + KRD); ADOPT(tstart, 0u - K0); }
#define LOADL(tm, kb) do { const int s = it & 3; \
                    mbar_wait(eb + 8 * s, ((it >> 2) & 1) ^ 1); \
                    const unsigned long long ph = clock64() - 1024u * (it - 4); \
                    TRACE(64 + w * 64 + it - 4); \
                    mbar_expect_tx(fb + 8 * s, SLOT); \
                    tma_2d(dst + s * SLOT, tm, (kb) * 64, row0, fb + 8 * s); \
                    if (w == 0) { \
                        if (((SYNCS << 4) >> it) & 1) red_max64(sy, ph); \
                        if (((SYNCS << (4 + SYNCD)) >> it) & 1) ADOPT(ph, SYNCLAG); \
                    } \
                    it++; } while (0)
#pragma unroll 1
                while (it < 16) LOADL(&tm_x, it);
#pragma unroll 1
                for (int cl = 0; cl < 4; cl++) LOADL(tmC, 4 * g + KO(cl));
#pragma unroll 1
                for (int cl = 0; cl < 4; cl++) {
#pragma unroll 1
                    for (int n = 1; n < 8; n++) LOADL(tmC, 4 * ((g + n) & 7) + KO(cl));
                }
            }
        } else {
            const unsigned ep = load_epoch(b);
            uint4 f[4];
#define GATHER(ptr, cnt, valid) do { int n = 0; bool ok; do { ok = true; \
                _Pragma("unroll") for (int i = 0; i < (cnt); i++) { f[i] = ld_relaxed128((ptr) + i * 32); ok = ok && (valid); } \
                if (__all_sync(0xffffffffu, ok)) break; \
                __nanosleep(GSL); \
            } while (++n < SPIN_LIMIT); } while (0)
            {
                sleep_until((uint32_t)tstart + 6000);
                const uint4* keys = at(reinterpret_cast<const uint4*>(g_key), lane * 16);
                bool mine = false;
                int n = 0;
                do {
                    f[0] = ld_relaxed128(keys); f[1] = ld_relaxed128(keys + 32);
                    if (__all_sync(0xffffffffu, f[0].y == ep && f[0].w == ep && f[1].y == ep && f[1].w == ep)) break;
                    if (!mine) {
                        mbar_wait(BAR(B_LST), 0);
                        const uint4 k = *reinterpret_cast<const uint4*>(smem + OFF_XB);
                        if (lane == 0) st_relaxed64(at(g_key, b * 8), ((unsigned long long)ep << 32) | max(max(k.x, k.y), max(k.z, k.w)));
                        mine = true;
                    }
                    __nanosleep(GSL);
                } while (++n < SPIN_LIMIT);
                const unsigned key = __reduce_max_sync(0xffffffffu, max(max(f[0].x, f[0].z), max(f[1].x, f[1].z)));
                if (lane == 0) { *reinterpret_cast<unsigned*>(smem + OFF_SEL) = key; mbar_arrive(BAR(B_SEL)); PROF_T(8); }
            }
            if (elect_one()) {
#pragma unroll 1
                for (int cl = 0; cl < 4; cl++) {
                    uint8_t* dst = at(g_ab, (grp * 32 + 4 * g + KO(cl)) * SLOT);
                    const uint32_t src = sb + OFF_S + cl * SLOT, chunk = cl ? 4096 : SLOT;
                    mbar_wait(BAR(B_FS + cl), 0);
                    if (cl == 0) PROF_T(3);
                    uint32_t t0 = clock32() + (cl == 1 ? PDEL : 0);
#pragma unroll 1
                    for (uint32_t o = 0; o < SLOT; o += chunk) {
                        sleep_until(t0);
                        bulk_s2g(dst + o, src + o, chunk);
                        bulk_commit();
                        t0 += PGAP;
                    }
                    bulk_wait<0>();
                    TRACE(252 + cl);
                    if (cl < 2) mbar_arrive(BAR(B_SRD + cl));
                    else {
                        mbar_wait(BAR(B_ES + cl), 0);
                        mbar_expect_tx(BAR(B_FS + cl), SLOT);
                        tma_2d(src, &tm_x, grp * 64, g * 256 + (cl - 2) * 128, BAR(B_FS + cl));
                    }
                    if (cl) st_release8(at(g_flag, grp * 128 + cl * 8 + g), ep & 0xffu);
                    if (cl == 1) PROF_T(5);
                    if (cl == 3) PROF_T(4);
                }
            }
        }
    } else if (warp >= 8) {
        asm volatile("setmaxnreg.dec.sync.aligned.u32 %0;" ::"n"(512 - PROD_REGS - 2 * CONS_REGS));
        const int aw = warp - 8, mt = tid - 256;
        const unsigned ep = load_epoch(b);
        {
            const int row = b * 16 + aw * 4;
            const __nv_bfloat16* xp = at(P.x, (row * D_ + lane * 8) * 2);
            const __nv_bfloat16* dp = at(c ? P.dim : P.dre, ((r * 128 + g * 16 + aw * 4) * D_ + lane * 8) * 2);
            const __nv_bfloat16* wr = at(P.wr, lane * 16);
            uint4 v[4][4], w[4];
#define SLOAD(i) do { w[i] = ldg_ord(wr + (i) * 256); \
                _Pragma("unroll") for (int k = 0; k < 4; k++) v[i][k] = ldg_ord(xp + k * D_ + (i) * 256); } while (0)
            if (SDEL) __nanosleep(SDEL);
            SLOAD(0);
            __nanosleep(SGAP);
            SLOAD(1);
            __nanosleep(0);
            float x0[4], s1[4], s2[4], sx[4], sd[4], sw = 0.f;
#pragma unroll
            for (int k = 0; k < 4; k++) { x0[k] = bf_lo(v[0][k].x); s1[k] = 0.f; s2[k] = 0.f; sx[k] = 0.f; }
#pragma unroll
            for (int i = 0; i < 4; i++) {
                const float wf[8] = {bf_lo(w[i].x), bf_hi(w[i].x), bf_lo(w[i].y), bf_hi(w[i].y), bf_lo(w[i].z), bf_hi(w[i].z), bf_lo(w[i].w), bf_hi(w[i].w)};
                sw += ((wf[0] + wf[1]) + (wf[2] + wf[3])) + ((wf[4] + wf[5]) + (wf[6] + wf[7]));
#pragma unroll
                for (int k = 0; k < 4; k++) {
                    x0[k] = __shfl_sync(0xffffffffu, x0[k], 0);
                    const uint32_t xv[4] = {v[i][k].x, v[i][k].y, v[i][k].z, v[i][k].w};
#pragma unroll
                    for (int e = 0; e < 4; e++) {
                        const float a0 = bf_lo(xv[e]) - x0[k], a1 = bf_hi(xv[e]) - x0[k];
                        s1[k] += a0 + a1;
                        s2[k] = fmaf(a0, a0, fmaf(a1, a1, s2[k]));
                        sx[k] = fmaf(a0, wf[2 * e], fmaf(a1, wf[2 * e + 1], sx[k]));
                    }
                    yield(sx[k], zero);
                    if (k == 0 && i < 2) { SLOAD(i + 2); __nanosleep(0); }
                    if (i >= 2) v[i - 2][k] = ldg_ord(dp + k * D_ + (i - 2) * 256);
                }
            }
#pragma unroll
            for (int k = 0; k < 8; k++) v[2 + (k >> 2)][k & 3] = ldg_ord(dp + (k & 3) * D_ + (2 + (k >> 2)) * 256);
#define FOLD4(a) do { const bool u16 = lane & 16, u8 = lane & 8; \
                float p0 = (u16 ? a[2] : a[0]) + __shfl_xor_sync(0xffffffffu, u16 ? a[0] : a[2], 16); \
                float p1 = (u16 ? a[3] : a[1]) + __shfl_xor_sync(0xffffffffu, u16 ? a[1] : a[3], 16); \
                a[0] = (u8 ? p1 : p0) + __shfl_xor_sync(0xffffffffu, u8 ? p0 : p1, 8); \
                _Pragma("unroll") for (int o = 4; o; o >>= 1) a[0] += __shfl_xor_sync(0xffffffffu, a[0], o); } while (0)
            FOLD4(s1); FOLD4(s2); FOLD4(sx);
            sw = warp_sum(sw);
            const int rr = lane >> 3;
            const float c0 = rr == 0 ? x0[0] : rr == 1 ? x0[1] : rr == 2 ? x0[2] : x0[3];
            const float dm = s1[0] * (1.0f / D_);
            const float mb = rbf(c0 + dm);
            const float rinv = 1.0f / rbf(sqrtf(rbf(rbf(fmaxf(s2[0] * (1.0f / D_) - dm * dm, 0.f)) + 1e-5f)));
            unsigned u = __bfloat16_as_ushort(__float2bfloat16_rn((sx[0] + (c0 - mb) * sw) * rinv));
            u = (u & 0x8000u) ? (~u & 0xffffu) : (u | 0x8000u);
            u = (u << 16) | (0xffffu - (unsigned)(row + rr));
            const uint4 rec = make_uint4(__float_as_uint(mb), __float_as_uint(rinv), ep, u);
            if ((lane & 7) == 0) st_relaxed128(at(g_stat, (row + rr) * 16), rec);
            CLUSTER_WAIT();
            u = __reduce_max_sync(0xffffffffu, u);
            if (lane == 0) { *reinterpret_cast<unsigned*>(smem + OFF_XB + aw * 4) = u; mbar_arrive(BAR(B_LST)); }
            if (mt == 0) PROF_T(2);
            float run = 0.f;
#pragma unroll
            for (int k = 0; k < 4; k++) {
                run = __uint_as_float(__float_as_uint(run) & zero);
#pragma unroll
                for (int i = 0; i < 4; i++) {
                    const uint32_t dv[4] = {v[i][k].x, v[i][k].y, v[i][k].z, v[i][k].w};
#pragma unroll
                    for (int e = 0; e < 4; e++) run = (run + bf_lo(dv[e])) + bf_hi(dv[e]);
                }
                sd[k] = run;
            }
            FOLD4(sd);
            const float nb = __shfl_down_sync(0xffffffffu, sd[0], 8);
            if ((lane & 15) == 0)
                st_relaxed128(at(g_rs, (grp * 64 + g * 8 + aw * 2 + (lane >> 4)) * 16), make_uint4(__float_as_uint(sd[0]), ep, __float_as_uint(nb), ep));
            if (mt == 0) PROF_T(6);
            uint4 f[4];
            if (aw < 2) {
                const int t = aw * 128 + lane;
                GATHER(at(g_stat, (g * 256 + t) * 16), 4, f[i].z == ep);
#pragma unroll
                for (int i = 0; i < 4; i++) {
                    *reinterpret_cast<uint32_t*>(smem + OFF_RSTD + (POS(t) + i * 32) * 4) = f[i].y;
                    *reinterpret_cast<uint16_t*>(smem + OFF_MEAN + (POS(t) + i * 32) * 2) = (uint16_t)(f[i].x >> 16);
                }
            } else {
                const int e2 = (aw - 2) * 32 + lane;
                GATHER(at(g_rs, (grp * 64 + e2) * 16), 1, f[i].y == ep && f[i].w == ep);
#pragma unroll
                for (int i = 0; i < 2; i++) {
                    const float v = __uint_as_float(i ? f[0].z : f[0].x);
                    const float hi = rbf(v), mid = rbf(v - hi), lo = v - hi - mid;
                    *reinterpret_cast<uint4*>(smem + OFF_S + SLOT + (e2 * 2 + i) * 16) = make_uint4(pack_bf(hi, mid), pack_bf(lo, 0.f), 0, 0);
                }
            }
            fence_async_smem();
            __syncwarp();
            if (lane == 0) mbar_arrive(BAR(B_STATS));
            if (mt == 127) PROF_T(9);
        }
        const int pair = g * 7 + r;
        if (r < 7) {
            const uint64_t pol = policy_evict_first();
            const __nv_bfloat16* wp = at((aw & 1) ? P.wu : P.wg, ((c * 512 + (aw >> 1) * 256 + (lane >> 3) * 8) * F_ + pair * 64 + (lane & 7) * 8) * 2);
            uint4 b0[8], b1[8];
#define FILL(buf, str) do { _Pragma("unroll") for (int q = 0; q < 8; q++) buf[q] = ldg_stream(wp + q * (str), pol); } while (0)
            FILL(b0, F_);
            mbar_wait(BAR(B_SEL), 0);
            uint4 xn;
            {
                const int sel = 0xffff - (int)(*reinterpret_cast<volatile unsigned*>(smem + OFF_SEL) & 0xffffu);
                xn = __ldg(reinterpret_cast<const uint4*>(at(P.x, (sel * D_ + c * 512 + (aw >> 1) * 256 + (lane & 7) * 32 + (lane >> 3) * 8) * 2)));
                uint4 f[1];
                GATHER(at(g_stat, sel * 16), 1, f[i].z == ep);
                const float m = __uint_as_float(f[0].x), ri = __uint_as_float(f[0].y);
                xn = make_uint4(norm2(xn.x, m, ri), norm2(xn.y, m, ri), norm2(xn.z, m, ri), norm2(xn.w, m, ri));
            }
            float ag[8];
#pragma unroll
            for (int i = 0; i < 8; i++) ag[i] = 0.f;
            const uint32_t stag = (aw * 4 + (grp & 3)) * ESTAG;
            uint32_t te = clock32() + stag;
            bool paused = !QUIET;
#define ROUND(cur, nxt, rd) do { \
                if (!paused && mbar_test(BAR(B_QUIET), 0)) { mbar_wait_sleep(BAR(B_GO), 0); te = clock32() + stag; paused = true; } \
                sleep_until(te); \
                te = clock32() + (paused ? EGAP2 : EGAP1); \
                if (lane == 0) TRACE(192 + aw * 12 + (rd)); \
                if ((rd) == 7) wp = at(P.wd - 16 * D_, ((pair * 64 + (lane >> 4) * 8) * D_ + c * 512 + aw * 128 + (lane & 15) * 8) * 2); \
                wp = at(wp, ((rd) < 7 ? 64 * F_ : 32 * D_) + (cur[7].x & zero)); \
                if ((rd) < 7) FILL(nxt, F_); else if ((rd) != 8 && (rd) < 11) FILL(nxt, D_); \
                _Pragma("unroll") for (int q = 0; q < 8; q += 2) { \
                    uint32_t xw = __shfl_sync(0xffffffffu, q == 0 ? xn.x : q == 2 ? xn.y : q == 4 ? xn.z : xn.w, (lane & 24) | ((rd) & 7)); \
                    fma8(ag, cur[q], bf_lo(xw)); \
                    if (YLD > 1) { yield(ag[7], zero); xw = __shfl_sync(0xffffffffu, xw, lane); } \
                    fma8(ag, cur[q + 1], bf_hi(xw)); \
                    if (q < 6) yield(ag[7], zero); \
                } } while (0)
#pragma unroll 1
            for (int rd = 0; rd < 12; rd += 2) {
                ROUND(b0, b1, rd);
                ROUND(b1, b0, rd + 1);
                if (rd == 6) { wp += 16 * D_; FILL(b1, D_); wp -= 16 * D_; }
                if (rd == 6 || rd == 10) {
#pragma unroll
                    for (int i = 0; i < 8; i++) ag[i] += __shfl_xor_sync(0xffffffffu, ag[i], 16);
                }
                if (rd == 6) {
#pragma unroll
                    for (int i = 0; i < 8; i++) ag[i] += __shfl_xor_sync(0xffffffffu, ag[i], 8);
                    if (lane < 8) {
                        const uint32_t dst = mapa(sb + OFF_XB + (c * 4 + aw) * 128 + (lane & 3) * 32, lane >> 2), pb = mapa(BAR(B_PEER), lane >> 2);
                        st_async4(dst, __float_as_uint(ag[0]), __float_as_uint(ag[1]), __float_as_uint(ag[2]), __float_as_uint(ag[3]), pb);
                        st_async4(dst + 16, __float_as_uint(ag[4]), __float_as_uint(ag[5]), __float_as_uint(ag[6]), __float_as_uint(ag[7]), pb);
                    }
                    if (aw == 3) {
                        mbar_wait_cluster(BAR(B_PEER), 0);
                        const float* ps = reinterpret_cast<const float*>(smem + OFF_XB) + lane;
                        const float go = (ps[0] + ps[64]) + (ps[128] + ps[192]), uo = (ps[32] + ps[96]) + (ps[160] + ps[224]);
                        const float h = rbf(silu_f(rbf(go))) * rbf(uo), ho = __shfl_xor_sync(0xffffffffu, h, 1);
                        asm volatile("st.async.weak.shared::cluster.mbarrier::complete_tx::bytes.b32 [%0], %1, [%2];"
                                     ::"r"(mapa(sb + OFF_H + c * 64 + (lane >> 1) * 4, lane & 1)), "r"((lane & 1) ? pack_bf(ho, h) : pack_bf(h, ho)),
                                       "r"(mapa(BAR(B_H), lane & 1)) : "memory");
                    }
                    mbar_wait_cluster(BAR(B_H), 0);
                    xn = *reinterpret_cast<const uint4*>(smem + OFF_H + (lane & 3) * 32 + (lane >> 4) * 16);
#pragma unroll
                    for (int i = 0; i < 8; i++) ag[i] = 0.f;
                    if (mt == 0) PROF_T(10);
                }
            }
            const int hi = lane >> 4;
            st_relaxed128(at(g_part, pair * 4096 + (c * 8 + aw * 2 + ((lane >> 3) & 1)) * 256 + hi * 128 + (lane & 7) * 16),
                          make_uint4((__float_as_uint(hi ? ag[4] : ag[0]) & ~15u) | (ep & 15u), __float_as_uint(hi ? ag[5] : ag[1]),
                                     __float_as_uint(hi ? ag[6] : ag[2]), __float_as_uint(hi ? ag[7] : ag[3])));
            if (mt == 0) PROF_T(11);
        } else {
            mbar_wait_sleep(BAR(B_SEL), 0);
        }
        const int sel = 0xffff - (int)(*reinterpret_cast<volatile unsigned*>(smem + OFF_SEL) & 0xffffu);
        if ((sel >> 8) == g) {
            const int col = (lane & 7) * 8 + ((lane >> 3) & 1) * 4;
            const uint2 xv = __ldg(reinterpret_cast<const uint2*>(at(P.x, (sel * D_ + grp * 64 + col) * 2)));
            uint4 f[1];
            GATHER(at(g_stat, sel * 16), 1, f[i].z == ep);
            const uint4 rec = f[0];
            const uint4* src = at(g_part, (aw * 14 + (lane >> 4)) * 4096 + grp * 256 + (lane & 15) * 16);
            if (r == 7) {
                int n = 0;
                while (((ld_relaxed(src) ^ ep) & 15u) != 0 && ++n < SPIN_LIMIT) __nanosleep(500);
            }
            uint4 t[7];
            int n = 0;
            bool ok;
            do {
                ok = true;
#pragma unroll
                for (int u = 0; u < 7; u++) { t[u] = ld_relaxed128(src + u * 512); ok = ok && ((t[u].x ^ ep) & 15u) == 0; }
            } while (!__all_sync(0xffffffffu, ok) && ++n < SPIN_LIMIT);
            float4 a = make_float4(0.f, 0.f, 0.f, 0.f);
#pragma unroll
            for (int u = 0; u < 7; u++) {
                a.x += __uint_as_float(t[u].x & ~15u); a.y += __uint_as_float(t[u].y); a.z += __uint_as_float(t[u].z); a.w += __uint_as_float(t[u].w);
            }
            a.x += __shfl_xor_sync(0xffffffffu, a.x, 16); a.y += __shfl_xor_sync(0xffffffffu, a.y, 16);
            a.z += __shfl_xor_sync(0xffffffffu, a.z, 16); a.w += __shfl_xor_sync(0xffffffffu, a.w, 16);
            float4* park = reinterpret_cast<float4*>(smem + OFF_XB) + (lane & 15);
            if (lane < 16) park[aw * 16] = a;
            named_bar<4, 128>();
            if (aw == 0) {
                const float4 p1 = park[16], p2 = park[32], p3 = park[48];
                a.x = (a.x + p1.x) + (p2.x + p3.x); a.y = (a.y + p1.y) + (p2.y + p3.y);
                a.z = (a.z + p1.z) + (p2.z + p3.z); a.w = (a.w + p1.w) + (p2.w + p3.w);
                unsigned u = rec.w >> 16;
                u = (u & 0x8000u) ? (u & 0x7fffu) : (~u & 0xffffu);
                const float sg = rbf(__fdividef(1.0f, 1.0f + __expf(-__uint_as_float(u << 16))));
                const float m = __uint_as_float(rec.x), ri = __uint_as_float(rec.y);
                const uint32_t n0 = norm2(xv.x, m, ri), n1 = norm2(xv.y, m, ri);
                uint2 o;
                o.x = silu2(pack_bf(bf_lo(n0) + rbf(rbf(a.x) * sg), bf_hi(n0) + rbf(rbf(a.y) * sg)));
                o.y = silu2(pack_bf(bf_lo(n1) + rbf(rbf(a.z) * sg), bf_hi(n1) + rbf(rbf(a.w) * sg)));
                if (lane < 16) *reinterpret_cast<uint2*>(smem + OFF_H + col * 2) = o;
                if (lane == 0) *reinterpret_cast<int*>(smem + OFF_SEL + 4) = sel & 255;
                __syncwarp();
                if (lane == 0) { mbar_arrive(BAR(B_UPD)); PROF_T(12); }
            }
        } else if (mt == 0) {
            *reinterpret_cast<int*>(smem + OFF_SEL + 4) = -1;
            mbar_arrive(BAR(B_UPD));
        }
    } else {
        asm volatile("setmaxnreg.inc.sync.aligned.u32 %0;" ::"n"(CONS_REGS));
        CLUSTER_WAIT();
        const int wg = warp >> 2, wq = warp & 3;
        const int wt = tid & 127;
        float acc[128];
        const uint32_t fL = BAR(B_FL + 4 * wg), eL = BAR(B_EL + 4 * wg);
        const uint32_t dL = desc_lo(SB0 + OFF_L, 16) + wg * 4096;
        constexpr uint32_t dS = desc_lo(SB0 + OFF_S, 16);
        constexpr uint32_t SL = SLOT >> 4;
#define RELEASE(ls, ss) do { if (wt == 0) { mbar_arrive(eL + 8u * (ls)); mbar_arrive(BAR(B_ES + (ss))); } } while (0)
#define WAIT_FULL(ls, lph, ss, sph) do { mbar_wait(BAR(B_FS + (ss)), sph); mbar_wait(fL + 8u * (ls), lph); } while (0)
#define TURN() do { if (wg) named_bar<6, 256>(); else named_bar<5, 256>(); } while (0)
#define PASS() do { if (wg) named_arrive<5, 256>(); else named_arrive<6, 256>(); } while (0)
#define WG_BAR() do { if (wg) named_bar<2, 128>(); else named_bar<1, 128>(); } while (0)
        uint32_t held = 0, tgt = 0;
#define PEEK() do { if (wg == 0) tgt = *reinterpret_cast<volatile uint32_t*>(smem + OFF_SEL + 8); } while (0)
#define HOLD(step) do { if (tgt != held) { held = tgt; sleep_until(tgt + 1024u * (step) - 100u); \
                int n = 0; while ((int)(clock32() - tgt - 1024u * (step)) < 0 && ++n < SPIN_LIMIT) {} } } while (0)
        if (wg == 1) PASS();

#define MMA1_P(O, s, first, pass) do { _Pragma("unroll") for (int kk = 0; kk < 4; kk++) { if (kk == PK && (pass)) PASS(); \
            wgmma128<O, 0>(acc, dL + (s) * SL + kk * 2 + (O) * 8, dS + DSLOT(s) * SL + kk * 2, !((first) && kk == 0)); } \
            if (PK == 4 && (pass)) PASS(); } while (0)
#define MMA1_H(O, s, first) MMA1_P(O, s, first, false)
#define WAIT1(s, ph) WAIT_FULL(s, ph, DSLOT(s), ph)
#define PROBE(ls, lph, ss, sph) (mbar_test(BAR(B_FS + (ss)), sph) & mbar_test(fL + 8u * (ls), lph))
#define REL1(s) RELEASE(s, DSLOT(s))
#pragma unroll 1
        for (int it = 0; it < 12; it++) {
            const int s = it & 3;
            const bool ok = PROBE(s, (it >> 2) & 1, DSLOT(s), (it >> 2) & 1);
            PEEK();
            if (it) { wg_wait<0>(); REL1((it - 1) & 3); }
            if (!ok) WAIT1(s, (it >> 2) & 1);
            HOLD(it);
            TURN();
            wg_fence(); MMA1_H(0, s, it == 0); MMA1_P(64, s, it == 0, true); wg_commit();
            if (it == QJ && tid == 0) { mbar_arrive(BAR(B_QUIET)); PROF_T(15); }
            if (it == 0 && tid == 0) PROF_T(16);
        }
        TS(12);
        mbar_wait(BAR(B_STATS), 0);
        float rs[4];
        uint32_t nm[8];
        {
            const int p0 = POS(wg * 128 + wq * 16 + (lane >> 2));
            const uint32_t msk = (lane & 3) == 0 ? 0xffffffffu : (lane & 3) == 1 ? 0x0000ffffu : 0u;
#pragma unroll
            for (int i = 0; i < 4; i++) {
                const int p = p0 + (i & 1) * 2 + (i >> 1) * 64;
                rs[i] = *reinterpret_cast<const float*>(smem + OFF_RSTD + p * 4);
                const uint32_t m = *reinterpret_cast<const uint16_t*>(smem + OFF_MEAN + p * 2) ^ 0x8000u;
                nm[i + (i & 2)] = (m | (m << 16)) & msk;
                nm[i + (i & 2) + 2] = 0;
            }
            asm volatile("" : "+r"(nm[0]), "+r"(nm[1]), "+r"(nm[2]), "+r"(nm[3]), "+r"(nm[4]), "+r"(nm[5]), "+r"(nm[6]), "+r"(nm[7])::"memory");
        }
        WAIT1(0, 1);
        TS(13);
        wg_wait<0>(); REL1(3);
        TS(14);
        TURN();
        wg_fence();
        wgmma128_rs<0>(acc, nm, (SB0 + OFF_S + SLOT) >> 4);
        wgmma128_rs<64>(acc, nm + 4, (SB0 + OFF_S + SLOT) >> 4);
        MMA1_H(0, 0, false);
        if (QJ == 12 && tid == 0) { mbar_arrive(BAR(B_QUIET)); PROF_T(15); }
#pragma unroll
        for (int s = 1; s < 4; s++) { WAIT1(s, 1); wg_fence(); MMA1_P(0, s, false, s == 3); }
        wg_commit();
        const int mrow = wq * 16 + ((lane >> 3) & 1) * 8 + (lane & 7);
#define EPI1(O, slot, FREE) do { const uint32_t dst = sb + OFF_S + (slot) * SLOT + mrow * 128; \
            uint32_t pk[32]; \
            _Pragma("unroll") for (int i = 0; i < 32; i += 4) { \
                _Pragma("unroll") for (int k = 0; k < 4; k++) \
                    pk[i + k] = pack_bf(acc[(O) + 2 * (i + k)] * rs[(O) / 32 + (k & 1)], acc[(O) + 2 * (i + k) + 1] * rs[(O) / 32 + (k & 1)]); \
                if (i == EF) { FREE; } \
                if (i >= EF) { _Pragma("unroll") for (int v = (i == EF ? 0 : i); v <= i; v += 4) \
                    stmatrix4(dst + ((v >> 4) ^ c ^ 1) * 8192 + ((((v >> 1) & 7) + (lane >> 4)) ^ (lane & 7)) * 16, pk[v], pk[v + 1], pk[v + 2], pk[v + 3]); } } \
            fence_async_smem(); WG_BAR(); \
            if (wt == 0) mbar_arrive(BAR(B_FS + (slot))); } while (0)
        TS(15);
        wg_wait<0>();
        fence_regs64<0>(acc);
        TS(16);
        {
            constexpr int EF = 0;
            EPI1(0, wg, if (wg) mbar_wait(BAR(B_FS), 0));
        }
        TS(17);
        TURN();
        wg_fence();
        MMA1_H(64, 0, false); wg_commit();
        MMA1_H(64, 1, false); wg_commit();
        MMA1_H(64, 2, false); wg_commit();
        wg_wait<2>(); REL1(0);
        MMA1_P(64, 3, false, true); wg_commit();
        TS(18);
        wg_wait<2>(); REL1(1);
        wg_wait<1>(); REL1(2);
        wg_wait<0>(); REL1(3);
        fence_regs64<64>(acc);
        TS(19);
        {
            constexpr int EF = 12;
            EPI1(64, 2 + wg, mbar_wait(BAR(B_ES + 2 + wg), 1));
        }
        TS(20);

        float ac2[128];
#define MMA2_P(O, ls, ss, first, pass) do { _Pragma("unroll") for (int kk = 0; kk < 4; kk++) { if (kk == PK && (pass)) PASS(); \
            wgmma128<O, 1>(ac2, dS + (ss) * SL + kk * 128 + (O) * 8, dL + (ls) * SL + kk * 2, !((first) && kk == 0)); } \
            if (PK == 4 && (pass)) PASS(); } while (0)
#define MMA2_H(O, ls, ss, first) MMA2_P(O, ls, ss, first, false)
#define WAIT2(j) WAIT_FULL((j) & 3, ((j) >> 2) & 1, PSLOT(j), PPAR(j))
#define MMA2(j, pass) do { wg_fence(); MMA2_H(0, (j) & 3, PSLOT(j), (j) == 0); MMA2_P(64, (j) & 3, PSLOT(j), (j) == 0, pass); wg_commit(); } while (0)
#define REL2(j) RELEASE((j) & 3, PSLOT(j))
        if (GOJ == 0 && wt == 0) mbar_arrive(BAR(B_GO));
        WAIT2(0); TURN(); MMA2(0, false);
        WAIT2(1); MMA2(1, true);
        TS(21);
        wg_wait<1>(); REL2(0);
        TS(22);
        {
            uint32_t sp = 1;
#pragma unroll 1
            for (int j = 2; j < XJ; j++) {
                const uint32_t ss = PSLOT(j);
                const bool ok = PROBE(j & 3, (j >> 2) & 1, ss, PPAR(j));
                PEEK();
                wg_wait<0>(); RELEASE((j - 1) & 3, sp);
                if (!ok) WAIT_FULL(j & 3, (j >> 2) & 1, ss, PPAR(j));
                HOLD(16 + j);
                TURN();
                wg_fence(); MMA2_H(0, j & 3, ss, false); MMA2_P(64, j & 3, ss, false, true); wg_commit();
                if (j == GOJ && wt == 0) { mbar_arrive(BAR(B_GO)); if (wg == 0) PROF_T(19); }
                sp = ss;
            }
        }
        if (tid == 0) PROF_T(20);
        uint32_t gt[32];
        const uint32_t xrow = sb + OFF_S + (2 + wg) * SLOT + ((lane >> 4) * 8 + (lane & 7)) * 128 + (((2 * wq + ((lane >> 3) & 1)) ^ (lane & 7)) << 4);
        const uint32_t gsign = c ? 0x80008000u : 0u;
        mbar_wait(BAR(B_FS + 2 + wg), 1);
#pragma unroll
        for (int v = 0; v < 28 - XJ; v++) {
            WAIT2(XJ + v); wg_wait<0>(); REL2(XJ + v - 1); TURN(); MMA2(XJ + v, true);
            constexpr int NS = 8 / (28 - XJ);
#pragma unroll
            for (int u = v * NS; u < (v + 1) * NS; u++) {
                uint32_t* o = &gt[4 * u];
                ldmatrix4t(xrow + u * 2048, o[0], o[1], o[2], o[3]);
                const float4 r4 = *reinterpret_cast<const float4*>(smem + OFF_RSTD + (wg * 128 + u * 16 + (lane & 3) * 4) * 4);
                const uint2 m2 = *reinterpret_cast<const uint2*>(smem + OFF_MEAN + (wg * 128 + u * 16 + (lane & 3) * 4) * 2);
                o[0] = gate2(o[0], m2.x, r4.x, r4.y) ^ gsign;
                o[1] = gate2(o[1], m2.x, r4.x, r4.y) ^ gsign;
                o[2] = gate2(o[2], m2.y, r4.z, r4.w) ^ gsign;
                o[3] = gate2(o[3], m2.y, r4.z, r4.w) ^ gsign;
                asm volatile("st.shared.v2.u32 [%0], {%1,%2};" ::"r"(sb + OFF_SEL + 16), "r"(o[0] ^ o[1]), "r"(o[2] ^ o[3]) : "memory");
            }
        }
        if (tid == 0) PROF_T(21);
        WAIT2(28);
        wg_wait<0>(); REL2(27);
        TS(0);
        TURN();
        wg_fence();
        MMA2_H(0, 0, PSLOT(28), false); wg_commit();
        if (wg == 0) { wg_fence(); MMA2_H(64, 0, PSLOT(28), false); wg_commit(); }
        WAIT2(29); wg_fence(); MMA2_H(0, 1, PSLOT(29), false); wg_commit();
        WAIT2(30); wg_fence(); MMA2_H(0, 2, PSLOT(30), false); wg_commit();
        wg_wait<2>();
        if (tid == 0) mbar_arrive_cluster(mapa(BAR(B_RDY), c ^ 1));
        WAIT2(31); wg_fence(); MMA2_H(0, 3, PSLOT(31), false); wg_commit();
        TS(1);
        mbar_wait(BAR(B_RDY + wg), 0);
#define KEEP(i) wgmma128<64, 1>(ac2, dS + PSLOT(29 + ((i) >> 2)) * SL + ((i) & 3) * 128 + 512, dL + (1 + ((i) >> 2)) * SL + ((i) & 3) * 2, 1)
        wg_fence();
#pragma unroll
        for (int i = 0; i < KQ; i++) KEEP(i);
        wg_commit();
        wg_wait<1>();
        fence_regs64<0>(ac2);
        TS(2);
        wg_fence();
        {
            const uint32_t dst = mapa(sb + OFF_L + wg * SLOT + wt * 16, c ^ 1), rb = mapa(BAR(B_RECV + wg), c ^ 1);
#pragma unroll
            for (int v = 0; v < 8; v++) {
                if (KQ + v < 12) KEEP(KQ + v);
                if (KQ + v == 11) { wg_commit(); if (wg == 0) PASS(); }
                st_async4(dst + v * 2048, pack_bf(ac2[8 * v + 0], ac2[8 * v + 1]), pack_bf(ac2[8 * v + 2], ac2[8 * v + 3]),
                          pack_bf(ac2[8 * v + 4], ac2[8 * v + 5]), pack_bf(ac2[8 * v + 6], ac2[8 * v + 7]), rb);
            }
        }
        if (wg == 1) { wg_fence(); MMA2_H(64, 0, PSLOT(28), false); wg_commit(); }
        TS(3);
        uint32_t xr[32];
#pragma unroll
        for (int v = 0; v < 8; v++) ldmatrix4t(xrow + v * 2048, xr[4 * v], xr[4 * v + 1], xr[4 * v + 2], xr[4 * v + 3]);
        if (wg == 0) {
            wg_wait<0>();
            if (wt == 0) mbar_arrive_cluster(mapa(BAR(B_RDY + 1), c ^ 1));
        }
        TS(4);
        mbar_wait(BAR(B_UPD), 0);
        {
            const int sl = *reinterpret_cast<volatile int*>(smem + OFF_SEL + 4);
            if ((sl >> 7) == wg) {
                const uint32_t v0 = *reinterpret_cast<const uint16_t*>(smem + OFF_H + (wq * 16 + (lane >> 2)) * 2) ^ gsign;
                const uint32_t v1 = *reinterpret_cast<const uint16_t*>(smem + OFF_H + (wq * 16 + (lane >> 2)) * 2 + 16) ^ gsign;
                const uint32_t pick = (lane & 3) != ((sl >> 1) & 3) ? 0x3210u : (sl & 1) ? 0x5410u : 0x3254u;
#pragma unroll
                for (int i = 0; i < 16; i++) {
                    const uint32_t sel = ((sl >> 3) & 15) == i ? pick : 0x3210u;
                    gt[2 * i] = __byte_perm(gt[2 * i], v0, sel);
                    gt[2 * i + 1] = __byte_perm(gt[2 * i + 1], v1, sel);
                }
            }
        }
        TS(5);
        mbar_wait_cluster(BAR(B_RECV + wg), 0);
        TS(6);
        uint4 rv[8];
#pragma unroll
        for (int v = 0; v < 8; v++) rv[v] = *reinterpret_cast<const uint4*>(smem + OFF_L + wg * SLOT + v * 2048 + wt * 16);
        wg_wait<0>();
        fence_regs64<64>(ac2);
        TS(7);
#pragma unroll
        for (int v = 0; v < 8; v++) {
            const float* a = &ac2[64 + 8 * v];
            stmatrix4t(xrow + v * 2048,
                       bfma2(bsub2(pack_bf(a[0], a[1]), rv[v].x), gt[4 * v + 0], xr[4 * v + 0]),
                       bfma2(bsub2(pack_bf(a[2], a[3]), rv[v].y), gt[4 * v + 1], xr[4 * v + 1]),
                       bfma2(bsub2(pack_bf(a[4], a[5]), rv[v].z), gt[4 * v + 2], xr[4 * v + 2]),
                       bfma2(bsub2(pack_bf(a[6], a[7]), rv[v].w), gt[4 * v + 3], xr[4 * v + 3]));
            if (v % OP == OP - 1) {
                fence_async_smem();
                WG_BAR();
                if (wt == 0) {
                    tma_2d_store(&tm_out, grp * 64, g * 256 + wg * 128 + (v + 1 - OP) * 16, sb + OFF_S + (2 + wg) * SLOT + (v + 1 - OP) * 2048);
                    bulk_commit();
                }
                if (v == OP - 1) TS(8);
                if (v == 7) TS(9);
            }
        }
        if (wt == 0) {
            bulk_wait_read<0>();
            TS(10);
            if (wg == 0) PROF_T(14); else { PROF_T(25); PROF_G(26); }
        }
    }
}

typedef CUresult (*EncodeFn)(CUtensorMap*, CUtensorMapDataType, cuuint32_t, void*, const cuuint64_t*, const cuuint64_t*,
                             const cuuint32_t*, const cuuint32_t*, CUtensorMapInterleave, CUtensorMapSwizzle,
                             CUtensorMapL2promotion, CUtensorMapFloatOOBfill);

void make_map(EncodeFn fn, CUtensorMap* tm, const void* p, uint64_t rows, uint64_t cols, uint32_t box_rows,
              CUtensorMapL2promotion promo = CU_TENSOR_MAP_L2_PROMOTION_L2_128B) {
    cuuint64_t dims[2] = {cols, rows};
    cuuint64_t strides[1] = {cols * 2};
    cuuint32_t box[2] = {64, box_rows};
    cuuint32_t es[2] = {1, 1};
    fn(tm, CU_TENSOR_MAP_DATA_TYPE_BFLOAT16, 2, const_cast<void*>(p), dims, strides, box, es, CU_TENSOR_MAP_INTERLEAVE_NONE,
       CU_TENSOR_MAP_SWIZZLE_128B, promo, CU_TENSOR_MAP_FLOAT_OOB_FILL_NONE);
}

}

extern "C" void kernel_launch(void* const* d_in, const int* in_sizes, int n_in, void* d_out, int out_size) {
    (void)in_sizes; (void)n_in; (void)out_size;
    static EncodeFn fn = nullptr;
    if (!fn) {
        void* p = nullptr;
        cudaDriverEntryPointQueryResult q;
        cudaGetDriverEntryPoint("cuTensorMapEncodeTiled", &p, cudaEnableDefault, &q);
        fn = (EncodeFn)p;
        cudaFuncSetAttribute(fnet_fused_kernel, cudaFuncAttributeMaxDynamicSharedMemorySize, SMEM_BYTES);
    }
    CUtensorMap tx, tdre, tdim, tcre, tcim, tout;
    make_map(fn, &tx, d_in[0], S_, D_, 128, PRX);
    make_map(fn, &tcre, d_in[1], S_, S_, 128, PRC);
    make_map(fn, &tcim, d_in[2], S_, S_, 128, PRC);
    make_map(fn, &tdre, d_in[3], D_, D_, 128, PRD);
    make_map(fn, &tdim, d_in[4], D_, D_, 128, PRD);
    make_map(fn, &tout, d_out, S_, D_, 16 * OP);
    Params P;
    P.x = (const __nv_bfloat16*)d_in[0];
    P.dre = (const __nv_bfloat16*)d_in[3];
    P.dim = (const __nv_bfloat16*)d_in[4];
    P.wr = (const __nv_bfloat16*)d_in[6];
    P.wg = (const __nv_bfloat16*)d_in[7];
    P.wu = (const __nv_bfloat16*)d_in[8];
    P.wd = (const __nv_bfloat16*)d_in[9];
    P.zero = 0;
    fnet_fused_kernel<<<NCTA, NTHREADS, SMEM_BYTES, cudaStreamPerThread>>>(tx, tdre, tdim, tcre, tcim, tout, P);
}
```

```cpp
#include <cuda_runtime.h>
#include <cuda_bf16.h>
#include <cuda.h>
#include <stdint.h>

#define XLAG 0
#define GSL 200
#define YNS 0u
#define YLD 1
#define PDEL 2500
#define PGAP 600
#define PK 4
#define HELP 1
#define ASYM 1
#define KQ 4
#define OP 4
#define XJ0 20
#define EGAP1 0
#define EGAP2 0
#define ESTAG 120
#define QJ 12
#define GOJ 2
#define TANH 1
#define SYNCS 0x22200020ull
#define K0 0
#define KRD 1500
#define SYNCD 2
#define SYNCCAP 4000u
#define SYNCMIN 24u
#define SYNCLAG 820u
#define QUIET 1
#define PRX CU_TENSOR_MAP_L2_PROMOTION_L2_128B
#define PRD CU_TENSOR_MAP_L2_PROMOTION_L2_128B
#define PRC CU_TENSOR_MAP_L2_PROMOTION_L2_128B
#define SLEEP_NS 200
#define PROD_REGS 32
#define CONS_REGS 184

namespace {

constexpr int S_ = 2048, D_ = 1024, F_ = 3584;
constexpr int NCTA = 128;
constexpr int XJ = XJ0;
constexpr uint32_t SLOT = 16384;
constexpr uint32_t OFF_L = 0;
constexpr uint32_t OFF_S = 8 * SLOT;
constexpr uint32_t OFF_RS = OFF_S + SLOT;
constexpr uint32_t OFF_BAR = 14 * SLOT;
constexpr uint32_t OFF_SEL = OFF_BAR + 360;
constexpr uint32_t OFF_RSTD = OFF_BAR + 384;
constexpr uint32_t OFF_MEAN = OFF_RSTD + 1024;
constexpr uint32_t OFF_XB = OFF_MEAN + 512;
constexpr uint32_t OFF_H = OFF_XB + 1024;
constexpr uint32_t SMEM_BYTES = OFF_H + 128;
constexpr uint32_t OFF_TS = OFF_XB + 512;
constexpr uint32_t SB0 = 1024;
constexpr int NTHREADS = 512;
static_assert(SMEM_BYTES <= 232448, "smem");

enum { B_FS = 0, B_ES = 6, B_FL = 12, B_EL = 20, B_SRD = 28, B_OUT = 30, B_RECV = 32, B_RDY = 34, B_STATS = 36, B_LST = 37  , B_UPD = 38,
       B_QUIET = 39, B_GO = 40, B_PEER = 41, B_SEL = 42, B_H = 43, B_COUNT = 44 };
static_assert(B_COUNT * 8 <= 360, "barriers");

__device__ __align__(1024) uint8_t g_ab[16u * 32u * SLOT];
__device__ __align__(128) uint4 g_part[56 * (D_ / 4)];
__device__ __align__(128) uint4 g_stat[S_];
__device__ __align__(128) uint4 g_rs[D_];
__device__ __align__(128) unsigned long long g_key[NCTA];
__device__ __align__(128) unsigned long long g_flag[16 * 16];
__device__ __align__(128) unsigned long long g_sync[16 * 16];
__device__ __align__(128) unsigned g_epoch[NCTA];
#define PROF_T(i) do {} while (0)
#define TRACE(i) do {} while (0)
#define PROF_G(i) do {} while (0)
#define TS(i) do {} while (0)
#define FINISH(wg) bulk_wait_read<0>()

__device__ __forceinline__ uint32_t smem_u32(const void* p) { return (uint32_t)__cvta_generic_to_shared(p); }
__device__ __forceinline__ void mbar_init(uint32_t bar, uint32_t cnt) {
    asm volatile("mbarrier.init.shared::cta.b64 [%0], %1;" ::"r"(bar), "r"(cnt) : "memory");
}
__device__ __forceinline__ bool mbar_try(uint32_t bar, uint32_t parity) {
    uint32_t ok;
    asm volatile("{\n.reg .pred p;\nmbarrier.try_wait.parity.shared::cta.b64 p, [%1], %2;\nselp.u32 %0, 1, 0, p;\n}"
                 : "=r"(ok) : "r"(bar), "r"(parity) : "memory");
    return ok;
}
__device__ __forceinline__ bool mbar_test(uint32_t bar, uint32_t parity) {
    uint32_t ok;
    asm volatile("{\n.reg .pred p;\nmbarrier.test_wait.parity.shared::cta.b64 p, [%1], %2;\nselp.u32 %0, 1, 0, p;\n}"
                 : "=r"(ok) : "r"(bar), "r"(parity) : "memory");
    return ok;
}
__device__ __forceinline__ bool mbar_try_cluster(uint32_t bar, uint32_t parity) {
    uint32_t ok;
    asm volatile("{\n.reg .pred p;\nmbarrier.try_wait.parity.acquire.cluster.shared::cta.b64 p, [%1], %2;\nselp.u32 %0, 1, 0, p;\n}"
                 : "=r"(ok) : "r"(bar), "r"(parity) : "memory");
    return ok;
}
constexpr int SPIN_LIMIT = 1 << 20;
__device__ __forceinline__ void mbar_wait(uint32_t bar, uint32_t parity) {
    if (mbar_try(bar, parity)) return;
    int n = 0;
    while (!mbar_try(bar, parity) && ++n < SPIN_LIMIT) {}
}
__device__ __forceinline__ void mbar_wait_cluster(uint32_t bar, uint32_t parity) {
    int n = 0;
    while (!mbar_try_cluster(bar, parity) && ++n < SPIN_LIMIT) {}
}
__device__ __forceinline__ void mbar_wait_sleep(uint32_t bar, uint32_t parity) {
    int n = 0;
    while (!mbar_try(bar, parity) && ++n < SPIN_LIMIT) __nanosleep(SLEEP_NS);
}
__device__ __forceinline__ void mbar_arrive(uint32_t bar) {
    asm volatile("mbarrier.arrive.shared::cta.b64 _, [%0];" ::"r"(bar) : "memory");
}
__device__ __forceinline__ void mbar_arrive_cluster(uint32_t cluster_bar) {
    asm volatile("mbarrier.arrive.shared::cluster.b64 _, [%0];" ::"r"(cluster_bar) : "memory");
}
__device__ __forceinline__ void mbar_expect_tx(uint32_t bar, uint32_t bytes) {
    asm volatile("mbarrier.arrive.expect_tx.shared::cta.b64 _, [%0], %1;" ::"r"(bar), "r"(bytes) : "memory");
}
__device__ __forceinline__ bool elect_one() {
    uint32_t p;
    asm volatile("{\n.reg .pred p;\nelect.sync _|p, 0xffffffff;\nselp.u32 %0, 1, 0, p;\n}" : "=r"(p));
    return p;
}
__device__ __forceinline__ uint32_t mapa(uint32_t addr, uint32_t rank) {
    uint32_t r;
    asm("mapa.shared::cluster.u32 %0, %1, %2;" : "=r"(r) : "r"(addr), "r"(rank));
    return r;
}
__device__ __forceinline__ uint32_t clock32() { uint32_t t; asm volatile("mov.u32 %0, %%clock;" : "=r"(t)); return t; }
__device__ __forceinline__ void sleep_until(uint32_t t) {
    int n = 0;
    while ((int)(clock32() - t) < 0 && ++n < SPIN_LIMIT) __nanosleep(20);
}
__device__ __forceinline__ void yield(float last, uint32_t zero) {
    if (YLD) asm volatile("nanosleep.u32 %0;" ::"r"((__float_as_uint(last) & zero) | YNS));
}
template <typename T> __device__ __forceinline__ T* at(T* p, uint32_t bytes) {
    asm("" : "+r"(bytes));
    return reinterpret_cast<T*>(reinterpret_cast<uintptr_t>(p) + bytes);
}
__device__ __forceinline__ void tma_2d(uint32_t dst, const CUtensorMap* tm, int c0, int c1, uint32_t bar) {
    asm volatile("cp.async.bulk.tensor.2d.shared::cluster.global.mbarrier::complete_tx::bytes [%0], [%1, {%3, %4}], [%2];"
                 ::"r"(dst), "l"(tm), "r"(bar), "r"(c0), "r"(c1) : "memory");
}
__device__ __forceinline__ void tma_2d_store(const CUtensorMap* tm, int c0, int c1, uint32_t src) {
    asm volatile("cp.async.bulk.tensor.2d.global.shared::cta.bulk_group [%0, {%2, %3}], [%1];"
                 ::"l"(tm), "r"(src), "r"(c0), "r"(c1) : "memory");
}
__device__ __forceinline__ void bulk_g2s(uint32_t dst, const void* src, uint32_t bytes, uint32_t bar) {
    asm volatile("cp.async.bulk.shared::cluster.global.mbarrier::complete_tx::bytes [%0], [%1], %2, [%3];"
                 ::"r"(dst), "l"(src), "r"(bytes), "r"(bar) : "memory");
}
__device__ __forceinline__ void bulk_s2g(void* dst, uint32_t src, uint32_t bytes) {
    asm volatile("cp.async.bulk.global.shared::cta.bulk_group [%0], [%1], %2;" ::"l"(dst), "r"(src), "r"(bytes) : "memory");
}
__device__ __forceinline__ void st_async4(uint32_t dst, uint32_t a, uint32_t b, uint32_t c, uint32_t d, uint32_t bar) {
    asm volatile("st.async.weak.shared::cluster.mbarrier::complete_tx::bytes.v4.b32 [%0], {%1,%2,%3,%4}, [%5];"
                 ::"r"(dst), "r"(a), "r"(b), "r"(c), "r"(d), "r"(bar) : "memory");
}
__device__ __forceinline__ void bulk_commit() { asm volatile("cp.async.bulk.commit_group;" ::: "memory"); }
template <int N> __device__ __forceinline__ void bulk_wait_read() { asm volatile("cp.async.bulk.wait_group.read %0;" ::"n"(N) : "memory"); }
template <int N> __device__ __forceinline__ void bulk_wait() { asm volatile("cp.async.bulk.wait_group %0;" ::"n"(N) : "memory"); }
__device__ __forceinline__ void fence_async_smem() { asm volatile("fence.proxy.async.shared::cta;" ::: "memory"); }
__device__ __forceinline__ void fence_async_global() { asm volatile("fence.proxy.async.global;" ::: "memory"); }
__device__ __forceinline__ void prefetch_tmap(const CUtensorMap* tm) {
    asm volatile("prefetch.tensormap [%0];" ::"l"(tm) : "memory");
}
__device__ __forceinline__ unsigned long long ld_acquire64(const unsigned long long* p) {
    unsigned long long v; asm volatile("ld.acquire.gpu.global.u64 %0, [%1];" : "=l"(v) : "l"(p) : "memory"); return v;
}
__device__ __forceinline__ unsigned load_epoch(int b) {
    unsigned v; asm volatile("ld.global.u32 %0, [%1];" : "=r"(v) : "l"(at(g_epoch, b * 4)) : "memory"); return v + 1;
}
__device__ __forceinline__ unsigned ld_relaxed(const void* p) {
    unsigned v; asm volatile("ld.relaxed.gpu.global.u32 %0, [%1];" : "=r"(v) : "l"(p) : "memory"); return v;
}
__device__ __forceinline__ unsigned long long ld_relaxed64(const unsigned long long* p) {
    unsigned long long v; asm volatile("ld.relaxed.gpu.global.u64 %0, [%1];" : "=l"(v) : "l"(p) : "memory"); return v;
}
__device__ __forceinline__ void red_max64(unsigned long long* p, unsigned long long v) {
    asm volatile("red.relaxed.gpu.global.max.u64 [%0], %1;" ::"l"(p), "l"(v) : "memory");
}
__device__ __forceinline__ uint4 ld_relaxed128(const uint4* p) {
    uint4 v;
    asm volatile("{\n.reg .b128 t;\n.reg .b64 lo, hi;\nld.relaxed.gpu.global.b128 t, [%4];\nmov.b128 {lo, hi}, t;\n"
                 "mov.b64 {%0, %1}, lo;\nmov.b64 {%2, %3}, hi;\n}"
                 : "=r"(v.x), "=r"(v.y), "=r"(v.z), "=r"(v.w) : "l"(p) : "memory");
    return v;
}
__device__ __forceinline__ void st_relaxed128(uint4* p, const uint4& v) {
    asm volatile("{\n.reg .b128 t;\n.reg .b64 lo, hi;\nmov.b64 lo, {%1, %2};\nmov.b64 hi, {%3, %4};\nmov.b128 t, {lo, hi};\n"
                 "st.relaxed.gpu.global.b128 [%0], t;\n}"
                 ::"l"(p), "r"(v.x), "r"(v.y), "r"(v.z), "r"(v.w) : "memory");
}
__device__ __forceinline__ void st_relaxed64(unsigned long long* p, unsigned long long v) {
    asm volatile("st.relaxed.gpu.global.u64 [%0], %1;" ::"l"(p), "l"(v) : "memory");
}
__device__ __forceinline__ void st_release8(void* p, unsigned v) {
    asm volatile("st.release.gpu.global.u8 [%0], %1;" ::"l"(p), "r"(v) : "memory");
}
__device__ __forceinline__ uint64_t policy_evict_first() {
    uint64_t pol;
    asm("createpolicy.fractional.L2::evict_first.b64 %0, 1.0;" : "=l"(pol));
    return pol;
}
__device__ __forceinline__ uint4 ldg_stream(const void* p, uint64_t pol) {
    uint4 v;
    asm volatile("ld.global.nc.L1::no_allocate.L2::cache_hint.v4.u32 {%0,%1,%2,%3}, [%4], %5;"
                 : "=r"(v.x), "=r"(v.y), "=r"(v.z), "=r"(v.w) : "l"(p), "l"(pol));
    return v;
}
template <int ID, int N> __device__ __forceinline__ void named_arrive() { asm volatile("bar.arrive %0, %1;" ::"n"(ID), "n"(N) : "memory"); }
template <int ID, int N> __device__ __forceinline__ void named_bar() { asm volatile("bar.sync %0, %1;" ::"n"(ID), "n"(N) : "memory"); }

__device__ __forceinline__ float bf_lo(uint32_t u) { return __uint_as_float(u << 16); }
__device__ __forceinline__ float bf_hi(uint32_t u) { return __uint_as_float(u & 0xffff0000u); }
__device__ __forceinline__ uint32_t pack_bf(float lo, float hi) {
    uint32_t r; asm("cvt.rn.bf16x2.f32 %0, %1, %2;" : "=r"(r) : "f"(hi), "f"(lo)); return r;
}
__device__ __forceinline__ float rbf(float v) { return __bfloat162float(__float2bfloat16_rn(v)); }
__device__ __forceinline__ float sqrt_f(float v) { float r; asm("sqrt.approx.f32 %0, %1;" : "=f"(r) : "f"(v)); return r; }
__device__ __forceinline__ float rcp_f(float v) { float r; asm("rcp.approx.f32 %0, %1;" : "=f"(r) : "f"(v)); return r; }
__device__ __forceinline__ float silu_f(float z) { return __fdividef(z, 1.0f + __expf(-z)); }
__device__ __forceinline__ uint32_t bsub2(uint32_t a, uint32_t b) {
    uint32_t r; asm("sub.rn.bf16x2 %0, %1, %2;" : "=r"(r) : "r"(a), "r"(b)); return r;
}
__device__ __forceinline__ uint32_t bfma2(uint32_t a, uint32_t b, uint32_t c) {
    uint32_t r; asm("fma.rn.bf16x2 %0, %1, %2, %3;" : "=r"(r) : "r"(a), "r"(b), "r"(c)); return r;
}
__device__ __forceinline__ uint32_t norm2(uint32_t xv, float m, float rinv) {
    uint32_t t = pack_bf(bf_lo(xv) - m, bf_hi(xv) - m);
    return pack_bf(bf_lo(t) * rinv, bf_hi(t) * rinv);
}
__device__ __forceinline__ float gate1(float z) {
    if (TANH) {
        float t;
        const float h = 0.5f * z;
        asm("tanh.approx.f32 %0, %1;" : "=f"(t) : "f"(h));
        return fmaf(h, t, h);
    }
    float e, r;
    asm("ex2.approx.ftz.f32 %0, %1;" : "=f"(e) : "f"(z * -1.4426950408889634f));
    asm("rcp.approx.ftz.f32 %0, %1;" : "=f"(r) : "f"(1.0f + e));
    return z * r;
}
__device__ __forceinline__ uint32_t gate2(uint32_t xv, uint32_t mean2, float r0, float r1) {
    const uint32_t t = bsub2(xv, mean2);
    return pack_bf(gate1(bf_lo(t) * r0), gate1(bf_hi(t) * r1));
}
__device__ __forceinline__ uint32_t silu2(uint32_t z) { return pack_bf(silu_f(bf_lo(z)), silu_f(bf_hi(z))); }

__device__ __forceinline__ void stmatrix4(uint32_t addr, uint32_t r0, uint32_t r1, uint32_t r2, uint32_t r3) {
    asm volatile("stmatrix.sync.aligned.m8n8.x4.shared.b16 [%0], {%1,%2,%3,%4};"
                 ::"r"(addr), "r"(r0), "r"(r1), "r"(r2), "r"(r3));
}
__device__ __forceinline__ void stmatrix4t(uint32_t addr, uint32_t r0, uint32_t r1, uint32_t r2, uint32_t r3) {
    asm volatile("stmatrix.sync.aligned.m8n8.x4.trans.shared.b16 [%0], {%1,%2,%3,%4};"
                 ::"r"(addr), "r"(r0), "r"(r1), "r"(r2), "r"(r3));
}
__device__ __forceinline__ void ldmatrix4t(uint32_t addr, uint32_t& r0, uint32_t& r1, uint32_t& r2, uint32_t& r3) {
    asm volatile("ldmatrix.sync.aligned.m8n8.x4.trans.shared.b16 {%0,%1,%2,%3}, [%4];"
                 : "=r"(r0), "=r"(r1), "=r"(r2), "=r"(r3) : "r"(addr));
}

__device__ __forceinline__ void wg_fence() { asm volatile("wgmma.fence.sync.aligned;" ::: "memory"); }
__device__ __forceinline__ void wg_commit() { asm volatile("wgmma.commit_group.sync.aligned;" ::: "memory"); }
template <int N> __device__ __forceinline__ void wg_wait() { asm volatile("wgmma.wait_group.sync.aligned %0;" ::"n"(N) : "memory"); }

__host__ __device__ constexpr uint32_t desc_lo(uint32_t addr, uint32_t lbo) { return ((addr & 0x3FFFF) >> 4) | ((lbo >> 4) << 16); }
#define DESC_HI "0x40000040"

#define R8(a, o) "+f"(a[(o) + 0]), "+f"(a[(o) + 1]), "+f"(a[(o) + 2]), "+f"(a[(o) + 3]), \
                 "+f"(a[(o) + 4]), "+f"(a[(o) + 5]), "+f"(a[(o) + 6]), "+f"(a[(o) + 7])
#define R64(a, o) R8(a, (o) + 0), R8(a, (o) + 8), R8(a, (o) + 16), R8(a, (o) + 24), \
                  R8(a, (o) + 32), R8(a, (o) + 40), R8(a, (o) + 48), R8(a, (o) + 56)

template <int O, int TA>
__device__ __forceinline__ void wgmma128(float (&a)[128], uint32_t da, uint32_t db, int scale_d) {
    asm volatile(
        "{\n.reg .pred p;\n.reg .b64 da, db;\nsetp.ne.b32 p, %66, 0;\n"
        "mov.b64 da, {%64, " DESC_HI "};\nmov.b64 db, {%65, " DESC_HI "};\n"
        "wgmma.mma_async.sync.aligned.m64n128k16.f32.bf16.bf16 "
        "{%0,%1,%2,%3,%4,%5,%6,%7,%8,%9,%10,%11,%12,%13,%14,%15,"
        "%16,%17,%18,%19,%20,%21,%22,%23,%24,%25,%26,%27,%28,%29,%30,%31,"
        "%32,%33,%34,%35,%36,%37,%38,%39,%40,%41,%42,%43,%44,%45,%46,%47,"
        "%48,%49,%50,%51,%52,%53,%54,%55,%56,%57,%58,%59,%60,%61,%62,%63},"
        "da, db, p, 1, 1, %67, 0;\n}"
        : R64(a, O)
        : "r"(da), "r"(db), "r"(scale_d), "n"(TA));
}
template <int O>
__device__ __forceinline__ void wgmma128_rs(float (&a)[128], const uint32_t* f, uint32_t db) {
    asm volatile(
        "{\n.reg .b64 db;\nmov.b64 db, {%68, 8};\n"
        "wgmma.mma_async.sync.aligned.m64n128k16.f32.bf16.bf16 "
        "{%0,%1,%2,%3,%4,%5,%6,%7,%8,%9,%10,%11,%12,%13,%14,%15,"
        "%16,%17,%18,%19,%20,%21,%22,%23,%24,%25,%26,%27,%28,%29,%30,%31,"
        "%32,%33,%34,%35,%36,%37,%38,%39,%40,%41,%42,%43,%44,%45,%46,%47,"
        "%48,%49,%50,%51,%52,%53,%54,%55,%56,%57,%58,%59,%60,%61,%62,%63},"
        "{%64, %65, %66, %67}, db, 1, 1, 1, 0;\n}"
        : R64(a, O)
        : "r"(f[0]), "r"(f[1]), "r"(f[2]), "r"(f[3]), "r"(db));
}
template <int O>
__device__ __forceinline__ void fence_regs64(float (&a)[128]) {
    asm volatile("" : R64(a, O)::"memory");
}

struct Params {
    const __nv_bfloat16* x;
    const __nv_bfloat16* dre;
    const __nv_bfloat16* dim;
    const __nv_bfloat16* wr;
    const __nv_bfloat16* wg;
    const __nv_bfloat16* wu;
    const __nv_bfloat16* wd;
    uint32_t zero;
#define AB g_ab
};

__device__ __forceinline__ float warp_sum(float v) {
#pragma unroll
    for (int o = 16; o; o >>= 1) v += __shfl_xor_sync(0xffffffffu, v, o);
    return v;
}
__device__ __forceinline__ void fma8(float* acc, const uint4& w, float s) {
    acc[0] += s * bf_lo(w.x); acc[1] += s * bf_hi(w.x); acc[2] += s * bf_lo(w.y); acc[3] += s * bf_hi(w.y);
    acc[4] += s * bf_lo(w.z); acc[5] += s * bf_hi(w.z); acc[6] += s * bf_lo(w.w); acc[7] += s * bf_hi(w.w);
}
__device__ __forceinline__ int POS(int t) { return (t & ~15) | ((t & 6) << 1) | ((t & 8) >> 2) | (t & 1); }
__host__ __device__ constexpr int PSLOT(int j) { return j < 4 ? j : (j & 1) + ((j & 2) ? 0 : 4); }
__host__ __device__ constexpr int PPAR(int j) { return j < 4 ? 0 : ((j >> 2) ^ (j >> 1) ^ 1) & 1; }
__host__ __device__ constexpr int DSLOT(int it) { return (it & 3) + 2; }
__device__ __forceinline__ int SREC(int t) { return (t & ~15) | ((t & 3) << 2) | ((t >> 2) & 3); }
__device__ __forceinline__ int KO(int cl) { return ((cl & 1) << 1) | (cl >> 1); }

__device__ __forceinline__ unsigned long long* sync_words() {
    uint32_t t;
    asm volatile("mov.u32 %0, %%smid;" : "=r"(t));
    t >>= 1;
    const uint32_t u = t - 32;
    return at(g_sync, (t < 32 ? t & 7 : t < 60 ? 8 + u - 7 * ((u * 37) >> 8) : 15) * 128);
}

__global__ void __cluster_dims__(2, 1, 1) __launch_bounds__(NTHREADS, 1)
fnet_fused_kernel(const __grid_constant__ CUtensorMap tm_x, const __grid_constant__ CUtensorMap tm_dre,
                  const __grid_constant__ CUtensorMap tm_dim, const __grid_constant__ CUtensorMap tm_cre,
                  const __grid_constant__ CUtensorMap tm_cim, const __grid_constant__ CUtensorMap tm_out,
                  const Params P) {
    extern __shared__ __align__(1024) uint8_t smem[];
    const unsigned long long tstart = clock64();
    const uint32_t sb = smem_u32(smem);
    const int tid = threadIdx.x, lane = tid & 31;
    const int warp = __shfl_sync(0xffffffffu, tid >> 5, 0);
    const int pr = blockIdx.x >> 1, p7 = ((pr - 36) * 37) >> 8;
    const int c = blockIdx.x & 1;
    const int g = pr < 4 ? 0 : pr < 36 ? (pr - 4) & 7 : pr - 35 - 7 * p7;
    const int r = pr < 4 ? 4 + pr : pr < 36 ? (pr - 4) >> 3 : 4 + p7;
    const int grp = 2 * r + c;
    const int b = g * 16 + grp;
    const uint32_t bar0 = sb + OFF_BAR;
    const uint32_t zero = P.zero;
#define BAR(i) (bar0 + 8u * (i))
#define XBAR(i) (sb + OFF_XB + 64 + 8u * (i))
#define CLUSTER_ARRIVE() asm volatile("barrier.cluster.arrive.relaxed.aligned;" ::: "memory")
#define CLUSTER_WAIT() asm volatile("barrier.cluster.wait.aligned;" ::: "memory")
    if ((sb & 0xffffffu) != SB0) return;

    if (warp == 12) {
        const CUtensorMap* tmD = c ? &tm_dim : &tm_dre;
#define LOAD0(it) do { \
            mbar_expect_tx(BAR(B_FS + DSLOT(it)), SLOT); tma_2d(sb + OFF_S + DSLOT(it) * SLOT, tmD, (it) * 64, r * 128, BAR(B_FS + DSLOT(it))); \
            mbar_expect_tx(BAR(B_FL + (it)), SLOT); tma_2d(sb + OFF_L + (it) * SLOT, &tm_x, (it) * 64, g * 256, BAR(B_FL + (it))); \
            mbar_expect_tx(BAR(B_FL + 4 + (it)), SLOT); tma_2d(sb + OFF_L + (4 + (it)) * SLOT, &tm_x, (it) * 64, g * 256 + 128, BAR(B_FL + 4 + (it))); \
        } while (0)
        if (elect_one()) {
            prefetch_tmap(tmD); prefetch_tmap(&tm_x);
            mbar_init(BAR(B_FS + 2), 1); mbar_init(BAR(B_FL), 1); mbar_init(BAR(B_FL + 4), 1);
            fence_async_smem();
            LOAD0(0);
#pragma unroll
            for (int i = 0; i < B_COUNT; i++)
                if (i != B_FS + 2 && i != B_FL && i != B_FL + 4)
                    mbar_init(BAR(i), (i >= B_ES && i < B_FL) || i == B_GO ? 2 : i == B_STATS || i == B_LST || (i & ~1) == B_OUT ? 4 : 1);
#pragma unroll
            for (int i = 0; i < 8; i++) mbar_init(XBAR(i), 1);
            mbar_expect_tx(BAR(B_RECV), SLOT); mbar_expect_tx(BAR(B_RECV + 1), SLOT);
            mbar_expect_tx(BAR(B_PEER), 1024); mbar_expect_tx(BAR(B_H), 128);
            *reinterpret_cast<volatile uint32_t*>(smem + OFF_SEL + 8) = 0;
            asm volatile("fence.mbarrier_init.release.cluster;" ::: "memory");
            fence_async_smem();
        }
        __syncwarp();
        CLUSTER_ARRIVE();
        if (elect_one()) {
#define XROWS(k) do { mbar_expect_tx(XBAR(k), 8192); bulk_g2s(sb + OFF_S + (k) * 8192, at(P.x, (b * 16 + (k) * 4) * D_ * 2), 8192, XBAR(k)); } while (0)
#pragma unroll 1
            for (int it = 1; it < 5 + XLAG; it++) {
                if (it > XLAG) XROWS(it - 1 - XLAG);
                if (it < 4) LOAD0(it);
            }
        }
        __syncwarp();
    } else {
        CLUSTER_ARRIVE();
        if (K0 && tid == 13 * 32) red_max64(sync_words(), tstart);
    }

    if (warp >= 12) {
        asm volatile("setmaxnreg.dec.sync.aligned.u32 %0;" ::"n"(PROD_REGS));
        CLUSTER_WAIT();
        if (warp == 12) {
            if (elect_one()) {
                const CUtensorMap* tmD = c ? &tm_dim : &tm_dre;
#pragma unroll 1
                for (int it = 4; it < 16; it++) {
                    const int s = DSLOT(it);
                    mbar_wait(BAR(B_ES + s), ((it >> 2) & 1) ^ 1);
                    TRACE(it);
                    mbar_expect_tx(BAR(B_FS + s), SLOT);
                    tma_2d(sb + OFF_S + s * SLOT, tmD, it * 64, r * 128, BAR(B_FS + s));
                }
                const unsigned ep = load_epoch(b), e8 = ep & 0xffu;
                const uint8_t* abg = at(AB, grp * 32 * SLOT);
                const unsigned long long* fl = at(g_flag, grp * 128);
                unsigned long long rdy = ld_acquire64(fl);
                mbar_wait(BAR(B_SRD), 0);
                st_release8(at(g_flag, grp * 128 + g), e8);
                PROF_T(7);
                int j = 4;
#pragma unroll 1
                for (int cl = 0; cl < 4; cl++) {
                    if (cl) rdy = ld_acquire64(fl + cl);
                    fence_async_global();
#pragma unroll 1
                    for (int n = 1; n < 8; n++, j++) {
                        const int q = (g + n) & 7, s = (j & 1) + ((j & 2) ? 0 : 4);
                        mbar_wait(BAR(B_ES + s), ((j >> 2) ^ (j >> 1)) & 1);
                        if (j == 7) mbar_wait(BAR(B_SRD + 1), 0);
                        if (((unsigned)(rdy >> (8 * q)) & 0xffu) != e8) {
                            int m = 0;
                            do { rdy = ld_acquire64(fl + cl); } while (((unsigned)(rdy >> (8 * q)) & 0xffu) != e8 && ++m < SPIN_LIMIT);
                            fence_async_global();
                        }
                        TRACE(16 + j);
                        mbar_expect_tx(BAR(B_FS + s), SLOT);
                        bulk_g2s(sb + OFF_S + s * SLOT, at(abg, (4 * q + KO(cl)) * SLOT), SLOT, BAR(B_FS + s));
                    }
                }
                *at(g_epoch, b * 4) = ep;
            }
        } else if (warp < 15) {
            if (elect_one()) {
                const int w = warp - 13, row0 = g * 256 + w * 128;
                const CUtensorMap* tmC = c ? &tm_cim : &tm_cre;
                const uint32_t fb = BAR(B_FL + 4 * w), eb = BAR(B_EL + 4 * w), dst = sb + OFF_L + w * 4 * SLOT;
                prefetch_tmap(w ? &tm_out : tmC);
                unsigned long long* sy = sync_words();
#define ADOPT(ph, lag) do { const unsigned long long v = ld_relaxed64(sy++); \
                    if (v - (ph) - SYNCMIN < SYNCCAP) *reinterpret_cast<volatile uint32_t*>(smem + OFF_SEL + 8) = (uint32_t)v - (lag); } while (0)
                if (w == 0 && K0) { sleep_until((uint32_t)tstart + KRD); ADOPT(tstart, 0u - K0); }
                int n = 0, cl = 0;
#pragma unroll 1
                for (int it = 4; it < 48; it++) {
                    const int s = it & 3;
                    mbar_wait(eb + 8 * s, ((it >> 2) & 1) ^ 1);
                    const unsigned long long ph = clock64() - 1024u * (it - 4);
                    TRACE(64 + w * 64 + it - 4);
                    mbar_expect_tx(fb + 8 * s, SLOT);
                    tma_2d(dst + s * SLOT, it < 16 ? &tm_x : tmC, (it < 16 ? it : 4 * ((g + n) & 7) + KO(cl)) * 64, row0, fb + 8 * s);
                    if (it >= 16) {
                        if (it == 19) { n = 1; cl = 0; } else if (it < 19) cl++; else if (++n == 8) { n = 1; cl++; }
                    }
                    if (w == 0) {
                        if (((SYNCS << 4) >> it) & 1) red_max64(sy, ph);
                        if (((SYNCS << (4 + SYNCD)) >> it) & 1) ADOPT(ph, SYNCLAG);
                    }
                }
                if (HELP) {
#pragma unroll 1
                    for (int h = 0; h < 8 / OP; h++) {
                        mbar_wait(BAR((h ? B_STATS : B_OUT) + w), h);
                        fence_async_smem();
                        tma_2d_store(&tm_out, grp * 64, row0 + h * OP * 16, sb + OFF_S + (2 + w) * SLOT + h * OP * 2048);
                        bulk_commit();
                    }
                    FINISH(w);
                }
            }
        } else {
            const unsigned ep = load_epoch(b);
            uint4 f[4];
#define GATHER(ptr, cnt, valid) do { int n = 0; bool ok; do { ok = true; \
                _Pragma("unroll") for (int i = 0; i < (cnt); i++) { f[i] = ld_relaxed128((ptr) + i * 32); ok = ok && (valid); } \
                if (__all_sync(0xffffffffu, ok)) break; \
                __nanosleep(GSL); \
            } while (++n < SPIN_LIMIT); } while (0)
            {
                sleep_until((uint32_t)tstart + 6000);
                const uint4* keys = at(reinterpret_cast<const uint4*>(g_key), lane * 16);
                bool mine = false;
                int n = 0;
                do {
                    f[0] = ld_relaxed128(keys); f[1] = ld_relaxed128(keys + 32);
                    if (__all_sync(0xffffffffu, f[0].y == ep && f[0].w == ep && f[1].y == ep && f[1].w == ep)) break;
                    if (!mine) {
                        mbar_wait(BAR(B_LST), 0);
                        const uint4 k = *reinterpret_cast<const uint4*>(smem + OFF_XB);
                        if (lane == 0) st_relaxed64(at(g_key, b * 8), ((unsigned long long)ep << 32) | max(max(k.x, k.y), max(k.z, k.w)));
                        mine = true;
                    }
                    __nanosleep(GSL);
                } while (++n < SPIN_LIMIT);
                const unsigned key = __reduce_max_sync(0xffffffffu, max(max(f[0].x, f[0].z), max(f[1].x, f[1].z)));
                if (lane == 0) { *reinterpret_cast<unsigned*>(smem + OFF_SEL) = key; mbar_arrive(BAR(B_SEL)); PROF_T(8); }
            }
            if (elect_one()) {
#pragma unroll 1
                for (int cl = 0; cl < 4; cl++) {
                    uint8_t* dst = at(AB, (grp * 32 + 4 * g + KO(cl)) * SLOT);
                    const uint32_t src = sb + OFF_S + cl * SLOT, chunk = cl ? 4096 : SLOT;
                    mbar_wait(BAR(B_FS + cl), 0);
                    if (cl == 0) PROF_T(3);
                    uint32_t t0 = clock32() + (cl == 1 ? PDEL : 0);
#pragma unroll 1
                    for (uint32_t o = 0; o < SLOT; o += chunk) {
                        sleep_until(t0);
                        bulk_s2g(dst + o, src + o, chunk);
                        bulk_commit();
                        t0 += PGAP;
                    }
                    bulk_wait<0>();
                    TRACE(252 + cl);
                    if (cl < 2) mbar_arrive(BAR(B_SRD + cl));
                    else {
                        mbar_wait(BAR(B_ES + cl), 0);
                        mbar_expect_tx(BAR(B_FS + cl), SLOT);
                        tma_2d(src, &tm_x, grp * 64, g * 256 + (cl - 2) * 128, BAR(B_FS + cl));
                    }
                    if (cl) st_release8(at(g_flag, grp * 128 + cl * 8 + g), ep & 0xffu);
                    if (cl == 1) PROF_T(5);
                    if (cl == 3) PROF_T(4);
                }
            }
        }
    } else if (warp >= 8) {
        asm volatile("setmaxnreg.dec.sync.aligned.u32 %0;" ::"n"(512 - PROD_REGS - 2 * CONS_REGS));
        const int aw = warp - 8, mt = tid - 256;
        unsigned ep;
        {
            const uint8_t* rp = smem + OFF_S + aw * 2048 + lane * 16;
            const __nv_bfloat16* dp = at(c ? P.dim : P.dre, (r * 128 + g * 16 + aw * 4) * D_ * 2);
            float wf[32], sw = 0.f;
#pragma unroll
            for (int i = 0; i < 4; i++) {
                const uint4 w = __ldg(reinterpret_cast<const uint4*>(at(P.wr, lane * 16) + i * 256));
                const uint32_t wv[4] = {w.x, w.y, w.z, w.w};
#pragma unroll
                for (int e = 0; e < 4; e++) { wf[8 * i + 2 * e] = bf_lo(wv[e]); wf[8 * i + 2 * e + 1] = bf_hi(wv[e]); sw = (sw + bf_lo(wv[e])) + bf_hi(wv[e]); }
            }
            ep = load_epoch(b);
            CLUSTER_WAIT();
            float x0[4] = {}, s1[4] = {}, s2[4] = {}, sx[4] = {}, sd[4] = {};
#define PUSH(a, v) do { a[0] = a[1]; a[1] = a[2]; a[2] = a[3]; a[3] = v; } while (0)
#pragma unroll 1
            for (int k = 0; k < 4; k++) {
                mbar_wait(XBAR(k), 0);
                uint4 v[4];
#pragma unroll
                for (int i = 0; i < 4; i++) v[i] = *reinterpret_cast<const uint4*>(rp + k * 8192 + i * 512);
                float sh = bf_lo(v[0].x), a1s = 0.f, a2s = 0.f, axs = 0.f;
#pragma unroll
                for (int i = 0; i < 4; i++) {
                    sh = __shfl_sync(0xffffffffu, sh, 0);
                    const uint32_t xv[4] = {v[i].x, v[i].y, v[i].z, v[i].w};
#pragma unroll
                    for (int e = 0; e < 4; e++) {
                        const float a0 = bf_lo(xv[e]) - sh, a1 = bf_hi(xv[e]) - sh;
                        a1s += a0 + a1;
                        a2s = fmaf(a0, a0, fmaf(a1, a1, a2s));
                        axs = fmaf(a0, wf[8 * i + 2 * e], fmaf(a1, wf[8 * i + 2 * e + 1], axs));
                    }
                    if (i < 3) yield(axs, zero);
                }
                PUSH(x0, sh); PUSH(s1, a1s); PUSH(s2, a2s); PUSH(sx, axs);
                fence_async_smem();
                __syncwarp();
                if (elect_one()) {
                    if (k == 0) mbar_expect_tx(XBAR(4 + aw), 8192);
                    bulk_g2s(sb + OFF_S + k * 8192 + aw * 2048, dp + k * D_, 2048, XBAR(4 + aw));
                }
            }
#define FOLD4(a) do { const bool u16 = lane & 16, u8 = lane & 8; \
                float p0 = (u16 ? a[2] : a[0]) + __shfl_xor_sync(0xffffffffu, u16 ? a[0] : a[2], 16); \
                float p1 = (u16 ? a[3] : a[1]) + __shfl_xor_sync(0xffffffffu, u16 ? a[1] : a[3], 16); \
                a[0] = (u8 ? p1 : p0) + __shfl_xor_sync(0xffffffffu, u8 ? p0 : p1, 8); \
                _Pragma("unroll") for (int o = 4; o; o >>= 1) a[0] += __shfl_xor_sync(0xffffffffu, a[0], o); } while (0)
            FOLD4(s1); FOLD4(s2); FOLD4(sx);
            sw = warp_sum(sw);
            const int rr = lane >> 3;
            const float c0 = rr == 0 ? x0[0] : rr == 1 ? x0[1] : rr == 2 ? x0[2] : x0[3];
            const float dm = s1[0] * (1.0f / D_);
            const float mb = rbf(c0 + dm);
            const float rinv = rcp_f(rbf(sqrt_f(rbf(rbf(fmaxf(s2[0] * (1.0f / D_) - dm * dm, 0.f)) + 1e-5f))));
            unsigned u = __bfloat16_as_ushort(__float2bfloat16_rn((sx[0] + (c0 - mb) * sw) * rinv));
            u = (u & 0x8000u) ? (~u & 0xffffu) : (u | 0x8000u);
            u = (u << 16) | (0xffffu - (unsigned)(b * 16 + rr * 4 + aw));
            const uint4 rec = make_uint4(__float_as_uint(mb), __float_as_uint(rinv), ep, u);
            if ((lane & 7) == 0) st_relaxed128(at(g_stat, (b * 16 + aw * 4 + rr) * 16), rec);
            u = __reduce_max_sync(0xffffffffu, u);
            if (lane == 0) { *reinterpret_cast<unsigned*>(smem + OFF_XB + aw * 4) = u; mbar_arrive(BAR(B_LST)); }
            if (mt == 0) PROF_T(2);
            mbar_wait(XBAR(4 + aw), 0);
#pragma unroll 1
            for (int k = 0; k < 4; k++) {
                float run = 0.f;
#pragma unroll
                for (int i = 0; i < 4; i++) {
                    const uint4 v = *reinterpret_cast<const uint4*>(rp + k * 8192 + i * 512);
                    const uint32_t dv[4] = {v.x, v.y, v.z, v.w};
#pragma unroll
                    for (int e = 0; e < 4; e++) run = (run + bf_lo(dv[e])) + bf_hi(dv[e]);
                }
                PUSH(sd, run);
            }
            FOLD4(sd);
            const float nb = __shfl_down_sync(0xffffffffu, sd[0], 8);
            if ((lane & 15) == 0)
                st_relaxed128(at(g_rs, (grp * 64 + g * 8 + aw * 2 + (lane >> 4)) * 16), make_uint4(__float_as_uint(sd[0]), ep, __float_as_uint(nb), ep));
            if (mt == 0) PROF_T(6);
            named_bar<4, 128>();
            if (mt < 8) asm volatile("mbarrier.inval.shared::cta.b64 [%0];" ::"r"(XBAR(mt)) : "memory");
            uint4 f[4];
            if (aw < 2) {
                const int t = SREC(aw * 128 + lane);
                GATHER(at(g_stat, (g * 256 + aw * 128 + lane) * 16), 4, f[i].z == ep);
#pragma unroll
                for (int i = 0; i < 4; i++) {
                    *reinterpret_cast<uint32_t*>(smem + OFF_RSTD + (POS(t) + i * 32) * 4) = f[i].y;
                    *reinterpret_cast<uint16_t*>(smem + OFF_MEAN + (POS(t) + i * 32) * 2) = (uint16_t)(f[i].x >> 16);
                }
            } else {
                const int e2 = (aw - 2) * 32 + lane;
                GATHER(at(g_rs, (grp * 64 + e2) * 16), 1, f[i].y == ep && f[i].w == ep);
#pragma unroll
                for (int i = 0; i < 2; i++) {
                    const float v = __uint_as_float(i ? f[0].z : f[0].x);
                    const float hi = rbf(v), mid = rbf(v - hi), lo = v - hi - mid;
                    *reinterpret_cast<uint4*>(smem + OFF_RS + (e2 * 2 + i) * 16) = make_uint4(pack_bf(hi, mid), pack_bf(lo, 0.f), 0, 0);
                }
            }
            fence_async_smem();
            __syncwarp();
            if (lane == 0) mbar_arrive(BAR(B_STATS));
            if (mt == 127) PROF_T(9);
        }
        const int pair = g * 7 + r;
        if (r < 7) {
            const uint64_t pol = policy_evict_first();
            const __nv_bfloat16* wp = at((aw & 1) ? P.wu : P.wg, ((c * 512 + (aw >> 1) * 256 + (lane >> 3) * 8) * F_ + pair * 64 + (lane & 7) * 8) * 2);
            uint4 b0[8], b1[8];
#define FILL(buf, str) do { _Pragma("unroll") for (int q = 0; q < 8; q++) buf[q] = ldg_stream(wp + q * (str), pol); } while (0)
            FILL(b0, F_);
            mbar_wait(BAR(B_SEL), 0);
            uint4 xn;
            {
                const int sel = 0xffff - (int)(*reinterpret_cast<volatile unsigned*>(smem + OFF_SEL) & 0xffffu);
                xn = __ldg(reinterpret_cast<const uint4*>(at(P.x, (sel * D_ + c * 512 + (aw >> 1) * 256 + (lane & 7) * 32 + (lane >> 3) * 8) * 2)));
                uint4 f[1];
                GATHER(at(g_stat, SREC(sel) * 16), 1, f[i].z == ep);
                const float m = __uint_as_float(f[0].x), ri = __uint_as_float(f[0].y);
                xn = make_uint4(norm2(xn.x, m, ri), norm2(xn.y, m, ri), norm2(xn.z, m, ri), norm2(xn.w, m, ri));
            }
            float ag[8];
#pragma unroll
            for (int i = 0; i < 8; i++) ag[i] = 0.f;
            const uint32_t stag = (aw * 4 + (grp & 3)) * ESTAG;
            uint32_t te = clock32() + stag;
            bool paused = !QUIET;
#define ROUND(cur, nxt, rd) do { \
                if (!paused && mbar_test(BAR(B_QUIET), 0)) { mbar_wait_sleep(BAR(B_GO), 0); te = clock32() + stag; paused = true; } \
                sleep_until(te); \
                te = clock32() + (paused ? EGAP2 : EGAP1); \
                if (lane == 0) TRACE(192 + aw * 12 + (rd)); \
                if ((rd) == 7) wp = at(P.wd - 16 * D_, ((pair * 64 + (lane >> 4) * 8) * D_ + c * 512 + aw * 128 + (lane & 15) * 8) * 2); \
                wp = at(wp, ((rd) < 7 ? 64 * F_ : 32 * D_) + (cur[7].x & zero)); \
                if ((rd) < 7) FILL(nxt, F_); else if ((rd) != 8 && (rd) < 11) FILL(nxt, D_); \
                _Pragma("unroll") for (int q = 0; q < 8; q += 2) { \
                    uint32_t xw = __shfl_sync(0xffffffffu, q == 0 ? xn.x : q == 2 ? xn.y : q == 4 ? xn.z : xn.w, (lane & 24) | ((rd) & 7)); \
                    fma8(ag, cur[q], bf_lo(xw)); \
                    if (YLD > 1) { yield(ag[7], zero); xw = __shfl_sync(0xffffffffu, xw, lane); } \
                    fma8(ag, cur[q + 1], bf_hi(xw)); \
                    if (q < 6) yield(ag[7], zero); \
                } } while (0)
#pragma unroll 1
            for (int rd = 0; rd < 12; rd += 2) {
                ROUND(b0, b1, rd);
                ROUND(b1, b0, rd + 1);
                if (rd == 6) { wp += 16 * D_; FILL(b1, D_); wp -= 16 * D_; }
                if (rd == 6 || rd == 10) {
#pragma unroll
                    for (int i = 0; i < 8; i++) ag[i] += __shfl_xor_sync(0xffffffffu, ag[i], 16);
                }
                if (rd == 6) {
#pragma unroll
                    for (int i = 0; i < 8; i++) ag[i] += __shfl_xor_sync(0xffffffffu, ag[i], 8);
                    if (lane < 8) {
                        const uint32_t dst = mapa(sb + OFF_XB + (c * 4 + aw) * 128 + (lane & 3) * 32, lane >> 2), pb = mapa(BAR(B_PEER), lane >> 2);
                        st_async4(dst, __float_as_uint(ag[0]), __float_as_uint(ag[1]), __float_as_uint(ag[2]), __float_as_uint(ag[3]), pb);
                        st_async4(dst + 16, __float_as_uint(ag[4]), __float_as_uint(ag[5]), __float_as_uint(ag[6]), __float_as_uint(ag[7]), pb);
                    }
                    if (aw == 3) {
                        mbar_wait_cluster(BAR(B_PEER), 0);
                        const float* ps = reinterpret_cast<const float*>(smem + OFF_XB) + lane;
                        const float go = (ps[0] + ps[64]) + (ps[128] + ps[192]), uo = (ps[32] + ps[96]) + (ps[160] + ps[224]);
                        const float h = rbf(silu_f(rbf(go))) * rbf(uo), ho = __shfl_xor_sync(0xffffffffu, h, 1);
                        asm volatile("st.async.weak.shared::cluster.mbarrier::complete_tx::bytes.b32 [%0], %1, [%2];"
                                     ::"r"(mapa(sb + OFF_H + c * 64 + (lane >> 1) * 4, lane & 1)), "r"((lane & 1) ? pack_bf(ho, h) : pack_bf(h, ho)),
                                       "r"(mapa(BAR(B_H), lane & 1)) : "memory");
                    }
                    mbar_wait_cluster(BAR(B_H), 0);
                    xn = *reinterpret_cast<const uint4*>(smem + OFF_H + (lane & 3) * 32 + (lane >> 4) * 16);
#pragma unroll
                    for (int i = 0; i < 8; i++) ag[i] = 0.f;
                    if (mt == 0) PROF_T(10);
                }
            }
            const int hi = lane >> 4;
            st_relaxed128(at(g_part, pair * 4096 + (c * 8 + aw * 2 + ((lane >> 3) & 1)) * 256 + hi * 128 + (lane & 7) * 16),
                          make_uint4((__float_as_uint(hi ? ag[4] : ag[0]) & ~15u) | (ep & 15u), __float_as_uint(hi ? ag[5] : ag[1]),
                                     __float_as_uint(hi ? ag[6] : ag[2]), __float_as_uint(hi ? ag[7] : ag[3])));
            if (mt == 0) PROF_T(11);
        } else {
            mbar_wait_sleep(BAR(B_SEL), 0);
        }
        const int sel = 0xffff - (int)(*reinterpret_cast<volatile unsigned*>(smem + OFF_SEL) & 0xffffu);
        if ((sel >> 8) == g) {
            const int col = (lane & 7) * 8 + ((lane >> 3) & 1) * 4;
            const uint2 xv = __ldg(reinterpret_cast<const uint2*>(at(P.x, (sel * D_ + grp * 64 + col) * 2)));
            uint4 f[1];
            GATHER(at(g_stat, SREC(sel) * 16), 1, f[i].z == ep);
            const uint4 rec = f[0];
            const uint4* src = at(g_part, (aw * 14 + (lane >> 4)) * 4096 + grp * 256 + (lane & 15) * 16);
            if (r == 7) {
                int n = 0;
                while (((ld_relaxed(src) ^ ep) & 15u) != 0 && ++n < SPIN_LIMIT) __nanosleep(500);
            }
            uint4 t[7];
            int n = 0;
            bool ok;
            do {
                ok = true;
#pragma unroll
                for (int u = 0; u < 7; u++) { t[u] = ld_relaxed128(src + u * 512); ok = ok && ((t[u].x ^ ep) & 15u) == 0; }
            } while (!__all_sync(0xffffffffu, ok) && ++n < SPIN_LIMIT);
            float4 a = make_float4(0.f, 0.f, 0.f, 0.f);
#pragma unroll
            for (int u = 0; u < 7; u++) {
                a.x += __uint_as_float(t[u].x & ~15u); a.y += __uint_as_float(t[u].y); a.z += __uint_as_float(t[u].z); a.w += __uint_as_float(t[u].w);
            }
            a.x += __shfl_xor_sync(0xffffffffu, a.x, 16); a.y += __shfl_xor_sync(0xffffffffu, a.y, 16);
            a.z += __shfl_xor_sync(0xffffffffu, a.z, 16); a.w += __shfl_xor_sync(0xffffffffu, a.w, 16);
            float4* park = reinterpret_cast<float4*>(smem + OFF_XB) + (lane & 15);
            if (lane < 16) park[aw * 16] = a;
            named_bar<4, 128>();
            if (aw == 0) {
                const float4 p1 = park[16], p2 = park[32], p3 = park[48];
                a.x = (a.x + p1.x) + (p2.x + p3.x); a.y = (a.y + p1.y) + (p2.y + p3.y);
                a.z = (a.z + p1.z) + (p2.z + p3.z); a.w = (a.w + p1.w) + (p2.w + p3.w);
                unsigned u = rec.w >> 16;
                u = (u & 0x8000u) ? (u & 0x7fffu) : (~u & 0xffffu);
                const float sg = rbf(__fdividef(1.0f, 1.0f + __expf(-__uint_as_float(u << 16))));
                const float m = __uint_as_float(rec.x), ri = __uint_as_float(rec.y);
                const uint32_t n0 = norm2(xv.x, m, ri), n1 = norm2(xv.y, m, ri);
                uint2 o;
                o.x = silu2(pack_bf(bf_lo(n0) + rbf(rbf(a.x) * sg), bf_hi(n0) + rbf(rbf(a.y) * sg)));
                o.y = silu2(pack_bf(bf_lo(n1) + rbf(rbf(a.z) * sg), bf_hi(n1) + rbf(rbf(a.w) * sg)));
                if (lane < 16) *reinterpret_cast<uint2*>(smem + OFF_H + col * 2) = o;
                __syncwarp();
                if (lane == 0) { mbar_arrive(BAR(B_UPD)); PROF_T(12); }
            }
        }
    } else {
        asm volatile("setmaxnreg.inc.sync.aligned.u32 %0;" ::"n"(CONS_REGS));
        CLUSTER_WAIT();
        const int wg = warp >> 2, wq = warp & 3;
        const int wt = tid & 127;
        float acc[128];
        const uint32_t fL = BAR(B_FL + 4 * wg), eL = BAR(B_EL + 4 * wg);
        const uint32_t dL = desc_lo(SB0 + OFF_L, 16) + wg * 4096;
        constexpr uint32_t dS = desc_lo(SB0 + OFF_S, 16);
        constexpr uint32_t SL = SLOT >> 4;
#define RELEASE(ls, ss) do { if (wt == 0) { mbar_arrive(eL + 8u * (ls)); mbar_arrive(BAR(B_ES + (ss))); } } while (0)
#define WAIT_FULL(ls, lph, ss, sph) do { mbar_wait(BAR(B_FS + (ss)), sph); mbar_wait(fL + 8u * (ls), lph); } while (0)
#define TURN() do { if (wg) named_bar<6, 256>(); else named_bar<5, 256>(); } while (0)
#define PASS() do { if (wg) named_arrive<5, 256>(); else named_arrive<6, 256>(); } while (0)
#define WG_BAR() do { if (wg) named_bar<2, 128>(); else named_bar<1, 128>(); } while (0)
        uint32_t held = 0, tgt = 0;
#define PEEK() do { if (wg == 0) tgt = *reinterpret_cast<volatile uint32_t*>(smem + OFF_SEL + 8); } while (0)
#define HOLD(step) do { if (tgt != held) { held = tgt; sleep_until(tgt + 1024u * (step) - 100u); \
                int n = 0; while ((int)(clock32() - tgt - 1024u * (step)) < 0 && ++n < SPIN_LIMIT) {} } } while (0)
        if (wg == 1) PASS();

#define MMA1_P(O, s, first, pass) do { _Pragma("unroll") for (int kk = 0; kk < 4; kk++) { if (kk == PK && (pass)) PASS(); \
            wgmma128<O, 0>(acc, dL + (s) * SL + kk * 2 + (O) * 8, dS + DSLOT(s) * SL + kk * 2, !((first) && kk == 0)); } \
            if (PK == 4 && (pass)) PASS(); } while (0)
#define MMA1_H(O, s, first) MMA1_P(O, s, first, false)
#define WAIT1(s, ph) WAIT_FULL(s, ph, DSLOT(s), ph)
#define PROBE(ls, lph, ss, sph) (mbar_test(BAR(B_FS + (ss)), sph) & mbar_test(fL + 8u * (ls), lph))
#define REL1(s) RELEASE(s, DSLOT(s))
#pragma unroll 1
        for (int it = 0; it < 12; it++) {
            const int s = it & 3;
            const bool ok = PROBE(s, (it >> 2) & 1, DSLOT(s), (it >> 2) & 1);
            PEEK();
            if (it) { wg_wait<0>(); REL1((it - 1) & 3); }
            if (!ok) WAIT1(s, (it >> 2) & 1);
            HOLD(it);
            TURN();
            wg_fence(); MMA1_H(0, s, it == 0); MMA1_P(64, s, it == 0, true); wg_commit();
            if (it == QJ && tid == 0) { mbar_arrive(BAR(B_QUIET)); PROF_T(15); }
            if (it == 0 && tid == 0) PROF_T(16);
        }
        TS(12);
        mbar_wait(BAR(B_STATS), 0);
        float rs[4];
        uint32_t nm[8];
        {
            const int p0 = POS(wg * 128 + wq * 16 + (lane >> 2));
            const uint32_t msk = (lane & 3) == 0 ? 0xffffffffu : (lane & 3) == 1 ? 0x0000ffffu : 0u;
#pragma unroll
            for (int i = 0; i < 4; i++) {
                const int p = p0 + (i & 1) * 2 + (i >> 1) * 64;
                rs[i] = *reinterpret_cast<const float*>(smem + OFF_RSTD + p * 4);
                const uint32_t m = *reinterpret_cast<const uint16_t*>(smem + OFF_MEAN + p * 2) ^ 0x8000u;
                nm[i + (i & 2)] = (m | (m << 16)) & msk;
                nm[i + (i & 2) + 2] = 0;
            }
            asm volatile("" : "+r"(nm[0]), "+r"(nm[1]), "+r"(nm[2]), "+r"(nm[3]), "+r"(nm[4]), "+r"(nm[5]), "+r"(nm[6]), "+r"(nm[7])::"memory");
        }
        WAIT1(0, 1);
        TS(13);
        wg_wait<0>(); REL1(3);
        TS(14);
        TURN();
        wg_fence();
        wgmma128_rs<0>(acc, nm, (SB0 + OFF_RS) >> 4);
        wgmma128_rs<64>(acc, nm + 4, (SB0 + OFF_RS) >> 4);
        MMA1_H(0, 0, false);
        if (QJ == 12 && tid == 0) { mbar_arrive(BAR(B_QUIET)); PROF_T(15); }
#pragma unroll
        for (int s = 1; s < 4; s++) { WAIT1(s, 1); wg_fence(); MMA1_P(0, s, false, s == 3); }
        wg_commit();
        const int mrow = wq * 16 + ((lane >> 3) & 1) * 8 + (lane & 7);
#define EPI1(O, slot, FREE) do { const uint32_t dst = sb + OFF_S + (slot) * SLOT + mrow * 128; \
            uint32_t pk[32]; \
            _Pragma("unroll") for (int i = 0; i < 32; i += 4) { \
                _Pragma("unroll") for (int k = 0; k < 4; k++) \
                    pk[i + k] = pack_bf(acc[(O) + 2 * (i + k)] * rs[(O) / 32 + (k & 1)], acc[(O) + 2 * (i + k) + 1] * rs[(O) / 32 + (k & 1)]); \
                if (i == EF) { FREE; } \
                if (i >= EF) { _Pragma("unroll") for (int v = (i == EF ? 0 : i); v <= i; v += 4) \
                    stmatrix4(dst + ((v >> 4) ^ c ^ 1) * 8192 + ((((v >> 1) & 7) + (lane >> 4)) ^ (lane & 7)) * 16, pk[v], pk[v + 1], pk[v + 2], pk[v + 3]); } } \
            fence_async_smem(); WG_BAR(); \
            if (wt == 0) mbar_arrive(BAR(B_FS + (slot))); } while (0)
        TS(15);
        wg_wait<0>();
        fence_regs64<0>(acc);
        TS(16);
        {
            constexpr int EF = 0;
            EPI1(0, wg, if (wg) mbar_wait(BAR(B_FS), 0));
        }
        TS(17);
        TURN();
        wg_fence();
        MMA1_H(64, 0, false); wg_commit();
        MMA1_H(64, 1, false); wg_commit();
        MMA1_H(64, 2, false); wg_commit();
        wg_wait<2>(); REL1(0);
        MMA1_P(64, 3, false, true); wg_commit();
        TS(18);
        wg_wait<2>(); REL1(1);
        wg_wait<1>(); REL1(2);
        wg_wait<0>(); REL1(3);
        fence_regs64<64>(acc);
        TS(19);
        {
            constexpr int EF = 12;
            EPI1(64, 2 + wg, mbar_wait(BAR(B_ES + 2 + wg), 1));
        }
        TS(20);

        float ac2[128];
#define MMA2_P(O, ls, ss, first, pass) do { _Pragma("unroll") for (int kk = 0; kk < 4; kk++) { if (kk == PK && (pass)) PASS(); \
            wgmma128<O, 1>(ac2, dS + (ss) * SL + kk * 128 + (O) * 8, dL + (ls) * SL + kk * 2, !((first) && kk == 0)); } \
            if (PK == 4 && (pass)) PASS(); } while (0)
#define MMA2_H(O, ls, ss, first) MMA2_P(O, ls, ss, first, false)
#define WAIT2(j) WAIT_FULL((j) & 3, ((j) >> 2) & 1, PSLOT(j), PPAR(j))
#define MMA2(j, pass) do { wg_fence(); MMA2_H(0, (j) & 3, PSLOT(j), (j) == 0); MMA2_P(64, (j) & 3, PSLOT(j), (j) == 0, pass); wg_commit(); } while (0)
#define REL2(j) RELEASE((j) & 3, PSLOT(j))
        if (GOJ == 0 && wt == 0) mbar_arrive(BAR(B_GO));
        WAIT2(0); TURN(); MMA2(0, false);
        WAIT2(1); MMA2(1, true);
        TS(21);
        wg_wait<1>(); REL2(0);
        TS(22);
        {
            uint32_t sp = 1;
#pragma unroll 1
            for (int j = 2; j < XJ; j++) {
                const uint32_t ss = PSLOT(j);
                const bool ok = PROBE(j & 3, (j >> 2) & 1, ss, PPAR(j));
                PEEK();
                wg_wait<0>(); RELEASE((j - 1) & 3, sp);
                if (!ok) WAIT_FULL(j & 3, (j >> 2) & 1, ss, PPAR(j));
                HOLD(16 + j);
                TURN();
                wg_fence(); MMA2_H(0, j & 3, ss, false); MMA2_P(64, j & 3, ss, false, true); wg_commit();
                if (j == GOJ && wt == 0) { mbar_arrive(BAR(B_GO)); if (wg == 0) PROF_T(19); }
                sp = ss;
            }
        }
        if (tid == 0) PROF_T(20);
        uint32_t gt[32];
        const uint32_t xrow = sb + OFF_S + (2 + wg) * SLOT + ((lane >> 4) * 8 + (lane & 7)) * 128 + (((2 * wq + ((lane >> 3) & 1)) ^ (lane & 7)) << 4);
        const uint32_t gsign = c ? 0x80008000u : 0u;
        mbar_wait(BAR(B_FS + 2 + wg), 1);
        mbar_wait(BAR(B_SEL), 0);
        const int sel = 0xffff - (int)(*reinterpret_cast<volatile unsigned*>(smem + OFF_SEL) & 0xffffu);
        bool own = (sel >> 7) == 2 * g + wg;
#define PATCH() do { own = false; \
            const uint32_t v0 = *reinterpret_cast<const uint16_t*>(smem + OFF_H + (wq * 16 + (lane >> 2)) * 2) ^ gsign; \
            const uint32_t v1 = *reinterpret_cast<const uint16_t*>(smem + OFF_H + (wq * 16 + (lane >> 2)) * 2 + 16) ^ gsign; \
            const uint32_t pick = (lane & 3) != ((sel >> 1) & 3) ? 0x3210u : (sel & 1) ? 0x5410u : 0x3254u; \
            _Pragma("unroll") for (int i = 0; i < 16; i++) { \
                const uint32_t m = ((sel >> 3) & 15) == i ? pick : 0x3210u; \
                gt[2 * i] = __byte_perm(gt[2 * i], v0, m); \
                gt[2 * i + 1] = __byte_perm(gt[2 * i + 1], v1, m); \
            } } while (0)
#pragma unroll
        for (int v = 0; v < 28 - XJ; v++) {
            WAIT2(XJ + v); wg_wait<0>(); REL2(XJ + v - 1); TURN(); MMA2(XJ + v, true);
            constexpr int NS = 8 / (28 - XJ);
#pragma unroll
            for (int u = v * NS; u < (v + 1) * NS; u++) {
                uint32_t* o = &gt[4 * u];
                ldmatrix4t(xrow + u * 2048, o[0], o[1], o[2], o[3]);
                const float4 r4 = *reinterpret_cast<const float4*>(smem + OFF_RSTD + (wg * 128 + u * 16 + (lane & 3) * 4) * 4);
                const uint2 m2 = *reinterpret_cast<const uint2*>(smem + OFF_MEAN + (wg * 128 + u * 16 + (lane & 3) * 4) * 2);
                o[0] = gate2(o[0], m2.x, r4.x, r4.y) ^ gsign;
                o[1] = gate2(o[1], m2.x, r4.x, r4.y) ^ gsign;
                o[2] = gate2(o[2], m2.y, r4.z, r4.w) ^ gsign;
                o[3] = gate2(o[3], m2.y, r4.z, r4.w) ^ gsign;
                asm volatile("st.shared.v2.u32 [%0], {%1,%2};" ::"r"(sb + OFF_SEL + 16), "r"(o[0] ^ o[1]), "r"(o[2] ^ o[3]) : "memory");
            }
        }
        if (tid == 0) PROF_T(21);
        WAIT2(28);
        wg_wait<0>(); REL2(27);
        if (own && mbar_test(BAR(B_UPD), 0)) PATCH();
        TS(0);
        TURN();
        wg_fence(); MMA2_H(0, 0, PSLOT(28), false); wg_commit();
        if (wg == 0 || !ASYM) { wg_fence(); MMA2_H(64, 0, PSLOT(28), false); wg_commit(); }
        WAIT2(29); wg_fence(); MMA2_H(0, 1, PSLOT(29), false); wg_commit();
        WAIT2(30); wg_fence(); MMA2_H(0, 2, PSLOT(30), false); wg_commit();
        wg_wait<2>();
        if (tid == 0) mbar_arrive_cluster(mapa(BAR(B_RDY), c ^ 1));
        WAIT2(31); wg_fence(); MMA2_H(0, 3, PSLOT(31), false); wg_commit();
        TS(1);
#define KEEP(i) wgmma128<64, 1>(ac2, dS + PSLOT(29 + ((i) >> 2)) * SL + ((i) & 3) * 128 + 512, dL + (1 + ((i) >> 2)) * SL + ((i) & 3) * 2, 1)
        wg_fence();
#pragma unroll
        for (int i = 0; i < KQ; i++) KEEP(i);
        wg_commit();
        mbar_wait(BAR(B_RDY + wg), 0);
        wg_wait<1>();
        fence_regs64<0>(ac2);
        TS(2);
        wg_fence();
        {
            const uint32_t dst = mapa(sb + OFF_L + wg * SLOT + wt * 16, c ^ 1), rb = mapa(BAR(B_RECV + wg), c ^ 1);
#pragma unroll
            for (int v = 0; v < 8; v++) {
                if (KQ + v < 12) KEEP(KQ + v);
                if (KQ + v == 11) { wg_commit(); if (wg == 0) PASS(); }
                st_async4(dst + v * 2048, pack_bf(ac2[8 * v + 0], ac2[8 * v + 1]), pack_bf(ac2[8 * v + 2], ac2[8 * v + 3]),
                          pack_bf(ac2[8 * v + 4], ac2[8 * v + 5]), pack_bf(ac2[8 * v + 6], ac2[8 * v + 7]), rb);
            }
        }
        if (wg == 1 && ASYM) { wg_fence(); MMA2_H(64, 0, PSLOT(28), false); wg_commit(); }
        TS(3);
        uint32_t xr[32];
#pragma unroll
        for (int v = 0; v < 8; v++) ldmatrix4t(xrow + v * 2048, xr[4 * v], xr[4 * v + 1], xr[4 * v + 2], xr[4 * v + 3]);
        if (wg == 0) {
            wg_wait<0>();
            if (wt == 0) mbar_arrive_cluster(mapa(BAR(B_RDY + 1), c ^ 1));
        }
        TS(4);
        if (own) { mbar_wait(BAR(B_UPD), 0); PATCH(); }
        TS(5);
        mbar_wait_cluster(BAR(B_RECV + wg), 0);
        TS(6);
        uint4 rv[8];
#pragma unroll
        for (int v = 0; v < 8; v++) rv[v] = *reinterpret_cast<const uint4*>(smem + OFF_L + wg * SLOT + v * 2048 + wt * 16);
        wg_wait<0>();
        fence_regs64<64>(ac2);
        TS(7);
#pragma unroll
        for (int v = 0; v < 8; v++) {
            const float* a = &ac2[64 + 8 * v];
            stmatrix4t(xrow + v * 2048,
                       bfma2(bsub2(pack_bf(a[0], a[1]), rv[v].x), gt[4 * v + 0], xr[4 * v + 0]),
                       bfma2(bsub2(pack_bf(a[2], a[3]), rv[v].y), gt[4 * v + 1], xr[4 * v + 1]),
                       bfma2(bsub2(pack_bf(a[4], a[5]), rv[v].z), gt[4 * v + 2], xr[4 * v + 2]),
                       bfma2(bsub2(pack_bf(a[6], a[7]), rv[v].w), gt[4 * v + 3], xr[4 * v + 3]));
            if (v % OP == OP - 1) {
                if (HELP) {
                    __syncwarp();
                    if (lane == 0) mbar_arrive(BAR((v / OP ? B_STATS : B_OUT) + wg));
                } else {
                    fence_async_smem();
                    WG_BAR();
                    if (wt == 0) {
                        tma_2d_store(&tm_out, grp * 64, g * 256 + wg * 128 + (v + 1 - OP) * 16, sb + OFF_S + (2 + wg) * SLOT + (v + 1 - OP) * 2048);
                        bulk_commit();
                    }
                }
                if (v == OP - 1) TS(8);
                if (v == 7) TS(9);
            }
        }
        if (!HELP && wt == 0) { const int w = wg; FINISH(w); }
    }
}

typedef CUresult (*EncodeFn)(CUtensorMap*, CUtensorMapDataType, cuuint32_t, void*, const cuuint64_t*, const cuuint64_t*,
                             const cuuint32_t*, const cuuint32_t*, CUtensorMapInterleave, CUtensorMapSwizzle,
                             CUtensorMapL2promotion, CUtensorMapFloatOOBfill);

void make_map(EncodeFn fn, CUtensorMap* tm, const void* p, uint64_t rows, uint64_t cols, uint32_t box_rows,
              CUtensorMapL2promotion promo = CU_TENSOR_MAP_L2_PROMOTION_L2_128B) {
    cuuint64_t dims[2] = {cols, rows};
    cuuint64_t strides[1] = {cols * 2};
    cuuint32_t box[2] = {64, box_rows};
    cuuint32_t es[2] = {1, 1};
    fn(tm, CU_TENSOR_MAP_DATA_TYPE_BFLOAT16, 2, const_cast<void*>(p), dims, strides, box, es, CU_TENSOR_MAP_INTERLEAVE_NONE,
       CU_TENSOR_MAP_SWIZZLE_128B, promo, CU_TENSOR_MAP_FLOAT_OOB_FILL_NONE);
}

}

extern "C" void kernel_launch(void* const* d_in, const int* in_sizes, int n_in, void* d_out, int out_size) {
    (void)in_sizes; (void)n_in; (void)out_size;
    static EncodeFn fn = nullptr;
    if (!fn) {
        void* p = nullptr;
        cudaDriverEntryPointQueryResult q;
        cudaGetDriverEntryPoint("cuTensorMapEncodeTiled", &p, cudaEnableDefault, &q);
        fn = (EncodeFn)p;
        cudaFuncSetAttribute(fnet_fused_kernel, cudaFuncAttributeMaxDynamicSharedMemorySize, SMEM_BYTES);
    }
    CUtensorMap tx, tdre, tdim, tcre, tcim, tout;
    make_map(fn, &tx, d_in[0], S_, D_, 128, PRX);
    make_map(fn, &tcre, d_in[1], S_, S_, 128, PRC);
    make_map(fn, &tcim, d_in[2], S_, S_, 128, PRC);
    make_map(fn, &tdre, d_in[3], D_, D_, 128, PRD);
    make_map(fn, &tdim, d_in[4], D_, D_, 128, PRD);
    make_map(fn, &tout, d_out, S_, D_, 16 * OP);
    Params P;
    P.x = (const __nv_bfloat16*)d_in[0];
    P.dre = (const __nv_bfloat16*)d_in[3];
    P.dim = (const __nv_bfloat16*)d_in[4];
    P.wr = (const __nv_bfloat16*)d_in[6];
    P.wg = (const __nv_bfloat16*)d_in[7];
    P.wu = (const __nv_bfloat16*)d_in[8];
    P.wd = (const __nv_bfloat16*)d_in[9];
    P.zero = 0;
    fnet_fused_kernel<<<NCTA, NTHREADS, SMEM_BYTES, cudaStreamPerThread>>>(tx, tdre, tdim, tcre, tcim, tout, P);
}
```

```cpp
#include <cuda_runtime.h>
#include <cuda_bf16.h>
#include <cuda.h>
#include <stdint.h>

#define LDEL 0
#define XS 0x5431
#define GSL 200
#define YNS 0u
#define YLD 1
#define PDEL 2500
#define PGAP 600
#define PK 4
#define ASYM 1
#define KQ 4
#define OP 4
#define XJ0 20
#define EGAP1 0
#define EGAP2 0
#define ESTAG 120
#define QJ 12
#define GOJ 2
#define TANH 1
#define SYNCS 0x22200020ull
#define K0 0
#define KRD 1500
#define SYNCD 2
#define SYNCCAP 4000u
#define SYNCMIN 24u
#define SYNCLAG 820u
#define QUIET 1
#define PRX CU_TENSOR_MAP_L2_PROMOTION_L2_128B
#define PRD CU_TENSOR_MAP_L2_PROMOTION_L2_128B
#define PRC CU_TENSOR_MAP_L2_PROMOTION_L2_128B
#define SLEEP_NS 200
#define PROD_REGS 32
#define CONS_REGS 184

namespace {

constexpr int S_ = 2048, D_ = 1024, F_ = 3584;
constexpr int NCTA = 128;
constexpr int XJ = XJ0;
constexpr uint32_t SLOT = 16384;
constexpr uint32_t OFF_L = 0;
constexpr uint32_t OFF_S = 8 * SLOT;
constexpr uint32_t OFF_RS = OFF_S + SLOT;
constexpr uint32_t OFF_BAR = 14 * SLOT;
constexpr uint32_t OFF_SEL = OFF_BAR + 360;
constexpr uint32_t OFF_RSTD = OFF_BAR + 384;
constexpr uint32_t OFF_MEAN = OFF_RSTD + 1024;
constexpr uint32_t OFF_XB = OFF_MEAN + 512;
constexpr uint32_t OFF_H = OFF_XB + 1024;
constexpr uint32_t SMEM_BYTES = OFF_H + 128;
constexpr uint32_t OFF_TS = OFF_XB + 512;
constexpr uint32_t SB0 = 1024;
constexpr int NTHREADS = 512;
static_assert(SMEM_BYTES <= 232448, "smem");

enum { B_FS = 0, B_ES = 6, B_FL = 12, B_EL = 20, B_SRD = 28, B_OUT = 30, B_RECV = 32, B_RDY = 34, B_STATS = 36, B_LST = 37  , B_UPD = 38,
       B_QUIET = 39, B_GO = 40, B_PEER = 41, B_SEL = 42, B_H = 43, B_COUNT = 44 };
static_assert(B_COUNT * 8 <= 360, "barriers");

__device__ __align__(1024) uint8_t g_ab[16u * 32u * SLOT];
__device__ __align__(128) uint4 g_part[56 * (D_ / 4)];
__device__ __align__(128) uint4 g_stat[S_];
__device__ __align__(128) uint4 g_rs[D_];
__device__ __align__(128) unsigned long long g_key[NCTA];
__device__ __align__(128) unsigned long long g_flag[16 * 16];
__device__ __align__(128) unsigned long long g_sync[16 * 16];
__device__ __align__(128) unsigned g_epoch[NCTA];
#define PROF_T(i) do {} while (0)
#define TRACE(i) do {} while (0)
#define PROF_G(i) do {} while (0)
#define TS(i) do {} while (0)
#define FINISH(wg) bulk_wait_read<0>()

#define MARK(it, ph) do {} while (0)

__device__ __forceinline__ uint32_t smem_u32(const void* p) { return (uint32_t)__cvta_generic_to_shared(p); }
__device__ __forceinline__ void mbar_init(uint32_t bar, uint32_t cnt) {
    asm volatile("mbarrier.init.shared::cta.b64 [%0], %1;" ::"r"(bar), "r"(cnt) : "memory");
}
__device__ __forceinline__ bool mbar_try(uint32_t bar, uint32_t parity) {
    uint32_t ok;
    asm volatile("{\n.reg .pred p;\nmbarrier.try_wait.parity.shared::cta.b64 p, [%1], %2;\nselp.u32 %0, 1, 0, p;\n}"
                 : "=r"(ok) : "r"(bar), "r"(parity) : "memory");
    return ok;
}
__device__ __forceinline__ bool mbar_test(uint32_t bar, uint32_t parity) {
    uint32_t ok;
    asm volatile("{\n.reg .pred p;\nmbarrier.test_wait.parity.shared::cta.b64 p, [%1], %2;\nselp.u32 %0, 1, 0, p;\n}"
                 : "=r"(ok) : "r"(bar), "r"(parity) : "memory");
    return ok;
}
__device__ __forceinline__ bool mbar_try_cluster(uint32_t bar, uint32_t parity) {
    uint32_t ok;
    asm volatile("{\n.reg .pred p;\nmbarrier.try_wait.parity.acquire.cluster.shared::cta.b64 p, [%1], %2;\nselp.u32 %0, 1, 0, p;\n}"
                 : "=r"(ok) : "r"(bar), "r"(parity) : "memory");
    return ok;
}
constexpr int SPIN_LIMIT = 1 << 20;
__device__ __forceinline__ void mbar_wait(uint32_t bar, uint32_t parity) {
    if (mbar_try(bar, parity)) return;
    int n = 0;
    while (!mbar_try(bar, parity) && ++n < SPIN_LIMIT) {}
}
__device__ __forceinline__ void mbar_wait_cluster(uint32_t bar, uint32_t parity) {
    int n = 0;
    while (!mbar_try_cluster(bar, parity) && ++n < SPIN_LIMIT) {}
}
__device__ __forceinline__ void mbar_wait_sleep(uint32_t bar, uint32_t parity) {
    int n = 0;
    while (!mbar_try(bar, parity) && ++n < SPIN_LIMIT) __nanosleep(SLEEP_NS);
}
__device__ __forceinline__ void mbar_arrive(uint32_t bar) {
    asm volatile("mbarrier.arrive.shared::cta.b64 _, [%0];" ::"r"(bar) : "memory");
}
__device__ __forceinline__ void mbar_arrive_cluster(uint32_t cluster_bar) {
    asm volatile("mbarrier.arrive.shared::cluster.b64 _, [%0];" ::"r"(cluster_bar) : "memory");
}
__device__ __forceinline__ void mbar_expect_tx(uint32_t bar, uint32_t bytes) {
    asm volatile("mbarrier.arrive.expect_tx.shared::cta.b64 _, [%0], %1;" ::"r"(bar), "r"(bytes) : "memory");
}
__device__ __forceinline__ bool elect_one() {
    uint32_t p;
    asm volatile("{\n.reg .pred p;\nelect.sync _|p, 0xffffffff;\nselp.u32 %0, 1, 0, p;\n}" : "=r"(p));
    return p;
}
__device__ __forceinline__ uint32_t mapa(uint32_t addr, uint32_t rank) {
    uint32_t r;
    asm("mapa.shared::cluster.u32 %0, %1, %2;" : "=r"(r) : "r"(addr), "r"(rank));
    return r;
}
__device__ __forceinline__ uint32_t clock32() { uint32_t t; asm volatile("mov.u32 %0, %%clock;" : "=r"(t)); return t; }
__device__ __forceinline__ void sleep_until(uint32_t t) {
    int n = 0;
    while ((int)(clock32() - t) < 0 && ++n < SPIN_LIMIT) __nanosleep(20);
}
__device__ __forceinline__ void yield(float last, uint32_t zero) {
    if (YLD) asm volatile("nanosleep.u32 %0;" ::"r"((__float_as_uint(last) & zero) | YNS));
}
template <typename T> __device__ __forceinline__ T* at(T* p, uint32_t bytes) {
    asm("" : "+r"(bytes));
    return reinterpret_cast<T*>(reinterpret_cast<uintptr_t>(p) + bytes);
}
__device__ __forceinline__ void tma_2d(uint32_t dst, const CUtensorMap* tm, int c0, int c1, uint32_t bar) {
    asm volatile("cp.async.bulk.tensor.2d.shared::cluster.global.mbarrier::complete_tx::bytes [%0], [%1, {%3, %4}], [%2];"
                 ::"r"(dst), "l"(tm), "r"(bar), "r"(c0), "r"(c1) : "memory");
}
__device__ __forceinline__ void tma_2d_store(const CUtensorMap* tm, int c0, int c1, uint32_t src) {
    asm volatile("cp.async.bulk.tensor.2d.global.shared::cta.bulk_group [%0, {%2, %3}], [%1];"
                 ::"l"(tm), "r"(src), "r"(c0), "r"(c1) : "memory");
}
__device__ __forceinline__ void bulk_g2s(uint32_t dst, const void* src, uint32_t bytes, uint32_t bar) {
    asm volatile("cp.async.bulk.shared::cluster.global.mbarrier::complete_tx::bytes [%0], [%1], %2, [%3];"
                 ::"r"(dst), "l"(src), "r"(bytes), "r"(bar) : "memory");
}
__device__ __forceinline__ void bulk_s2g(void* dst, uint32_t src, uint32_t bytes) {
    asm volatile("cp.async.bulk.global.shared::cta.bulk_group [%0], [%1], %2;" ::"l"(dst), "r"(src), "r"(bytes) : "memory");
}
__device__ __forceinline__ void st_async4(uint32_t dst, uint32_t a, uint32_t b, uint32_t c, uint32_t d, uint32_t bar) {
    asm volatile("st.async.weak.shared::cluster.mbarrier::complete_tx::bytes.v4.b32 [%0], {%1,%2,%3,%4}, [%5];"
                 ::"r"(dst), "r"(a), "r"(b), "r"(c), "r"(d), "r"(bar) : "memory");
}
__device__ __forceinline__ void bulk_commit() { asm volatile("cp.async.bulk.commit_group;" ::: "memory"); }
template <int N> __device__ __forceinline__ void bulk_wait_read() { asm volatile("cp.async.bulk.wait_group.read %0;" ::"n"(N) : "memory"); }
template <int N> __device__ __forceinline__ void bulk_wait() { asm volatile("cp.async.bulk.wait_group %0;" ::"n"(N) : "memory"); }
__device__ __forceinline__ void fence_async_smem() { asm volatile("fence.proxy.async.shared::cta;" ::: "memory"); }
__device__ __forceinline__ void fence_async_global() { asm volatile("fence.proxy.async.global;" ::: "memory"); }
__device__ __forceinline__ void prefetch_tmap(const CUtensorMap* tm) {
    asm volatile("prefetch.tensormap [%0];" ::"l"(tm) : "memory");
}
__device__ __forceinline__ unsigned long long ld_acquire64(const unsigned long long* p) {
    unsigned long long v; asm volatile("ld.acquire.gpu.global.u64 %0, [%1];" : "=l"(v) : "l"(p) : "memory"); return v;
}
__device__ __forceinline__ unsigned load_epoch(int b) {
    unsigned v; asm volatile("ld.global.u32 %0, [%1];" : "=r"(v) : "l"(at(g_epoch, b * 4)) : "memory"); return v + 1;
}
__device__ __forceinline__ unsigned ld_relaxed(const void* p) {
    unsigned v; asm volatile("ld.relaxed.gpu.global.u32 %0, [%1];" : "=r"(v) : "l"(p) : "memory"); return v;
}
__device__ __forceinline__ unsigned long long ld_relaxed64(const unsigned long long* p) {
    unsigned long long v; asm volatile("ld.relaxed.gpu.global.u64 %0, [%1];" : "=l"(v) : "l"(p) : "memory"); return v;
}
__device__ __forceinline__ void red_max64(unsigned long long* p, unsigned long long v) {
    asm volatile("red.relaxed.gpu.global.max.u64 [%0], %1;" ::"l"(p), "l"(v) : "memory");
}
__device__ __forceinline__ uint4 ld_relaxed128(const uint4* p) {
    uint4 v;
    asm volatile("{\n.reg .b128 t;\n.reg .b64 lo, hi;\nld.relaxed.gpu.global.b128 t, [%4];\nmov.b128 {lo, hi}, t;\n"
                 "mov.b64 {%0, %1}, lo;\nmov.b64 {%2, %3}, hi;\n}"
                 : "=r"(v.x), "=r"(v.y), "=r"(v.z), "=r"(v.w) : "l"(p) : "memory");
    return v;
}
__device__ __forceinline__ void st_relaxed128(uint4* p, const uint4& v) {
    asm volatile("{\n.reg .b128 t;\n.reg .b64 lo, hi;\nmov.b64 lo, {%1, %2};\nmov.b64 hi, {%3, %4};\nmov.b128 t, {lo, hi};\n"
                 "st.relaxed.gpu.global.b128 [%0], t;\n}"
                 ::"l"(p), "r"(v.x), "r"(v.y), "r"(v.z), "r"(v.w) : "memory");
}
__device__ __forceinline__ void st_relaxed64(unsigned long long* p, unsigned long long v) {
    asm volatile("st.relaxed.gpu.global.u64 [%0], %1;" ::"l"(p), "l"(v) : "memory");
}
__device__ __forceinline__ void st_release8(void* p, unsigned v) {
    asm volatile("st.release.gpu.global.u8 [%0], %1;" ::"l"(p), "r"(v) : "memory");
}
__device__ __forceinline__ uint64_t policy_evict_first() {
    uint64_t pol;
    asm("createpolicy.fractional.L2::evict_first.b64 %0, 1.0;" : "=l"(pol));
    return pol;
}
__device__ __forceinline__ uint4 ldg_stream(const void* p, uint64_t pol) {
    uint4 v;
    asm volatile("ld.global.nc.L1::no_allocate.L2::cache_hint.v4.u32 {%0,%1,%2,%3}, [%4], %5;"
                 : "=r"(v.x), "=r"(v.y), "=r"(v.z), "=r"(v.w) : "l"(p), "l"(pol));
    return v;
}
template <int ID, int N> __device__ __forceinline__ void named_arrive() { asm volatile("bar.arrive %0, %1;" ::"n"(ID), "n"(N) : "memory"); }
template <int ID, int N> __device__ __forceinline__ void named_bar() { asm volatile("bar.sync %0, %1;" ::"n"(ID), "n"(N) : "memory"); }

__device__ __forceinline__ float bf_lo(uint32_t u) { return __uint_as_float(u << 16); }
__device__ __forceinline__ float bf_hi(uint32_t u) { return __uint_as_float(u & 0xffff0000u); }
__device__ __forceinline__ uint32_t pack_bf(float lo, float hi) {
    uint32_t r; asm("cvt.rn.bf16x2.f32 %0, %1, %2;" : "=r"(r) : "f"(hi), "f"(lo)); return r;
}
__device__ __forceinline__ float rbf(float v) { return __bfloat162float(__float2bfloat16_rn(v)); }
__device__ __forceinline__ float sqrt_f(float v) { float r; asm("sqrt.approx.f32 %0, %1;" : "=f"(r) : "f"(v)); return r; }
__device__ __forceinline__ float rcp_f(float v) { float r; asm("rcp.approx.f32 %0, %1;" : "=f"(r) : "f"(v)); return r; }
__device__ __forceinline__ float silu_f(float z) { return __fdividef(z, 1.0f + __expf(-z)); }
__device__ __forceinline__ uint32_t bsub2(uint32_t a, uint32_t b) {
    uint32_t r; asm("sub.rn.bf16x2 %0, %1, %2;" : "=r"(r) : "r"(a), "r"(b)); return r;
}
__device__ __forceinline__ uint32_t bfma2(uint32_t a, uint32_t b, uint32_t c) {
    uint32_t r; asm("fma.rn.bf16x2 %0, %1, %2, %3;" : "=r"(r) : "r"(a), "r"(b), "r"(c)); return r;
}
__device__ __forceinline__ uint32_t norm2(uint32_t xv, float m, float rinv) {
    uint32_t t = pack_bf(bf_lo(xv) - m, bf_hi(xv) - m);
    return pack_bf(bf_lo(t) * rinv, bf_hi(t) * rinv);
}
__device__ __forceinline__ float gate1(float z) {
    if (TANH) {
        float t;
        const float h = 0.5f * z;
        asm("tanh.approx.f32 %0, %1;" : "=f"(t) : "f"(h));
        return fmaf(h, t, h);
    }
    float e, r;
    asm("ex2.approx.ftz.f32 %0, %1;" : "=f"(e) : "f"(z * -1.4426950408889634f));
    asm("rcp.approx.ftz.f32 %0, %1;" : "=f"(r) : "f"(1.0f + e));
    return z * r;
}
__device__ __forceinline__ uint32_t gate2(uint32_t xv, uint32_t mean2, float r0, float r1) {
    const uint32_t t = bsub2(xv, mean2);
    return pack_bf(gate1(bf_lo(t) * r0), gate1(bf_hi(t) * r1));
}
__device__ __forceinline__ uint32_t silu2(uint32_t z) { return pack_bf(silu_f(bf_lo(z)), silu_f(bf_hi(z))); }

__device__ __forceinline__ void stmatrix4(uint32_t addr, uint32_t r0, uint32_t r1, uint32_t r2, uint32_t r3) {
    asm volatile("stmatrix.sync.aligned.m8n8.x4.shared.b16 [%0], {%1,%2,%3,%4};"
                 ::"r"(addr), "r"(r0), "r"(r1), "r"(r2), "r"(r3));
}
__device__ __forceinline__ void stmatrix4t(uint32_t addr, uint32_t r0, uint32_t r1, uint32_t r2, uint32_t r3) {
    asm volatile("stmatrix.sync.aligned.m8n8.x4.trans.shared.b16 [%0], {%1,%2,%3,%4};"
                 ::"r"(addr), "r"(r0), "r"(r1), "r"(r2), "r"(r3));
}
__device__ __forceinline__ void ldmatrix4t(uint32_t addr, uint32_t& r0, uint32_t& r1, uint32_t& r2, uint32_t& r3) {
    asm volatile("ldmatrix.sync.aligned.m8n8.x4.trans.shared.b16 {%0,%1,%2,%3}, [%4];"
                 : "=r"(r0), "=r"(r1), "=r"(r2), "=r"(r3) : "r"(addr));
}

__device__ __forceinline__ void wg_fence() { asm volatile("wgmma.fence.sync.aligned;" ::: "memory"); }
__device__ __forceinline__ void wg_commit() { asm volatile("wgmma.commit_group.sync.aligned;" ::: "memory"); }
template <int N> __device__ __forceinline__ void wg_wait() { asm volatile("wgmma.wait_group.sync.aligned %0;" ::"n"(N) : "memory"); }

__host__ __device__ constexpr uint32_t desc_lo(uint32_t addr, uint32_t lbo) { return ((addr & 0x3FFFF) >> 4) | ((lbo >> 4) << 16); }
#define DESC_HI "0x40000040"

#define R8(a, o) "+f"(a[(o) + 0]), "+f"(a[(o) + 1]), "+f"(a[(o) + 2]), "+f"(a[(o) + 3]), \
                 "+f"(a[(o) + 4]), "+f"(a[(o) + 5]), "+f"(a[(o) + 6]), "+f"(a[(o) + 7])
#define R64(a, o) R8(a, (o) + 0), R8(a, (o) + 8), R8(a, (o) + 16), R8(a, (o) + 24), \
                  R8(a, (o) + 32), R8(a, (o) + 40), R8(a, (o) + 48), R8(a, (o) + 56)

template <int O, int TA>
__device__ __forceinline__ void wgmma128(float (&a)[128], uint32_t da, uint32_t db, int scale_d) {
    asm volatile(
        "{\n.reg .pred p;\n.reg .b64 da, db;\nsetp.ne.b32 p, %66, 0;\n"
        "mov.b64 da, {%64, " DESC_HI "};\nmov.b64 db, {%65, " DESC_HI "};\n"
        "wgmma.mma_async.sync.aligned.m64n128k16.f32.bf16.bf16 "
        "{%0,%1,%2,%3,%4,%5,%6,%7,%8,%9,%10,%11,%12,%13,%14,%15,"
        "%16,%17,%18,%19,%20,%21,%22,%23,%24,%25,%26,%27,%28,%29,%30,%31,"
        "%32,%33,%34,%35,%36,%37,%38,%39,%40,%41,%42,%43,%44,%45,%46,%47,"
        "%48,%49,%50,%51,%52,%53,%54,%55,%56,%57,%58,%59,%60,%61,%62,%63},"
        "da, db, p, 1, 1, %67, 0;\n}"
        : R64(a, O)
        : "r"(da), "r"(db), "r"(scale_d), "n"(TA));
}
template <int O>
__device__ __forceinline__ void wgmma128_rs(float (&a)[128], const uint32_t* f, uint32_t db) {
    asm volatile(
        "{\n.reg .b64 db;\nmov.b64 db, {%68, 8};\n"
        "wgmma.mma_async.sync.aligned.m64n128k16.f32.bf16.bf16 "
        "{%0,%1,%2,%3,%4,%5,%6,%7,%8,%9,%10,%11,%12,%13,%14,%15,"
        "%16,%17,%18,%19,%20,%21,%22,%23,%24,%25,%26,%27,%28,%29,%30,%31,"
        "%32,%33,%34,%35,%36,%37,%38,%39,%40,%41,%42,%43,%44,%45,%46,%47,"
        "%48,%49,%50,%51,%52,%53,%54,%55,%56,%57,%58,%59,%60,%61,%62,%63},"
        "{%64, %65, %66, %67}, db, 1, 1, 1, 0;\n}"
        : R64(a, O)
        : "r"(f[0]), "r"(f[1]), "r"(f[2]), "r"(f[3]), "r"(db));
}
template <int O>
__device__ __forceinline__ void fence_regs64(float (&a)[128]) {
    asm volatile("" : R64(a, O)::"memory");
}

struct Params {
    const __nv_bfloat16* x;
    const __nv_bfloat16* dre;
    const __nv_bfloat16* dim;
    const __nv_bfloat16* wr;
    const __nv_bfloat16* wg;
    const __nv_bfloat16* wu;
    const __nv_bfloat16* wd;
    uint32_t zero;
#define AB g_ab
};

__device__ __forceinline__ float warp_sum(float v) {
#pragma unroll
    for (int o = 16; o; o >>= 1) v += __shfl_xor_sync(0xffffffffu, v, o);
    return v;
}
__device__ __forceinline__ void fma8(float* acc, const uint4& w, float s) {
    acc[0] += s * bf_lo(w.x); acc[1] += s * bf_hi(w.x); acc[2] += s * bf_lo(w.y); acc[3] += s * bf_hi(w.y);
    acc[4] += s * bf_lo(w.z); acc[5] += s * bf_hi(w.z); acc[6] += s * bf_lo(w.w); acc[7] += s * bf_hi(w.w);
}
__device__ __forceinline__ int POS(int t) { return (t & ~15) | ((t & 6) << 1) | ((t & 8) >> 2) | (t & 1); }
__host__ __device__ constexpr int PSLOT(int j) { return j < 4 ? j : (j & 1) + ((j & 2) ? 0 : 4); }
__host__ __device__ constexpr int PPAR(int j) { return j < 4 ? 0 : ((j >> 2) ^ (j >> 1) ^ 1) & 1; }
__host__ __device__ constexpr int DSLOT(int it) { return (it & 3) + 2; }
__device__ __forceinline__ int SREC(int t) { return (t & ~15) | ((t & 3) << 2) | ((t >> 2) & 3); }
__device__ __forceinline__ int KO(int cl) { return ((cl & 1) << 1) | (cl >> 1); }

__device__ __forceinline__ unsigned long long* sync_words() {
    uint32_t t;
    asm volatile("mov.u32 %0, %%smid;" : "=r"(t));
    t >>= 1;
    const uint32_t u = t - 32;
    return at(g_sync, (t < 32 ? t & 7 : t < 60 ? 8 + u - 7 * ((u * 37) >> 8) : 15) * 128);
}

__global__ void __cluster_dims__(2, 1, 1) __launch_bounds__(NTHREADS, 1)
fnet_fused_kernel(const __grid_constant__ CUtensorMap tm_x, const __grid_constant__ CUtensorMap tm_dre,
                  const __grid_constant__ CUtensorMap tm_dim, const __grid_constant__ CUtensorMap tm_cre,
                  const __grid_constant__ CUtensorMap tm_cim, const __grid_constant__ CUtensorMap tm_out,
                  const Params P) {
    extern __shared__ __align__(1024) uint8_t smem[];
    const unsigned long long tstart = clock64();
    const uint32_t sb = smem_u32(smem);
    const int tid = threadIdx.x, lane = tid & 31;
    const int warp = __shfl_sync(0xffffffffu, tid >> 5, 0);
    const int pr = blockIdx.x >> 1, p7 = ((pr - 36) * 37) >> 8;
    const int c = blockIdx.x & 1;
    const int g = pr < 4 ? 0 : pr < 36 ? (pr - 4) & 7 : pr - 35 - 7 * p7;
    const int r = pr < 4 ? 4 + pr : pr < 36 ? (pr - 4) >> 3 : 4 + p7;
    const int grp = 2 * r + c;
    const int b = g * 16 + grp;
    const uint32_t bar0 = sb + OFF_BAR;
    const uint32_t zero = P.zero;
#define BAR(i) (bar0 + 8u * (i))
#define XBAR(i) (sb + OFF_XB + 64 + 8u * (i))
#define CLUSTER_ARRIVE() asm volatile("barrier.cluster.arrive.relaxed.aligned;" ::: "memory")
#define CLUSTER_WAIT() asm volatile("barrier.cluster.wait.aligned;" ::: "memory")
    if ((sb & 0xffffffu) != SB0) return;

    if (warp == 12) {
        const CUtensorMap* tmD = c ? &tm_dim : &tm_dre;
#define LOAD0(it) do { \
            mbar_expect_tx(BAR(B_FS + DSLOT(it)), SLOT); tma_2d(sb + OFF_S + DSLOT(it) * SLOT, tmD, (it) * 64, r * 128, BAR(B_FS + DSLOT(it))); \
            mbar_expect_tx(BAR(B_FL + (it)), SLOT); tma_2d(sb + OFF_L + (it) * SLOT, &tm_x, (it) * 64, g * 256, BAR(B_FL + (it))); \
            mbar_expect_tx(BAR(B_FL + 4 + (it)), SLOT); tma_2d(sb + OFF_L + (4 + (it)) * SLOT, &tm_x, (it) * 64, g * 256 + 128, BAR(B_FL + 4 + (it))); \
        } while (0)
        if (elect_one()) {
            prefetch_tmap(tmD); prefetch_tmap(&tm_x);
            mbar_init(BAR(B_FS + 2), 1); mbar_init(BAR(B_FL), 1); mbar_init(BAR(B_FL + 4), 1);
            fence_async_smem();
            LOAD0(0);
#pragma unroll
            for (int i = 0; i < B_COUNT; i++)
                if (i != B_FS + 2 && i != B_FL && i != B_FL + 4)
                    mbar_init(BAR(i), (i >= B_ES && i < B_FL) || i == B_GO ? 2 : i == B_STATS || i == B_LST || (i & ~1) == B_OUT ? 4 : 1);
#pragma unroll
            for (int i = 0; i < 12; i++) mbar_init(XBAR(i), 1);
            mbar_expect_tx(BAR(B_RECV), SLOT); mbar_expect_tx(BAR(B_RECV + 1), SLOT);
            mbar_expect_tx(BAR(B_PEER), 1024); mbar_expect_tx(BAR(B_H), 128);
            *reinterpret_cast<volatile uint32_t*>(smem + OFF_SEL + 8) = 0;
            asm volatile("fence.mbarrier_init.release.cluster;" ::: "memory");
            fence_async_smem();
        }
        __syncwarp();
        CLUSTER_ARRIVE();
    } else {
        CLUSTER_ARRIVE();
        if (K0 && tid == 13 * 32) red_max64(sync_words(), tstart);
    }

    if (warp >= 12) {
        asm volatile("setmaxnreg.dec.sync.aligned.u32 %0;" ::"n"(PROD_REGS));
        if (warp != 12) CLUSTER_WAIT();
        if (warp == 12) {
            if (elect_one()) {
                const CUtensorMap* tmD = c ? &tm_dim : &tm_dre;
                if (LDEL) sleep_until((uint32_t)tstart + LDEL);
#define XROWS(k) do { mbar_expect_tx(XBAR(k), 8192); bulk_g2s(sb + OFF_S + (k) * 8192, at(P.x, (b * 16 + (k) * 4) * D_ * 2), 8192, XBAR(k)); } while (0)
                int k = 0;
#pragma unroll 1
                for (int it = 1; it < 16; it++) {
                    if (it < 4) LOAD0(it);
                    else {
                        const int s = DSLOT(it);
                        mbar_wait(BAR(B_ES + s), ((it >> 2) & 1) ^ 1);
                        TRACE(it);
                        mbar_expect_tx(BAR(B_FS + s), SLOT);
                        tma_2d(sb + OFF_S + s * SLOT, tmD, it * 64, r * 128, BAR(B_FS + s));
                    }
                    while (((XS >> (4 * k)) & 15) == it) { XROWS(k); k++; }
                }
                const unsigned ep = load_epoch(b), e8 = ep & 0xffu;
                const uint8_t* abg = at(AB, grp * 32 * SLOT);
                const unsigned long long* fl = at(g_flag, grp * 128);
                unsigned long long rdy = ld_acquire64(fl);
                mbar_wait(BAR(B_SRD), 0);
                st_release8(at(g_flag, grp * 128 + g), e8);
                PROF_T(7);
                int j = 4;
#pragma unroll 1
                for (int cl = 0; cl < 4; cl++) {
                    if (cl) rdy = ld_acquire64(fl + cl);
                    fence_async_global();
#pragma unroll 1
                    for (int n = 1; n < 8; n++, j++) {
                        const int q = (g + n) & 7, s = (j & 1) + ((j & 2) ? 0 : 4);
                        mbar_wait(BAR(B_ES + s), ((j >> 2) ^ (j >> 1)) & 1);
                        if (j == 7) mbar_wait(BAR(B_SRD + 1), 0);
                        if (((unsigned)(rdy >> (8 * q)) & 0xffu) != e8) {
                            int m = 0;
                            do { rdy = ld_acquire64(fl + cl); } while (((unsigned)(rdy >> (8 * q)) & 0xffu) != e8 && ++m < SPIN_LIMIT);
                            fence_async_global();
                        }
                        TRACE(16 + j);
                        mbar_expect_tx(BAR(B_FS + s), SLOT);
                        bulk_g2s(sb + OFF_S + s * SLOT, at(abg, (4 * q + KO(cl)) * SLOT), SLOT, BAR(B_FS + s));
                    }
                }
                *at(g_epoch, b * 4) = ep;
            }
        } else if (warp < 15) {
            if (elect_one()) {
                const int w = warp - 13, row0 = g * 256 + w * 128;
                const CUtensorMap* tmC = c ? &tm_cim : &tm_cre;
                const uint32_t fb = BAR(B_FL + 4 * w), eb = BAR(B_EL + 4 * w), dst = sb + OFF_L + w * 4 * SLOT;
                prefetch_tmap(w ? &tm_out : tmC);
                unsigned long long* sy = sync_words();
#define ADOPT(ph, lag) do { const unsigned long long v = ld_relaxed64(sy++); \
                    if (v - (ph) - SYNCMIN < SYNCCAP) *reinterpret_cast<volatile uint32_t*>(smem + OFF_SEL + 8) = (uint32_t)v - (lag); } while (0)
                if (w == 0 && K0) { sleep_until((uint32_t)tstart + KRD); ADOPT(tstart, 0u - K0); }
                [[maybe_unused]] unsigned long long mk = 0;
                int n = 0, cl = 0;
#pragma unroll 1
                for (int it = 4; it < 48; it++) {
                    const int s = it & 3;
                    mbar_wait(eb + 8 * s, ((it >> 2) & 1) ^ 1);
                    const unsigned long long ph = clock64() - 1024u * (it - 4);
                    TRACE(64 + w * 64 + it - 4);
                    MARK(it, ph);
                    mbar_expect_tx(fb + 8 * s, SLOT);
                    tma_2d(dst + s * SLOT, it < 16 ? &tm_x : tmC, (it < 16 ? it : 4 * ((g + n) & 7) + KO(cl)) * 64, row0, fb + 8 * s);
                    if (it >= 16) {
                        if (it == 19) { n = 1; cl = 0; } else if (it < 19) cl++; else if (++n == 8) { n = 1; cl++; }
                    }
                    if (w == 0) {
                        if (((SYNCS << 4) >> it) & 1) red_max64(sy, ph);
                        if (((SYNCS << (4 + SYNCD)) >> it) & 1) ADOPT(ph, SYNCLAG);
                    }
                }
                {
#pragma unroll 1
                    for (int h = 0; h < 8 / OP; h++) {
                        mbar_wait(BAR((h ? B_STATS : B_OUT) + w), h);
                        fence_async_smem();
                        tma_2d_store(&tm_out, grp * 64, row0 + h * OP * 16, sb + OFF_S + (2 + w) * SLOT + h * OP * 2048);
                        bulk_commit();
                    }
                    FINISH(w);
                }
            }
        } else {
            const unsigned ep = load_epoch(b);
            uint4 f[4];
#define GATHER(ptr, cnt, valid) do { int n = 0; bool ok; do { ok = true; \
                _Pragma("unroll") for (int i = 0; i < (cnt); i++) { f[i] = ld_relaxed128((ptr) + i * 32); ok = ok && (valid); } \
                if (__all_sync(0xffffffffu, ok)) break; \
                __nanosleep(GSL); \
            } while (++n < SPIN_LIMIT); } while (0)
            {
                sleep_until((uint32_t)tstart + 6000);
                const uint4* keys = at(reinterpret_cast<const uint4*>(g_key), lane * 16);
                bool mine = false;
                int n = 0;
                do {
                    f[0] = ld_relaxed128(keys); f[1] = ld_relaxed128(keys + 32);
                    if (__all_sync(0xffffffffu, f[0].y == ep && f[0].w == ep && f[1].y == ep && f[1].w == ep)) break;
                    if (!mine) {
                        mbar_wait(BAR(B_LST), 0);
                        const uint4 k = *reinterpret_cast<const uint4*>(smem + OFF_XB);
                        if (lane == 0) st_relaxed64(at(g_key, b * 8), ((unsigned long long)ep << 32) | max(max(k.x, k.y), max(k.z, k.w)));
                        mine = true;
                    }
                    __nanosleep(GSL);
                } while (++n < SPIN_LIMIT);
                const unsigned key = __reduce_max_sync(0xffffffffu, max(max(f[0].x, f[0].z), max(f[1].x, f[1].z)));
                if (lane == 0) { *reinterpret_cast<unsigned*>(smem + OFF_SEL) = key; mbar_arrive(BAR(B_SEL)); PROF_T(8); }
            }
            if (elect_one()) {
#pragma unroll 1
                for (int cl = 0; cl < 4; cl++) {
                    uint8_t* dst = at(AB, (grp * 32 + 4 * g + KO(cl)) * SLOT);
                    const uint32_t src = sb + OFF_S + cl * SLOT, chunk = cl ? 4096 : SLOT;
                    mbar_wait(BAR(B_FS + cl), 0);
                    if (cl == 0) PROF_T(3);
                    uint32_t t0 = clock32() + (cl == 1 ? PDEL : 0);
#pragma unroll 1
                    for (uint32_t o = 0; o < SLOT; o += chunk) {
                        sleep_until(t0);
                        bulk_s2g(dst + o, src + o, chunk);
                        bulk_commit();
                        t0 += PGAP;
                    }
                    bulk_wait<0>();
                    TRACE(252 + cl);
                    if (cl < 2) mbar_arrive(BAR(B_SRD + cl));
                    else {
                        mbar_wait(BAR(B_ES + cl), 0);
                        mbar_expect_tx(BAR(B_FS + cl), SLOT);
                        tma_2d(src, &tm_x, grp * 64, g * 256 + (cl - 2) * 128, BAR(B_FS + cl));
                    }
                    if (cl) st_release8(at(g_flag, grp * 128 + cl * 8 + g), ep & 0xffu);
                    if (cl == 1) PROF_T(5);
                    if (cl == 3) PROF_T(4);
                }
            }
        }
    } else if (warp >= 8) {
        asm volatile("setmaxnreg.dec.sync.aligned.u32 %0;" ::"n"(512 - PROD_REGS - 2 * CONS_REGS));
        const int aw = warp - 8, mt = tid - 256;
        unsigned ep;
        {
            const uint8_t* rp = smem + OFF_S + aw * 2048 + lane * 16;
            const __nv_bfloat16* dp = at(c ? P.dim : P.dre, (r * 128 + g * 16 + aw * 4) * D_ * 2);
            float wf[32], sw = 0.f;
#pragma unroll
            for (int i = 0; i < 4; i++) {
                const uint4 w = __ldg(reinterpret_cast<const uint4*>(at(P.wr, lane * 16) + i * 256));
                const uint32_t wv[4] = {w.x, w.y, w.z, w.w};
#pragma unroll
                for (int e = 0; e < 4; e++) { wf[8 * i + 2 * e] = bf_lo(wv[e]); wf[8 * i + 2 * e + 1] = bf_hi(wv[e]); sw = (sw + bf_lo(wv[e])) + bf_hi(wv[e]); }
            }
            ep = load_epoch(b);
            CLUSTER_WAIT();
            float x0[4] = {}, s1[4] = {}, s2[4] = {}, sx[4] = {}, sd[4] = {};
#define PUSH(a, v) do { a[0] = a[1]; a[1] = a[2]; a[2] = a[3]; a[3] = v; } while (0)
#pragma unroll 1
            for (int k = 0; k < 4; k++) {
                mbar_wait(XBAR(k), 0);
                uint4 v[4];
#pragma unroll
                for (int i = 0; i < 4; i++) v[i] = *reinterpret_cast<const uint4*>(rp + k * 8192 + i * 512);
                float sh = bf_lo(v[0].x), a1s = 0.f, a2s = 0.f, axs = 0.f;
#pragma unroll
                for (int i = 0; i < 4; i++) {
                    sh = __shfl_sync(0xffffffffu, sh, 0);
                    const uint32_t xv[4] = {v[i].x, v[i].y, v[i].z, v[i].w};
#pragma unroll
                    for (int e = 0; e < 4; e++) {
                        const float a0 = bf_lo(xv[e]) - sh, a1 = bf_hi(xv[e]) - sh;
                        a1s += a0 + a1;
                        a2s = fmaf(a0, a0, fmaf(a1, a1, a2s));
                        axs = fmaf(a0, wf[8 * i + 2 * e], fmaf(a1, wf[8 * i + 2 * e + 1], axs));
                    }
                    if (i < 3) yield(axs, zero);
                }
                PUSH(x0, sh); PUSH(s1, a1s); PUSH(s2, a2s); PUSH(sx, axs);
                fence_async_smem();
                __syncwarp();
                if (elect_one()) {
                    const uint32_t db = XBAR(k == 3 ? 8 + aw : 4 + aw);
                    if (k == 0 || k == 3) mbar_expect_tx(db, k ? 2048 : 6144);
                    bulk_g2s(sb + OFF_S + k * 8192 + aw * 2048, dp + k * D_, 2048, db);
                }
            }
#define FOLD4(a) do { const bool u16 = lane & 16, u8 = lane & 8; \
                float p0 = (u16 ? a[2] : a[0]) + __shfl_xor_sync(0xffffffffu, u16 ? a[0] : a[2], 16); \
                float p1 = (u16 ? a[3] : a[1]) + __shfl_xor_sync(0xffffffffu, u16 ? a[1] : a[3], 16); \
                a[0] = (u8 ? p1 : p0) + __shfl_xor_sync(0xffffffffu, u8 ? p0 : p1, 8); \
                _Pragma("unroll") for (int o = 4; o; o >>= 1) a[0] += __shfl_xor_sync(0xffffffffu, a[0], o); } while (0)
            FOLD4(s1); FOLD4(s2); FOLD4(sx);
            sw = warp_sum(sw);
            const int rr = lane >> 3;
            const float c0 = rr == 0 ? x0[0] : rr == 1 ? x0[1] : rr == 2 ? x0[2] : x0[3];
            const float dm = s1[0] * (1.0f / D_);
            const float mb = rbf(c0 + dm);
            const float rinv = rcp_f(rbf(sqrt_f(rbf(rbf(fmaxf(s2[0] * (1.0f / D_) - dm * dm, 0.f)) + 1e-5f))));
            unsigned u = __bfloat16_as_ushort(__float2bfloat16_rn((sx[0] + (c0 - mb) * sw) * rinv));
            u = (u & 0x8000u) ? (~u & 0xffffu) : (u | 0x8000u);
            u = (u << 16) | (0xffffu - (unsigned)(b * 16 + rr * 4 + aw));
            const uint4 rec = make_uint4(__float_as_uint(mb), __float_as_uint(rinv), ep, u);
            if ((lane & 7) == 0) st_relaxed128(at(g_stat, (b * 16 + aw * 4 + rr) * 16), rec);
            u = __reduce_max_sync(0xffffffffu, u);
            if (lane == 0) { *reinterpret_cast<unsigned*>(smem + OFF_XB + aw * 4) = u; mbar_arrive(BAR(B_LST)); }
            if (mt == 0) PROF_T(2);
#pragma unroll 1
            for (int k = 0; k < 4; k++) {
                mbar_wait(XBAR(k == 3 ? 8 + aw : 4 + aw), 0);
                float run = 0.f;
#pragma unroll
                for (int i = 0; i < 4; i++) {
                    const uint4 v = *reinterpret_cast<const uint4*>(rp + k * 8192 + i * 512);
                    const uint32_t dv[4] = {v.x, v.y, v.z, v.w};
#pragma unroll
                    for (int e = 0; e < 4; e++) run += bf_lo(dv[e]) + bf_hi(dv[e]);
                }
                PUSH(sd, run);
            }
            FOLD4(sd);
            const float nb = __shfl_down_sync(0xffffffffu, sd[0], 8);
            if ((lane & 15) == 0)
                st_relaxed128(at(g_rs, (grp * 64 + g * 8 + aw * 2 + (lane >> 4)) * 16), make_uint4(__float_as_uint(sd[0]), ep, __float_as_uint(nb), ep));
            if (mt == 0) PROF_T(6);
            named_bar<4, 128>();
            if (mt < 12) asm volatile("mbarrier.inval.shared::cta.b64 [%0];" ::"r"(XBAR(mt)) : "memory");
            uint4 f[4];
            if (aw < 2) {
                const int t = SREC(aw * 128 + lane);
                GATHER(at(g_stat, (g * 256 + aw * 128 + lane) * 16), 4, f[i].z == ep);
#pragma unroll
                for (int i = 0; i < 4; i++) {
                    *reinterpret_cast<uint32_t*>(smem + OFF_RSTD + (POS(t) + i * 32) * 4) = f[i].y;
                    *reinterpret_cast<uint16_t*>(smem + OFF_MEAN + (POS(t) + i * 32) * 2) = (uint16_t)(f[i].x >> 16);
                }
            } else {
                const int e2 = (aw - 2) * 32 + lane;
                GATHER(at(g_rs, (grp * 64 + e2) * 16), 1, f[i].y == ep && f[i].w == ep);
#pragma unroll
                for (int i = 0; i < 2; i++) {
                    const float v = __uint_as_float(i ? f[0].z : f[0].x);
                    const float hi = rbf(v), mid = rbf(v - hi), lo = v - hi - mid;
                    *reinterpret_cast<uint4*>(smem + OFF_RS + (e2 * 2 + i) * 16) = make_uint4(pack_bf(hi, mid), pack_bf(lo, 0.f), 0, 0);
                }
            }
            fence_async_smem();
            __syncwarp();
            if (lane == 0) mbar_arrive(BAR(B_STATS));
            if (mt == 127) PROF_T(9);
        }
        const int pair = g * 7 + r;
        if (r < 7) {
            const uint64_t pol = policy_evict_first();
            const __nv_bfloat16* wp = at((aw & 1) ? P.wu : P.wg, ((c * 512 + (aw >> 1) * 256 + (lane >> 3) * 8) * F_ + pair * 64 + (lane & 7) * 8) * 2);
            uint4 b0[8], b1[8];
#define FILL(buf, str) do { _Pragma("unroll") for (int q = 0; q < 8; q++) buf[q] = ldg_stream(wp + q * (str), pol); } while (0)
            FILL(b0, F_);
            mbar_wait(BAR(B_SEL), 0);
            uint4 xn;
            {
                const int sel = 0xffff - (int)(*reinterpret_cast<volatile unsigned*>(smem + OFF_SEL) & 0xffffu);
                xn = __ldg(reinterpret_cast<const uint4*>(at(P.x, (sel * D_ + c * 512 + (aw >> 1) * 256 + (lane & 7) * 32 + (lane >> 3) * 8) * 2)));
                uint4 f[1];
                GATHER(at(g_stat, SREC(sel) * 16), 1, f[i].z == ep);
                const float m = __uint_as_float(f[0].x), ri = __uint_as_float(f[0].y);
                xn = make_uint4(norm2(xn.x, m, ri), norm2(xn.y, m, ri), norm2(xn.z, m, ri), norm2(xn.w, m, ri));
            }
            float ag[8];
#pragma unroll
            for (int i = 0; i < 8; i++) ag[i] = 0.f;
            const uint32_t stag = (aw * 4 + (grp & 3)) * ESTAG;
            uint32_t te = clock32() + stag;
            bool paused = !QUIET;
#define ROUND(cur, nxt, rd) do { \
                if (!paused && mbar_test(BAR(B_QUIET), 0)) { mbar_wait_sleep(BAR(B_GO), 0); te = clock32() + stag; paused = true; } \
                sleep_until(te); \
                te = clock32() + (paused ? EGAP2 : EGAP1); \
                if (lane == 0) TRACE(192 + aw * 12 + (rd)); \
                if ((rd) == 7) wp = at(P.wd - 16 * D_, ((pair * 64 + (lane >> 4) * 8) * D_ + c * 512 + aw * 128 + (lane & 15) * 8) * 2); \
                wp = at(wp, ((rd) < 7 ? 64 * F_ : 32 * D_) + (cur[7].x & zero)); \
                if ((rd) < 7) FILL(nxt, F_); else if ((rd) != 8 && (rd) < 11) FILL(nxt, D_); \
                _Pragma("unroll") for (int q = 0; q < 8; q += 2) { \
                    uint32_t xw = __shfl_sync(0xffffffffu, q == 0 ? xn.x : q == 2 ? xn.y : q == 4 ? xn.z : xn.w, (lane & 24) | ((rd) & 7)); \
                    fma8(ag, cur[q], bf_lo(xw)); \
                    if (YLD > 1) { yield(ag[7], zero); xw = __shfl_sync(0xffffffffu, xw, lane); } \
                    fma8(ag, cur[q + 1], bf_hi(xw)); \
                    if (q < 6) yield(ag[7], zero); \
                } } while (0)
#pragma unroll 1
            for (int rd = 0; rd < 12; rd += 2) {
                ROUND(b0, b1, rd);
                ROUND(b1, b0, rd + 1);
                if (rd == 6) { wp += 16 * D_; FILL(b1, D_); wp -= 16 * D_; }
                if (rd == 6 || rd == 10) {
#pragma unroll
                    for (int i = 0; i < 8; i++) ag[i] += __shfl_xor_sync(0xffffffffu, ag[i], 16);
                }
                if (rd == 6) {
#pragma unroll
                    for (int i = 0; i < 8; i++) ag[i] += __shfl_xor_sync(0xffffffffu, ag[i], 8);
                    if (lane < 8) {
                        const uint32_t dst = mapa(sb + OFF_XB + (c * 4 + aw) * 128 + (lane & 3) * 32, lane >> 2), pb = mapa(BAR(B_PEER), lane >> 2);
                        st_async4(dst, __float_as_uint(ag[0]), __float_as_uint(ag[1]), __float_as_uint(ag[2]), __float_as_uint(ag[3]), pb);
                        st_async4(dst + 16, __float_as_uint(ag[4]), __float_as_uint(ag[5]), __float_as_uint(ag[6]), __float_as_uint(ag[7]), pb);
                    }
                    if (aw == 3) {
                        mbar_wait_cluster(BAR(B_PEER), 0);
                        const float* ps = reinterpret_cast<const float*>(smem + OFF_XB) + lane;
                        const float go = (ps[0] + ps[64]) + (ps[128] + ps[192]), uo = (ps[32] + ps[96]) + (ps[160] + ps[224]);
                        const float h = rbf(silu_f(rbf(go))) * rbf(uo), ho = __shfl_xor_sync(0xffffffffu, h, 1);
                        asm volatile("st.async.weak.shared::cluster.mbarrier::complete_tx::bytes.b32 [%0], %1, [%2];"
                                     ::"r"(mapa(sb + OFF_H + c * 64 + (lane >> 1) * 4, lane & 1)), "r"((lane & 1) ? pack_bf(ho, h) : pack_bf(h, ho)),
                                       "r"(mapa(BAR(B_H), lane & 1)) : "memory");
                    }
                    mbar_wait_cluster(BAR(B_H), 0);
                    xn = *reinterpret_cast<const uint4*>(smem + OFF_H + (lane & 3) * 32 + (lane >> 4) * 16);
#pragma unroll
                    for (int i = 0; i < 8; i++) ag[i] = 0.f;
                    if (mt == 0) PROF_T(10);
                }
            }
            const int hi = lane >> 4;
            st_relaxed128(at(g_part, pair * 4096 + (c * 8 + aw * 2 + ((lane >> 3) & 1)) * 256 + hi * 128 + (lane & 7) * 16),
                          make_uint4((__float_as_uint(hi ? ag[4] : ag[0]) & ~15u) | (ep & 15u), __float_as_uint(hi ? ag[5] : ag[1]),
                                     __float_as_uint(hi ? ag[6] : ag[2]), __float_as_uint(hi ? ag[7] : ag[3])));
            if (mt == 0) PROF_T(11);
        } else {
            mbar_wait_sleep(BAR(B_SEL), 0);
        }
        const int sel = 0xffff - (int)(*reinterpret_cast<volatile unsigned*>(smem + OFF_SEL) & 0xffffu);
        if ((sel >> 8) == g) {
            const int col = (lane & 7) * 8 + ((lane >> 3) & 1) * 4;
            const uint2 xv = __ldg(reinterpret_cast<const uint2*>(at(P.x, (sel * D_ + grp * 64 + col) * 2)));
            uint4 f[1];
            GATHER(at(g_stat, SREC(sel) * 16), 1, f[i].z == ep);
            const uint4 rec = f[0];
            const uint4* src = at(g_part, (aw * 14 + (lane >> 4)) * 4096 + grp * 256 + (lane & 15) * 16);
            if (r == 7) {
                int n = 0;
                while (((ld_relaxed(src) ^ ep) & 15u) != 0 && ++n < SPIN_LIMIT) __nanosleep(500);
            }
            uint4 t[7];
            int n = 0;
            bool ok;
            do {
                ok = true;
#pragma unroll
                for (int u = 0; u < 7; u++) { t[u] = ld_relaxed128(src + u * 512); ok = ok && ((t[u].x ^ ep) & 15u) == 0; }
            } while (!__all_sync(0xffffffffu, ok) && ++n < SPIN_LIMIT);
            float4 a = make_float4(0.f, 0.f, 0.f, 0.f);
#pragma unroll
            for (int u = 0; u < 7; u++) {
                a.x += __uint_as_float(t[u].x & ~15u); a.y += __uint_as_float(t[u].y); a.z += __uint_as_float(t[u].z); a.w += __uint_as_float(t[u].w);
            }
            a.x += __shfl_xor_sync(0xffffffffu, a.x, 16); a.y += __shfl_xor_sync(0xffffffffu, a.y, 16);
            a.z += __shfl_xor_sync(0xffffffffu, a.z, 16); a.w += __shfl_xor_sync(0xffffffffu, a.w, 16);
            float4* park = reinterpret_cast<float4*>(smem + OFF_XB) + (lane & 15);
            if (lane < 16) park[aw * 16] = a;
            named_bar<4, 128>();
            if (aw == 0) {
                const float4 p1 = park[16], p2 = park[32], p3 = park[48];
                a.x = (a.x + p1.x) + (p2.x + p3.x); a.y = (a.y + p1.y) + (p2.y + p3.y);
                a.z = (a.z + p1.z) + (p2.z + p3.z); a.w = (a.w + p1.w) + (p2.w + p3.w);
                unsigned u = rec.w >> 16;
                u = (u & 0x8000u) ? (u & 0x7fffu) : (~u & 0xffffu);
                const float sg = rbf(__fdividef(1.0f, 1.0f + __expf(-__uint_as_float(u << 16))));
                const float m = __uint_as_float(rec.x), ri = __uint_as_float(rec.y);
                const uint32_t n0 = norm2(xv.x, m, ri), n1 = norm2(xv.y, m, ri);
                uint2 o;
                o.x = silu2(pack_bf(bf_lo(n0) + rbf(rbf(a.x) * sg), bf_hi(n0) + rbf(rbf(a.y) * sg)));
                o.y = silu2(pack_bf(bf_lo(n1) + rbf(rbf(a.z) * sg), bf_hi(n1) + rbf(rbf(a.w) * sg)));
                if (lane < 16) *reinterpret_cast<uint2*>(smem + OFF_H + col * 2) = o;
                __syncwarp();
                if (lane == 0) { mbar_arrive(BAR(B_UPD)); PROF_T(12); }
            }
        }
    } else {
        asm volatile("setmaxnreg.inc.sync.aligned.u32 %0;" ::"n"(CONS_REGS));
        CLUSTER_WAIT();
        const int wg = warp >> 2, wq = warp & 3;
        const int wt = tid & 127;
        float acc[128];
        const uint32_t fL = BAR(B_FL + 4 * wg), eL = BAR(B_EL + 4 * wg);
        const uint32_t dL = desc_lo(SB0 + OFF_L, 16) + wg * 4096;
        constexpr uint32_t dS = desc_lo(SB0 + OFF_S, 16);
        constexpr uint32_t SL = SLOT >> 4;
#define RELEASE(ls, ss) do { if (wt == 0) { mbar_arrive(eL + 8u * (ls)); mbar_arrive(BAR(B_ES + (ss))); } } while (0)
#define WAIT_FULL(ls, lph, ss, sph) do { mbar_wait(BAR(B_FS + (ss)), sph); mbar_wait(fL + 8u * (ls), lph); } while (0)
#define TURN() do { if (wg) named_bar<6, 256>(); else named_bar<5, 256>(); } while (0)
#define PASS() do { if (wg) named_arrive<5, 256>(); else named_arrive<6, 256>(); } while (0)
#define WG_BAR() do { if (wg) named_bar<2, 128>(); else named_bar<1, 128>(); } while (0)
        uint32_t held = 0, tgt = 0;
#define PEEK() do { if (wg == 0) tgt = *reinterpret_cast<volatile uint32_t*>(smem + OFF_SEL + 8); } while (0)
#define HOLD(step) do { if (tgt != held) { held = tgt; sleep_until(tgt + 1024u * (step) - 100u); \
                int n = 0; while ((int)(clock32() - tgt - 1024u * (step)) < 0 && ++n < SPIN_LIMIT) {} } } while (0)
        if (wg == 1) PASS();

#define MMA1_P(O, s, first, pass) do { _Pragma("unroll") for (int kk = 0; kk < 4; kk++) { if (kk == PK && (pass)) PASS(); \
            wgmma128<O, 0>(acc, dL + (s) * SL + kk * 2 + (O) * 8, dS + DSLOT(s) * SL + kk * 2, !((first) && kk == 0)); } \
            if (PK == 4 && (pass)) PASS(); } while (0)
#define MMA1_H(O, s, first) MMA1_P(O, s, first, false)
#define WAIT1(s, ph) WAIT_FULL(s, ph, DSLOT(s), ph)
#define PROBE(ls, lph, ss, sph) (mbar_test(BAR(B_FS + (ss)), sph) & mbar_test(fL + 8u * (ls), lph))
#define REL1(s) RELEASE(s, DSLOT(s))
#pragma unroll 1
        for (int it = 0; it < 12; it++) {
            const int s = it & 3;
            const bool ok = PROBE(s, (it >> 2) & 1, DSLOT(s), (it >> 2) & 1);
            PEEK();
            if (it) { wg_wait<0>(); REL1((it - 1) & 3); }
            if (!ok) WAIT1(s, (it >> 2) & 1);
            HOLD(it);
            TURN();
            wg_fence(); MMA1_H(0, s, it == 0); MMA1_P(64, s, it == 0, true); wg_commit();
            if (it == QJ && tid == 0) { mbar_arrive(BAR(B_QUIET)); PROF_T(15); }
            if (it == 0 && tid == 0) PROF_T(16);
        }
        TS(12);
        WAIT1(0, 1);
        TS(13);
        wg_wait<0>(); REL1(3);
        TS(14);
        TURN();
        wg_fence();
        MMA1_H(0, 0, false);
        if (QJ == 12 && tid == 0) { mbar_arrive(BAR(B_QUIET)); PROF_T(15); }
        WAIT1(1, 1); wg_fence(); MMA1_H(0, 1, false);
        WAIT1(2, 1); wg_fence(); MMA1_H(0, 2, false); wg_commit();
        mbar_wait(BAR(B_STATS), 0);
        float rs[4];
        uint32_t nm[8];
        {
            const int p0 = POS(wg * 128 + wq * 16 + (lane >> 2));
            const uint32_t msk = (lane & 3) == 0 ? 0xffffffffu : (lane & 3) == 1 ? 0x0000ffffu : 0u;
#pragma unroll
            for (int i = 0; i < 4; i++) {
                const int p = p0 + (i & 1) * 2 + (i >> 1) * 64;
                rs[i] = *reinterpret_cast<const float*>(smem + OFF_RSTD + p * 4);
                const uint32_t m = *reinterpret_cast<const uint16_t*>(smem + OFF_MEAN + p * 2) ^ 0x8000u;
                nm[i + (i & 2)] = (m | (m << 16)) & msk;
                nm[i + (i & 2) + 2] = 0;
            }
            asm volatile("" : "+r"(nm[0]), "+r"(nm[1]), "+r"(nm[2]), "+r"(nm[3]), "+r"(nm[4]), "+r"(nm[5]), "+r"(nm[6]), "+r"(nm[7])::"memory");
        }
        wg_fence();
        wgmma128_rs<64>(acc, nm + 4, (SB0 + OFF_RS) >> 4);
        wgmma128_rs<0>(acc, nm, (SB0 + OFF_RS) >> 4);
        WAIT1(3, 1); wg_fence(); MMA1_P(0, 3, false, true);
        wg_commit();
        const int mrow = wq * 16 + ((lane >> 3) & 1) * 8 + (lane & 7);
#define EPI1(O, slot, FREE) do { const uint32_t dst = sb + OFF_S + (slot) * SLOT + mrow * 128; \
            uint32_t pk[32]; \
            _Pragma("unroll") for (int i = 0; i < 32; i += 4) { \
                _Pragma("unroll") for (int k = 0; k < 4; k++) \
                    pk[i + k] = pack_bf(acc[(O) + 2 * (i + k)] * rs[(O) / 32 + (k & 1)], acc[(O) + 2 * (i + k) + 1] * rs[(O) / 32 + (k & 1)]); \
                if (i == EF) { FREE; } \
                if (i >= EF) { _Pragma("unroll") for (int v = (i == EF ? 0 : i); v <= i; v += 4) \
                    stmatrix4(dst + ((v >> 4) ^ c ^ 1) * 8192 + ((((v >> 1) & 7) + (lane >> 4)) ^ (lane & 7)) * 16, pk[v], pk[v + 1], pk[v + 2], pk[v + 3]); } } \
            fence_async_smem(); WG_BAR(); \
            if (wt == 0) mbar_arrive(BAR(B_FS + (slot))); } while (0)
        TS(15);
        wg_wait<0>();
        fence_regs64<0>(acc);
        TS(16);
        {
            constexpr int EF = 0;
            EPI1(0, wg, if (wg) mbar_wait(BAR(B_FS), 0));
        }
        TS(17);
        TURN();
        wg_fence();
        MMA1_H(64, 0, false); wg_commit();
        MMA1_H(64, 1, false); wg_commit();
        MMA1_H(64, 2, false); wg_commit();
        wg_wait<2>(); REL1(0);
        MMA1_P(64, 3, false, true); wg_commit();
        TS(18);
        wg_wait<2>(); REL1(1);
        wg_wait<1>(); REL1(2);
        wg_wait<0>(); REL1(3);
        fence_regs64<64>(acc);
        TS(19);
        {
            constexpr int EF = 12;
            EPI1(64, 2 + wg, mbar_wait(BAR(B_ES + 2 + wg), 1));
        }
        TS(20);

        float ac2[128];
#define MMA2_P(O, ls, ss, first, pass) do { _Pragma("unroll") for (int kk = 0; kk < 4; kk++) { if (kk == PK && (pass)) PASS(); \
            wgmma128<O, 1>(ac2, dS + (ss) * SL + kk * 128 + (O) * 8, dL + (ls) * SL + kk * 2, !((first) && kk == 0)); } \
            if (PK == 4 && (pass)) PASS(); } while (0)
#define MMA2_H(O, ls, ss, first) MMA2_P(O, ls, ss, first, false)
#define WAIT2(j) WAIT_FULL((j) & 3, ((j) >> 2) & 1, PSLOT(j), PPAR(j))
#define MMA2(j, pass) do { wg_fence(); MMA2_H(0, (j) & 3, PSLOT(j), (j) == 0); MMA2_P(64, (j) & 3, PSLOT(j), (j) == 0, pass); wg_commit(); } while (0)
#define REL2(j) RELEASE((j) & 3, PSLOT(j))
        if (GOJ == 0 && wt == 0) mbar_arrive(BAR(B_GO));
        WAIT2(0); TURN(); MMA2(0, false);
        WAIT2(1); MMA2(1, true);
        TS(21);
        wg_wait<1>(); REL2(0);
        TS(22);
        {
            uint32_t sp = 1;
#pragma unroll 1
            for (int j = 2; j < XJ; j++) {
                const uint32_t ss = PSLOT(j);
                const bool ok = PROBE(j & 3, (j >> 2) & 1, ss, PPAR(j));
                PEEK();
                wg_wait<0>(); RELEASE((j - 1) & 3, sp);
                if (!ok) WAIT_FULL(j & 3, (j >> 2) & 1, ss, PPAR(j));
                HOLD(16 + j);
                TURN();
                wg_fence(); MMA2_H(0, j & 3, ss, false); MMA2_P(64, j & 3, ss, false, true); wg_commit();
                if (j == GOJ && wt == 0) { mbar_arrive(BAR(B_GO)); if (wg == 0) PROF_T(19); }
                sp = ss;
            }
        }
        if (tid == 0) PROF_T(20);
        uint32_t gt[32];
        const uint32_t xrow = sb + OFF_S + (2 + wg) * SLOT + ((lane >> 4) * 8 + (lane & 7)) * 128 + (((2 * wq + ((lane >> 3) & 1)) ^ (lane & 7)) << 4);
        const uint32_t gsign = c ? 0x80008000u : 0u;
        mbar_wait(BAR(B_FS + 2 + wg), 1);
        mbar_wait(BAR(B_SEL), 0);
        const int sel = 0xffff - (int)(*reinterpret_cast<volatile unsigned*>(smem + OFF_SEL) & 0xffffu);
        bool own = (sel >> 7) == 2 * g + wg;
#define PATCH() do { own = false; \
            const uint32_t v0 = *reinterpret_cast<const uint16_t*>(smem + OFF_H + (wq * 16 + (lane >> 2)) * 2) ^ gsign; \
            const uint32_t v1 = *reinterpret_cast<const uint16_t*>(smem + OFF_H + (wq * 16 + (lane >> 2)) * 2 + 16) ^ gsign; \
            const uint32_t pick = (lane & 3) != ((sel >> 1) & 3) ? 0x3210u : (sel & 1) ? 0x5410u : 0x3254u; \
            _Pragma("unroll") for (int i = 0; i < 16; i++) { \
                const uint32_t m = ((sel >> 3) & 15) == i ? pick : 0x3210u; \
                gt[2 * i] = __byte_perm(gt[2 * i], v0, m); \
                gt[2 * i + 1] = __byte_perm(gt[2 * i + 1], v1, m); \
            } } while (0)
#pragma unroll
        for (int v = 0; v < 28 - XJ; v++) {
            WAIT2(XJ + v); wg_wait<0>(); REL2(XJ + v - 1); TURN(); MMA2(XJ + v, true);
            constexpr int NS = 8 / (28 - XJ);
#pragma unroll
            for (int u = v * NS; u < (v + 1) * NS; u++) {
                uint32_t* o = &gt[4 * u];
                ldmatrix4t(xrow + u * 2048, o[0], o[1], o[2], o[3]);
                const float4 r4 = *reinterpret_cast<const float4*>(smem + OFF_RSTD + (wg * 128 + u * 16 + (lane & 3) * 4) * 4);
                const uint2 m2 = *reinterpret_cast<const uint2*>(smem + OFF_MEAN + (wg * 128 + u * 16 + (lane & 3) * 4) * 2);
                o[0] = gate2(o[0], m2.x, r4.x, r4.y) ^ gsign;
                o[1] = gate2(o[1], m2.x, r4.x, r4.y) ^ gsign;
                o[2] = gate2(o[2], m2.y, r4.z, r4.w) ^ gsign;
                o[3] = gate2(o[3], m2.y, r4.z, r4.w) ^ gsign;
                asm volatile("st.shared.v2.u32 [%0], {%1,%2};" ::"r"(sb + OFF_SEL + 16), "r"(o[0] ^ o[1]), "r"(o[2] ^ o[3]) : "memory");
            }
        }
        if (tid == 0) PROF_T(21);
        WAIT2(28);
        wg_wait<0>(); REL2(27);
        if (own && mbar_test(BAR(B_UPD), 0)) PATCH();
        TS(0);
        TURN();
        wg_fence(); MMA2_H(0, 0, PSLOT(28), false); wg_commit();
        if (wg == 0 || !ASYM) { wg_fence(); MMA2_H(64, 0, PSLOT(28), false); wg_commit(); }
        WAIT2(29); wg_fence(); MMA2_H(0, 1, PSLOT(29), false); wg_commit();
        WAIT2(30); wg_fence(); MMA2_H(0, 2, PSLOT(30), false); wg_commit();
        wg_wait<2>();
        if (tid == 0) mbar_arrive_cluster(mapa(BAR(B_RDY), c ^ 1));
        WAIT2(31); wg_fence(); MMA2_H(0, 3, PSLOT(31), false); wg_commit();
        TS(1);
#define KEEP(i) wgmma128<64, 1>(ac2, dS + PSLOT(29 + ((i) >> 2)) * SL + ((i) & 3) * 128 + 512, dL + (1 + ((i) >> 2)) * SL + ((i) & 3) * 2, 1)
        wg_fence();
#pragma unroll
        for (int i = 0; i < KQ; i++) KEEP(i);
        wg_commit();
        mbar_wait(BAR(B_RDY + wg), 0);
        wg_wait<1>();
        fence_regs64<0>(ac2);
        TS(2);
        wg_fence();
        {
            const uint32_t dst = mapa(sb + OFF_L + wg * SLOT + wt * 16, c ^ 1), rb = mapa(BAR(B_RECV + wg), c ^ 1);
#pragma unroll
            for (int v = 0; v < 8; v++) {
                if (KQ + v < 12) KEEP(KQ + v);
                if (KQ + v == 11) { wg_commit(); if (wg == 0) PASS(); }
                st_async4(dst + v * 2048, pack_bf(ac2[8 * v + 0], ac2[8 * v + 1]), pack_bf(ac2[8 * v + 2], ac2[8 * v + 3]),
                          pack_bf(ac2[8 * v + 4], ac2[8 * v + 5]), pack_bf(ac2[8 * v + 6], ac2[8 * v + 7]), rb);
            }
        }
        if (wg == 1 && ASYM) { wg_fence(); MMA2_H(64, 0, PSLOT(28), false); wg_commit(); }
        TS(3);
        uint32_t xr[32];
#pragma unroll
        for (int v = 0; v < 8; v++) ldmatrix4t(xrow + v * 2048, xr[4 * v], xr[4 * v + 1], xr[4 * v + 2], xr[4 * v + 3]);
        if (wg == 0) {
            wg_wait<0>();
            if (wt == 0) mbar_arrive_cluster(mapa(BAR(B_RDY + 1), c ^ 1));
        }
        TS(4);
        if (own) { mbar_wait(BAR(B_UPD), 0); PATCH(); }
        TS(5);
        mbar_wait_cluster(BAR(B_RECV + wg), 0);
        TS(6);
        uint4 rv[8];
#pragma unroll
        for (int v = 0; v < 8; v++) rv[v] = *reinterpret_cast<const uint4*>(smem + OFF_L + wg * SLOT + v * 2048 + wt * 16);
        wg_wait<0>();
        fence_regs64<64>(ac2);
        TS(7);
#pragma unroll
        for (int v = 0; v < 8; v++) {
            const float* a = &ac2[64 + 8 * v];
            stmatrix4t(xrow + v * 2048,
                       bfma2(bsub2(pack_bf(a[0], a[1]), rv[v].x), gt[4 * v + 0], xr[4 * v + 0]),
                       bfma2(bsub2(pack_bf(a[2], a[3]), rv[v].y), gt[4 * v + 1], xr[4 * v + 1]),
                       bfma2(bsub2(pack_bf(a[4], a[5]), rv[v].z), gt[4 * v + 2], xr[4 * v + 2]),
                       bfma2(bsub2(pack_bf(a[6], a[7]), rv[v].w), gt[4 * v + 3], xr[4 * v + 3]));
            if (v % OP == OP - 1) {
                __syncwarp();
                if (lane == 0) mbar_arrive(BAR((v / OP ? B_STATS : B_OUT) + wg));
                if (v == OP - 1) TS(8);
                if (v == 7) TS(9);
            }
        }
    }
}

typedef CUresult (*EncodeFn)(CUtensorMap*, CUtensorMapDataType, cuuint32_t, void*, const cuuint64_t*, const cuuint64_t*,
                             const cuuint32_t*, const cuuint32_t*, CUtensorMapInterleave, CUtensorMapSwizzle,
                             CUtensorMapL2promotion, CUtensorMapFloatOOBfill);

void make_map(EncodeFn fn, CUtensorMap* tm, const void* p, uint64_t rows, uint64_t cols, uint32_t box_rows,
              CUtensorMapL2promotion promo = CU_TENSOR_MAP_L2_PROMOTION_L2_128B) {
    cuuint64_t dims[2] = {cols, rows};
    cuuint64_t strides[1] = {cols * 2};
    cuuint32_t box[2] = {64, box_rows};
    cuuint32_t es[2] = {1, 1};
    fn(tm, CU_TENSOR_MAP_DATA_TYPE_BFLOAT16, 2, const_cast<void*>(p), dims, strides, box, es, CU_TENSOR_MAP_INTERLEAVE_NONE,
       CU_TENSOR_MAP_SWIZZLE_128B, promo, CU_TENSOR_MAP_FLOAT_OOB_FILL_NONE);
}

}

extern "C" void kernel_launch(void* const* d_in, const int* in_sizes, int n_in, void* d_out, int out_size) {
    (void)in_sizes; (void)n_in; (void)out_size;
    static EncodeFn fn = nullptr;
    if (!fn) {
        void* p = nullptr;
        cudaDriverEntryPointQueryResult q;
        cudaGetDriverEntryPoint("cuTensorMapEncodeTiled", &p, cudaEnableDefault, &q);
        fn = (EncodeFn)p;
        cudaFuncSetAttribute(fnet_fused_kernel, cudaFuncAttributeMaxDynamicSharedMemorySize, SMEM_BYTES);
    }
    CUtensorMap tx, tdre, tdim, tcre, tcim, tout;
    make_map(fn, &tx, d_in[0], S_, D_, 128, PRX);
    make_map(fn, &tcre, d_in[1], S_, S_, 128, PRC);
    make_map(fn, &tcim, d_in[2], S_, S_, 128, PRC);
    make_map(fn, &tdre, d_in[3], D_, D_, 128, PRD);
    make_map(fn, &tdim, d_in[4], D_, D_, 128, PRD);
    make_map(fn, &tout, d_out, S_, D_, 16 * OP);
    Params P;
    P.x = (const __nv_bfloat16*)d_in[0];
    P.dre = (const __nv_bfloat16*)d_in[3];
    P.dim = (const __nv_bfloat16*)d_in[4];
    P.wr = (const __nv_bfloat16*)d_in[6];
    P.wg = (const __nv_bfloat16*)d_in[7];
    P.wu = (const __nv_bfloat16*)d_in[8];
    P.wd = (const __nv_bfloat16*)d_in[9];
    P.zero = 0;
    fnet_fused_kernel<<<NCTA, NTHREADS, SMEM_BYTES, cudaStreamPerThread>>>(tx, tdre, tdim, tcre, tcim, tout, P);
}
```

```cpp
#include <cuda_runtime.h>
#include <cuda_bf16.h>
#include <cuda.h>
#include <stdint.h>

#define LDEL 0
#define XS 0x6543
#define GSL 200
#define YNS 0u
#define YLD 1
#define PDEL 2500
#define PGAP 600
#define PK 4
#define ASYM 1
#define RF 1
#define EF2 16
#define NLATE 1
#define KQ 4
#define OP 4
#define XJ0 20
#define EGAP1 0
#define EGAP2 0
#define ESTAG 120
#define QJ 10
#define GOJ 2
#define TANH 1
#define SYNCS 0x22200080ull
#define K0 0
#define KRD 1500
#define SYNCD 2
#define SYNCCAP 4000u
#define SYNCMIN 24u
#define SYNCLAG 820u
#define QUIET 1
#define PRX CU_TENSOR_MAP_L2_PROMOTION_L2_128B
#define PRD CU_TENSOR_MAP_L2_PROMOTION_L2_128B
#define PRC CU_TENSOR_MAP_L2_PROMOTION_L2_128B
#define SLEEP_NS 200
#define PROD_REGS 32
#define CONS_REGS 184

namespace {

constexpr int S_ = 2048, D_ = 1024, F_ = 3584;
constexpr int NCTA = 128;
constexpr int XJ = XJ0;
constexpr uint32_t SLOT = 16384;
constexpr uint32_t OFF_L = 0;
constexpr uint32_t OFF_S = 8 * SLOT;
constexpr uint32_t OFF_RS = OFF_S + SLOT;
constexpr uint32_t OFF_BAR = 14 * SLOT;
constexpr uint32_t OFF_SEL = OFF_BAR + 360;
constexpr uint32_t OFF_RSTD = OFF_BAR + 384;
constexpr uint32_t OFF_MEAN = OFF_RSTD + 1024;
constexpr uint32_t OFF_XB = OFF_MEAN + 512;
constexpr uint32_t OFF_H = OFF_XB + 1024;
constexpr uint32_t SMEM_BYTES = OFF_H + 128;
constexpr uint32_t OFF_TS = OFF_XB + 512;
constexpr uint32_t SB0 = 1024;
constexpr int NTHREADS = 512;
static_assert(SMEM_BYTES <= 232448, "smem");

enum { B_FS = 0, B_ES = 6, B_FL = 12, B_EL = 20, B_SRD = 28, B_OUT = 30, B_RECV = 32, B_RDY = 34, B_STATS = 36, B_LST = 37  , B_UPD = 38,
       B_QUIET = 39, B_GO = 40, B_PEER = 41, B_SEL = 42, B_H = 43, B_COUNT = 44 };
static_assert(B_COUNT * 8 <= 360, "barriers");

__device__ __align__(1024) uint8_t g_ab[16u * 32u * SLOT];
__device__ __align__(128) uint4 g_part[56 * (D_ / 4)];
__device__ __align__(128) uint4 g_stat[S_];
__device__ __align__(128) uint4 g_rs[D_];
__device__ __align__(128) unsigned long long g_key[NCTA];
__device__ __align__(128) unsigned long long g_flag[16 * 16];
__device__ __align__(128) unsigned long long g_sync[16 * 16];
__device__ __align__(128) unsigned g_epoch[NCTA];
#define PROF_T(i) do {} while (0)
#define TRACE(i) do {} while (0)
#define PROF_G(i) do {} while (0)
#define TS(i) do {} while (0)
#define FINISH(wg) bulk_wait_read<0>()

#define MARK(it, ph) do {} while (0)

__device__ __forceinline__ uint32_t smem_u32(const void* p) { return (uint32_t)__cvta_generic_to_shared(p); }
__device__ __forceinline__ void mbar_init(uint32_t bar, uint32_t cnt) {
    asm volatile("mbarrier.init.shared::cta.b64 [%0], %1;" ::"r"(bar), "r"(cnt) : "memory");
}
__device__ __forceinline__ bool mbar_try(uint32_t bar, uint32_t parity) {
    uint32_t ok;
    asm volatile("{\n.reg .pred p;\nmbarrier.try_wait.parity.shared::cta.b64 p, [%1], %2;\nselp.u32 %0, 1, 0, p;\n}"
                 : "=r"(ok) : "r"(bar), "r"(parity) : "memory");
    return ok;
}
__device__ __forceinline__ bool mbar_test(uint32_t bar, uint32_t parity) {
    uint32_t ok;
    asm volatile("{\n.reg .pred p;\nmbarrier.test_wait.parity.shared::cta.b64 p, [%1], %2;\nselp.u32 %0, 1, 0, p;\n}"
                 : "=r"(ok) : "r"(bar), "r"(parity) : "memory");
    return ok;
}
__device__ __forceinline__ bool mbar_try_cluster(uint32_t bar, uint32_t parity) {
    uint32_t ok;
    asm volatile("{\n.reg .pred p;\nmbarrier.try_wait.parity.acquire.cluster.shared::cta.b64 p, [%1], %2;\nselp.u32 %0, 1, 0, p;\n}"
                 : "=r"(ok) : "r"(bar), "r"(parity) : "memory");
    return ok;
}
constexpr int SPIN_LIMIT = 1 << 20;
__device__ __forceinline__ void mbar_wait(uint32_t bar, uint32_t parity) {
    if (mbar_try(bar, parity)) return;
    int n = 0;
    while (!mbar_try(bar, parity) && ++n < SPIN_LIMIT) {}
}
__device__ __forceinline__ void mbar_wait_cluster(uint32_t bar, uint32_t parity) {
    int n = 0;
    while (!mbar_try_cluster(bar, parity) && ++n < SPIN_LIMIT) {}
}
__device__ __forceinline__ void mbar_wait_sleep(uint32_t bar, uint32_t parity) {
    int n = 0;
    while (!mbar_try(bar, parity) && ++n < SPIN_LIMIT) __nanosleep(SLEEP_NS);
}
__device__ __forceinline__ void mbar_arrive(uint32_t bar) {
    asm volatile("mbarrier.arrive.shared::cta.b64 _, [%0];" ::"r"(bar) : "memory");
}
__device__ __forceinline__ void mbar_arrive_cluster(uint32_t cluster_bar) {
    asm volatile("mbarrier.arrive.shared::cluster.b64 _, [%0];" ::"r"(cluster_bar) : "memory");
}
__device__ __forceinline__ void mbar_expect_tx(uint32_t bar, uint32_t bytes) {
    asm volatile("mbarrier.arrive.expect_tx.shared::cta.b64 _, [%0], %1;" ::"r"(bar), "r"(bytes) : "memory");
}
__device__ __forceinline__ bool elect_one() {
    uint32_t p;
    asm volatile("{\n.reg .pred p;\nelect.sync _|p, 0xffffffff;\nselp.u32 %0, 1, 0, p;\n}" : "=r"(p));
    return p;
}
__device__ __forceinline__ uint32_t mapa(uint32_t addr, uint32_t rank) {
    uint32_t r;
    asm("mapa.shared::cluster.u32 %0, %1, %2;" : "=r"(r) : "r"(addr), "r"(rank));
    return r;
}
__device__ __forceinline__ uint32_t clock32() { uint32_t t; asm volatile("mov.u32 %0, %%clock;" : "=r"(t)); return t; }
__device__ __forceinline__ void sleep_until(uint32_t t) {
    int n = 0;
    while ((int)(clock32() - t) < 0 && ++n < SPIN_LIMIT) __nanosleep(20);
}
__device__ __forceinline__ void yield(float last, uint32_t zero) {
    if (YLD) asm volatile("nanosleep.u32 %0;" ::"r"((__float_as_uint(last) & zero) | YNS));
}
template <typename T> __device__ __forceinline__ T* at(T* p, uint32_t bytes) {
    asm("" : "+r"(bytes));
    return reinterpret_cast<T*>(reinterpret_cast<uintptr_t>(p) + bytes);
}
__device__ __forceinline__ void tma_2d(uint32_t dst, const CUtensorMap* tm, int c0, int c1, uint32_t bar) {
    asm volatile("cp.async.bulk.tensor.2d.shared::cluster.global.mbarrier::complete_tx::bytes [%0], [%1, {%3, %4}], [%2];"
                 ::"r"(dst), "l"(tm), "r"(bar), "r"(c0), "r"(c1) : "memory");
}
__device__ __forceinline__ void tma_2d_store(const CUtensorMap* tm, int c0, int c1, uint32_t src) {
    asm volatile("cp.async.bulk.tensor.2d.global.shared::cta.bulk_group [%0, {%2, %3}], [%1];"
                 ::"l"(tm), "r"(src), "r"(c0), "r"(c1) : "memory");
}
__device__ __forceinline__ void bulk_g2s(uint32_t dst, const void* src, uint32_t bytes, uint32_t bar) {
    asm volatile("cp.async.bulk.shared::cluster.global.mbarrier::complete_tx::bytes [%0], [%1], %2, [%3];"
                 ::"r"(dst), "l"(src), "r"(bytes), "r"(bar) : "memory");
}
__device__ __forceinline__ void bulk_s2g(void* dst, uint32_t src, uint32_t bytes) {
    asm volatile("cp.async.bulk.global.shared::cta.bulk_group [%0], [%1], %2;" ::"l"(dst), "r"(src), "r"(bytes) : "memory");
}
__device__ __forceinline__ void st_async4(uint32_t dst, uint32_t a, uint32_t b, uint32_t c, uint32_t d, uint32_t bar) {
    asm volatile("st.async.weak.shared::cluster.mbarrier::complete_tx::bytes.v4.b32 [%0], {%1,%2,%3,%4}, [%5];"
                 ::"r"(dst), "r"(a), "r"(b), "r"(c), "r"(d), "r"(bar) : "memory");
}
__device__ __forceinline__ void bulk_commit() { asm volatile("cp.async.bulk.commit_group;" ::: "memory"); }
template <int N> __device__ __forceinline__ void bulk_wait_read() { asm volatile("cp.async.bulk.wait_group.read %0;" ::"n"(N) : "memory"); }
template <int N> __device__ __forceinline__ void bulk_wait() { asm volatile("cp.async.bulk.wait_group %0;" ::"n"(N) : "memory"); }
__device__ __forceinline__ void fence_async_smem() { asm volatile("fence.proxy.async.shared::cta;" ::: "memory"); }
__device__ __forceinline__ void fence_async_global() { asm volatile("fence.proxy.async.global;" ::: "memory"); }
__device__ __forceinline__ void prefetch_tmap(const CUtensorMap* tm) {
    asm volatile("prefetch.tensormap [%0];" ::"l"(tm) : "memory");
}
__device__ __forceinline__ unsigned long long ld_acquire64(const unsigned long long* p) {
    unsigned long long v; asm volatile("ld.acquire.gpu.global.u64 %0, [%1];" : "=l"(v) : "l"(p) : "memory"); return v;
}
__device__ __forceinline__ unsigned load_epoch(int b) {
    unsigned v; asm volatile("ld.global.u32 %0, [%1];" : "=r"(v) : "l"(at(g_epoch, b * 4)) : "memory"); return v + 1;
}
__device__ __forceinline__ unsigned ld_relaxed(const void* p) {
    unsigned v; asm volatile("ld.relaxed.gpu.global.u32 %0, [%1];" : "=r"(v) : "l"(p) : "memory"); return v;
}
__device__ __forceinline__ unsigned long long ld_relaxed64(const unsigned long long* p) {
    unsigned long long v; asm volatile("ld.relaxed.gpu.global.u64 %0, [%1];" : "=l"(v) : "l"(p) : "memory"); return v;
}
__device__ __forceinline__ void red_max64(unsigned long long* p, unsigned long long v) {
    asm volatile("red.relaxed.gpu.global.max.u64 [%0], %1;" ::"l"(p), "l"(v) : "memory");
}
__device__ __forceinline__ uint4 ld_relaxed128(const uint4* p) {
    uint4 v;
    asm volatile("{\n.reg .b128 t;\n.reg .b64 lo, hi;\nld.relaxed.gpu.global.b128 t, [%4];\nmov.b128 {lo, hi}, t;\n"
                 "mov.b64 {%0, %1}, lo;\nmov.b64 {%2, %3}, hi;\n}"
                 : "=r"(v.x), "=r"(v.y), "=r"(v.z), "=r"(v.w) : "l"(p) : "memory");
    return v;
}
__device__ __forceinline__ void st_relaxed128(uint4* p, const uint4& v) {
    asm volatile("{\n.reg .b128 t;\n.reg .b64 lo, hi;\nmov.b64 lo, {%1, %2};\nmov.b64 hi, {%3, %4};\nmov.b128 t, {lo, hi};\n"
                 "st.relaxed.gpu.global.b128 [%0], t;\n}"
                 ::"l"(p), "r"(v.x), "r"(v.y), "r"(v.z), "r"(v.w) : "memory");
}
__device__ __forceinline__ void st_relaxed64(unsigned long long* p, unsigned long long v) {
    asm volatile("st.relaxed.gpu.global.u64 [%0], %1;" ::"l"(p), "l"(v) : "memory");
}
__device__ __forceinline__ void st_release8(void* p, unsigned v) {
    asm volatile("st.release.gpu.global.u8 [%0], %1;" ::"l"(p), "r"(v) : "memory");
}
__device__ __forceinline__ uint64_t policy_evict_first() {
    uint64_t pol;
    asm("createpolicy.fractional.L2::evict_first.b64 %0, 1.0;" : "=l"(pol));
    return pol;
}
__device__ __forceinline__ uint4 ldg_stream(const void* p, uint64_t pol) {
    uint4 v;
    asm volatile("ld.global.nc.L1::no_allocate.L2::cache_hint.v4.u32 {%0,%1,%2,%3}, [%4], %5;"
                 : "=r"(v.x), "=r"(v.y), "=r"(v.z), "=r"(v.w) : "l"(p), "l"(pol));
    return v;
}
template <int ID, int N> __device__ __forceinline__ void named_arrive() { asm volatile("bar.arrive %0, %1;" ::"n"(ID), "n"(N) : "memory"); }
template <int ID, int N> __device__ __forceinline__ void named_bar() { asm volatile("bar.sync %0, %1;" ::"n"(ID), "n"(N) : "memory"); }

__device__ __forceinline__ float bf_lo(uint32_t u) { return __uint_as_float(u << 16); }
__device__ __forceinline__ float bf_hi(uint32_t u) { return __uint_as_float(u & 0xffff0000u); }
__device__ __forceinline__ uint32_t pack_bf(float lo, float hi) {
    uint32_t r; asm("cvt.rn.bf16x2.f32 %0, %1, %2;" : "=r"(r) : "f"(hi), "f"(lo)); return r;
}
__device__ __forceinline__ float rbf(float v) { return __uint_as_float(pack_bf(0.f, v)); }
__device__ __forceinline__ float sqrt_f(float v) { float r; asm("sqrt.approx.f32 %0, %1;" : "=f"(r) : "f"(v)); return r; }
__device__ __forceinline__ float rcp_f(float v) { float r; asm("rcp.approx.f32 %0, %1;" : "=f"(r) : "f"(v)); return r; }
__device__ __forceinline__ float silu_f(float z) { return __fdividef(z, 1.0f + __expf(-z)); }
__device__ __forceinline__ uint32_t bsub2(uint32_t a, uint32_t b) {
    uint32_t r; asm("sub.rn.bf16x2 %0, %1, %2;" : "=r"(r) : "r"(a), "r"(b)); return r;
}
__device__ __forceinline__ uint32_t bfma2(uint32_t a, uint32_t b, uint32_t c) {
    uint32_t r; asm("fma.rn.bf16x2 %0, %1, %2, %3;" : "=r"(r) : "r"(a), "r"(b), "r"(c)); return r;
}
__device__ __forceinline__ uint32_t norm2(uint32_t xv, float m, float rinv) {
    uint32_t t = pack_bf(bf_lo(xv) - m, bf_hi(xv) - m);
    return pack_bf(bf_lo(t) * rinv, bf_hi(t) * rinv);
}
__device__ __forceinline__ float gate1(float z) {
    if (TANH) {
        float t;
        const float h = 0.5f * z;
        asm("tanh.approx.f32 %0, %1;" : "=f"(t) : "f"(h));
        return fmaf(h, t, h);
    }
    float e, r;
    asm("ex2.approx.ftz.f32 %0, %1;" : "=f"(e) : "f"(z * -1.4426950408889634f));
    asm("rcp.approx.ftz.f32 %0, %1;" : "=f"(r) : "f"(1.0f + e));
    return z * r;
}
__device__ __forceinline__ uint32_t gate2(uint32_t xv, uint32_t mean2, float r0, float r1) {
    const uint32_t t = bsub2(xv, mean2);
    return pack_bf(gate1(bf_lo(t) * r0), gate1(bf_hi(t) * r1));
}
__device__ __forceinline__ uint32_t silu2(uint32_t z) { return pack_bf(silu_f(bf_lo(z)), silu_f(bf_hi(z))); }

__device__ __forceinline__ void stmatrix4(uint32_t addr, uint32_t r0, uint32_t r1, uint32_t r2, uint32_t r3) {
    asm volatile("stmatrix.sync.aligned.m8n8.x4.shared.b16 [%0], {%1,%2,%3,%4};"
                 ::"r"(addr), "r"(r0), "r"(r1), "r"(r2), "r"(r3));
}
__device__ __forceinline__ void stmatrix4t(uint32_t addr, uint32_t r0, uint32_t r1, uint32_t r2, uint32_t r3) {
    asm volatile("stmatrix.sync.aligned.m8n8.x4.trans.shared.b16 [%0], {%1,%2,%3,%4};"
                 ::"r"(addr), "r"(r0), "r"(r1), "r"(r2), "r"(r3));
}
__device__ __forceinline__ void ldmatrix4t(uint32_t addr, uint32_t& r0, uint32_t& r1, uint32_t& r2, uint32_t& r3) {
    asm volatile("ldmatrix.sync.aligned.m8n8.x4.trans.shared.b16 {%0,%1,%2,%3}, [%4];"
                 : "=r"(r0), "=r"(r1), "=r"(r2), "=r"(r3) : "r"(addr));
}

__device__ __forceinline__ void wg_fence() { asm volatile("wgmma.fence.sync.aligned;" ::: "memory"); }
__device__ __forceinline__ void wg_commit() { asm volatile("wgmma.commit_group.sync.aligned;" ::: "memory"); }
template <int N> __device__ __forceinline__ void wg_wait() { asm volatile("wgmma.wait_group.sync.aligned %0;" ::"n"(N) : "memory"); }

__host__ __device__ constexpr uint32_t desc_lo(uint32_t addr, uint32_t lbo) { return ((addr & 0x3FFFF) >> 4) | ((lbo >> 4) << 16); }
#define DESC_HI "0x40000040"

#define R8(a, o) "+f"(a[(o) + 0]), "+f"(a[(o) + 1]), "+f"(a[(o) + 2]), "+f"(a[(o) + 3]), \
                 "+f"(a[(o) + 4]), "+f"(a[(o) + 5]), "+f"(a[(o) + 6]), "+f"(a[(o) + 7])
#define R64(a, o) R8(a, (o) + 0), R8(a, (o) + 8), R8(a, (o) + 16), R8(a, (o) + 24), \
                  R8(a, (o) + 32), R8(a, (o) + 40), R8(a, (o) + 48), R8(a, (o) + 56)

template <int O, int TA>
__device__ __forceinline__ void wgmma128(float (&a)[128], uint32_t da, uint32_t db, int scale_d) {
    asm volatile(
        "{\n.reg .pred p;\n.reg .b64 da, db;\nsetp.ne.b32 p, %66, 0;\n"
        "mov.b64 da, {%64, " DESC_HI "};\nmov.b64 db, {%65, " DESC_HI "};\n"
        "wgmma.mma_async.sync.aligned.m64n128k16.f32.bf16.bf16 "
        "{%0,%1,%2,%3,%4,%5,%6,%7,%8,%9,%10,%11,%12,%13,%14,%15,"
        "%16,%17,%18,%19,%20,%21,%22,%23,%24,%25,%26,%27,%28,%29,%30,%31,"
        "%32,%33,%34,%35,%36,%37,%38,%39,%40,%41,%42,%43,%44,%45,%46,%47,"
        "%48,%49,%50,%51,%52,%53,%54,%55,%56,%57,%58,%59,%60,%61,%62,%63},"
        "da, db, p, 1, 1, %67, 0;\n}"
        : R64(a, O)
        : "r"(da), "r"(db), "r"(scale_d), "n"(TA));
}
template <int O>
__device__ __forceinline__ void wgmma128_rs(float (&a)[128], const uint32_t* f, uint32_t db) {
    asm volatile(
        "{\n.reg .b64 db;\nmov.b64 db, {%68, 8};\n"
        "wgmma.mma_async.sync.aligned.m64n128k16.f32.bf16.bf16 "
        "{%0,%1,%2,%3,%4,%5,%6,%7,%8,%9,%10,%11,%12,%13,%14,%15,"
        "%16,%17,%18,%19,%20,%21,%22,%23,%24,%25,%26,%27,%28,%29,%30,%31,"
        "%32,%33,%34,%35,%36,%37,%38,%39,%40,%41,%42,%43,%44,%45,%46,%47,"
        "%48,%49,%50,%51,%52,%53,%54,%55,%56,%57,%58,%59,%60,%61,%62,%63},"
        "{%64, %65, %66, %67}, db, 1, 1, 1, 0;\n}"
        : R64(a, O)
        : "r"(f[0]), "r"(f[1]), "r"(f[2]), "r"(f[3]), "r"(db));
}
template <int O>
__device__ __forceinline__ void fence_regs64(float (&a)[128]) {
    asm volatile("" : R64(a, O)::"memory");
}

struct Params {
    const __nv_bfloat16* x;
    const __nv_bfloat16* dre;
    const __nv_bfloat16* dim;
    const __nv_bfloat16* wr;
    const __nv_bfloat16* wg;
    const __nv_bfloat16* wu;
    const __nv_bfloat16* wd;
    uint32_t zero;
#define AB g_ab
};

__device__ __forceinline__ float warp_sum(float v) {
#pragma unroll
    for (int o = 16; o; o >>= 1) v += __shfl_xor_sync(0xffffffffu, v, o);
    return v;
}
__device__ __forceinline__ void fma8(float* acc, const uint4& w, float s) {
    acc[0] += s * bf_lo(w.x); acc[1] += s * bf_hi(w.x); acc[2] += s * bf_lo(w.y); acc[3] += s * bf_hi(w.y);
    acc[4] += s * bf_lo(w.z); acc[5] += s * bf_hi(w.z); acc[6] += s * bf_lo(w.w); acc[7] += s * bf_hi(w.w);
}
__device__ __forceinline__ int POS(int t) { return (t & ~15) | ((t & 6) << 1) | ((t & 8) >> 2) | (t & 1); }
__host__ __device__ constexpr int PSLOT(int j) { return j < 4 ? j : (j & 1) + ((j & 2) ? 0 : 4); }
__host__ __device__ constexpr int PPAR(int j) { return j < 4 ? 0 : ((j >> 2) ^ (j >> 1) ^ 1) & 1; }
__host__ __device__ constexpr int DSLOT(int it) { return (it & 3) + 2; }
__device__ __forceinline__ int SREC(int t) { return (t & ~15) | ((t & 3) << 2) | ((t >> 2) & 3); }
__device__ __forceinline__ int KO(int cl) { return ((cl & 1) << 1) | (cl >> 1); }

__device__ __forceinline__ unsigned long long* sync_words() {
    uint32_t t;
    asm volatile("mov.u32 %0, %%smid;" : "=r"(t));
    t >>= 1;
    const uint32_t u = t - 32;
    return at(g_sync, (t < 32 ? t & 7 : t < 60 ? 8 + u - 7 * ((u * 37) >> 8) : 15) * 128);
}

__global__ void __cluster_dims__(2, 1, 1) __launch_bounds__(NTHREADS, 1)
fnet_fused_kernel(const __grid_constant__ CUtensorMap tm_x, const __grid_constant__ CUtensorMap tm_dre,
                  const __grid_constant__ CUtensorMap tm_dim, const __grid_constant__ CUtensorMap tm_cre,
                  const __grid_constant__ CUtensorMap tm_cim, const __grid_constant__ CUtensorMap tm_out,
                  const Params P) {
    extern __shared__ __align__(1024) uint8_t smem[];
    const unsigned long long tstart = clock64();
    const uint32_t sb = smem_u32(smem);
    const int tid = threadIdx.x, lane = tid & 31;
    const int warp = __shfl_sync(0xffffffffu, tid >> 5, 0);
    const int pr = blockIdx.x >> 1, p7 = ((pr - 36) * 37) >> 8;
    const int c = blockIdx.x & 1;
    const int g = pr < 4 ? 0 : pr < 36 ? (pr - 4) & 7 : pr - 35 - 7 * p7;
    const int r = pr < 4 ? 4 + pr : pr < 36 ? (pr - 4) >> 3 : 4 + p7;
    const int grp = 2 * r + c;
    const int b = g * 16 + grp;
    const uint32_t bar0 = sb + OFF_BAR;
    const uint32_t zero = P.zero;
#define BAR(i) (bar0 + 8u * (i))
#define XBAR(i) (sb + OFF_XB + 64 + 8u * (i))
#define CLUSTER_ARRIVE() asm volatile("barrier.cluster.arrive.relaxed.aligned;" ::: "memory")
#define CLUSTER_WAIT() asm volatile("barrier.cluster.wait.aligned;" ::: "memory")
    if ((sb & 0xffffffu) != SB0) return;

    if (warp == 12) {
        const CUtensorMap* tmD = c ? &tm_dim : &tm_dre;
#define LOAD0(it) do { \
            mbar_expect_tx(BAR(B_FS + DSLOT(it)), SLOT); tma_2d(sb + OFF_S + DSLOT(it) * SLOT, tmD, (it) * 64, r * 128, BAR(B_FS + DSLOT(it))); \
            mbar_expect_tx(BAR(B_FL + (it)), SLOT); tma_2d(sb + OFF_L + (it) * SLOT, &tm_x, (it) * 64, g * 256, BAR(B_FL + (it))); \
            mbar_expect_tx(BAR(B_FL + 4 + (it)), SLOT); tma_2d(sb + OFF_L + (4 + (it)) * SLOT, &tm_x, (it) * 64, g * 256 + 128, BAR(B_FL + 4 + (it))); \
        } while (0)
        if (elect_one()) {
            prefetch_tmap(tmD); prefetch_tmap(&tm_x);
            mbar_init(BAR(B_FS + 2), 1); mbar_init(BAR(B_FL), 1); mbar_init(BAR(B_FL + 4), 1);
            fence_async_smem();
            LOAD0(0);
#pragma unroll
            for (int i = 0; i < B_COUNT; i++)
                if (i != B_FS + 2 && i != B_FL && i != B_FL + 4)
                    mbar_init(BAR(i), (i >= B_ES && i < B_FL) || i == B_GO ? 2 : i == B_STATS || i == B_LST || (i & ~1) == B_OUT ? 4 : 1);
#pragma unroll
            for (int i = 0; i < 12; i++) mbar_init(XBAR(i), 1);
            mbar_expect_tx(BAR(B_RECV), SLOT); mbar_expect_tx(BAR(B_RECV + 1), SLOT);
            mbar_expect_tx(BAR(B_PEER), 1024); mbar_expect_tx(BAR(B_H), 128);
            *reinterpret_cast<volatile uint32_t*>(smem + OFF_SEL + 8) = 0;
            asm volatile("fence.mbarrier_init.release.cluster;" ::: "memory");
            fence_async_smem();
        }
        __syncwarp();
        CLUSTER_ARRIVE();
    } else {
        CLUSTER_ARRIVE();
        if (K0 && tid == 13 * 32) red_max64(sync_words(), tstart);
    }

    if (warp >= 12) {
        asm volatile("setmaxnreg.dec.sync.aligned.u32 %0;" ::"n"(PROD_REGS));
        if (warp != 12) CLUSTER_WAIT();
        if (warp == 12) {
            if (elect_one()) {
                const CUtensorMap* tmD = c ? &tm_dim : &tm_dre;
                if (LDEL) sleep_until((uint32_t)tstart + LDEL);
#define XROWS(k) do { mbar_expect_tx(XBAR(k), 8192); bulk_g2s(sb + OFF_S + (k) * 8192, at(P.x, (b * 16 + (k) * 4) * D_ * 2), 8192, XBAR(k)); } while (0)
                int k = 0;
#pragma unroll 1
                for (int it = 1; it < 16; it++) {
                    if (it < 4) LOAD0(it);
                    else {
                        const int s = DSLOT(it);
                        mbar_wait(BAR(B_ES + s), ((it >> 2) & 1) ^ 1);
                        TRACE(it);
                        mbar_expect_tx(BAR(B_FS + s), SLOT);
                        tma_2d(sb + OFF_S + s * SLOT, tmD, it * 64, r * 128, BAR(B_FS + s));
                    }
                    while (((XS >> (4 * k)) & 15) == it) { XROWS(k); k++; }
                }
                const unsigned ep = load_epoch(b), e8 = ep & 0xffu;
                const uint8_t* abg = at(AB, grp * 32 * SLOT);
                const unsigned long long* fl = at(g_flag, grp * 128);
                unsigned long long rdy = ld_acquire64(fl);
                mbar_wait(BAR(B_SRD), 0);
                st_release8(at(g_flag, grp * 128 + g), e8);
                PROF_T(7);
                int j = 4;
#pragma unroll 1
                for (int cl = 0; cl < 4; cl++) {
                    if (cl) rdy = ld_acquire64(fl + cl);
                    fence_async_global();
#pragma unroll 1
                    for (int n = 1; n < 8; n++, j++) {
                        const int q = (g + n) & 7, s = (j & 1) + ((j & 2) ? 0 : 4);
                        mbar_wait(BAR(B_ES + s), ((j >> 2) ^ (j >> 1)) & 1);
                        if (j == 7) mbar_wait(BAR(B_SRD + 1), 0);
                        if (((unsigned)(rdy >> (8 * q)) & 0xffu) != e8) {
                            int m = 0;
                            do { rdy = ld_acquire64(fl + cl); } while (((unsigned)(rdy >> (8 * q)) & 0xffu) != e8 && ++m < SPIN_LIMIT);
                            fence_async_global();
                        }
                        TRACE(16 + j);
                        mbar_expect_tx(BAR(B_FS + s), SLOT);
                        bulk_g2s(sb + OFF_S + s * SLOT, at(abg, (4 * q + KO(cl)) * SLOT), SLOT, BAR(B_FS + s));
                    }
                }
                *at(g_epoch, b * 4) = ep;
            }
        } else if (warp < 15) {
            if (elect_one()) {
                const int w = warp - 13, row0 = g * 256 + w * 128;
                const CUtensorMap* tmC = c ? &tm_cim : &tm_cre;
                const uint32_t fb = BAR(B_FL + 4 * w), eb = BAR(B_EL + 4 * w), dst = sb + OFF_L + w * 4 * SLOT;
                prefetch_tmap(w ? &tm_out : tmC);
                unsigned long long* sy = sync_words();
#define ADOPT(ph, lag) do { const unsigned long long v = ld_relaxed64(sy++); \
                    if (v - (ph) - SYNCMIN < SYNCCAP) *reinterpret_cast<volatile uint32_t*>(smem + OFF_SEL + 8) = (uint32_t)v - (lag); } while (0)
                if (w == 0 && K0) { sleep_until((uint32_t)tstart + KRD); ADOPT(tstart, 0u - K0); }
                [[maybe_unused]] unsigned long long mk = 0;
                int n = 0, cl = 0;
#pragma unroll 1
                for (int it = 4; it < 48; it++) {
                    const int s = it & 3;
                    mbar_wait(eb + 8 * s, ((it >> 2) & 1) ^ 1);
                    const unsigned long long ph = clock64() - 1024u * (it - 4);
                    TRACE(64 + w * 64 + it - 4);
                    MARK(it, ph);
                    mbar_expect_tx(fb + 8 * s, SLOT);
                    tma_2d(dst + s * SLOT, it < 16 ? &tm_x : tmC, (it < 16 ? it : 4 * ((g + n) & 7) + KO(cl)) * 64, row0, fb + 8 * s);
                    if (it >= 16) {
                        if (it == 19) { n = 1; cl = 0; } else if (it < 19) cl++; else if (++n == 8) { n = 1; cl++; }
                    }
                    if (w == 0) {
                        if (((SYNCS << 4) >> it) & 1) red_max64(sy, ph);
                        if (((SYNCS << (4 + SYNCD)) >> it) & 1) ADOPT(ph, SYNCLAG);
                    }
                }
                {
#pragma unroll 1
                    for (int h = 0; h < 8 / OP; h++) {
                        mbar_wait(BAR((h ? B_STATS : B_OUT) + w), h);
                        fence_async_smem();
                        tma_2d_store(&tm_out, grp * 64, row0 + h * OP * 16, sb + OFF_S + (2 + w) * SLOT + h * OP * 2048);
                        bulk_commit();
                    }
                    FINISH(w);
                }
            }
        } else {
            const unsigned ep = load_epoch(b);
            uint4 f[4];
#define GATHER(ptr, cnt, valid) do { int n = 0; bool ok; do { ok = true; \
                _Pragma("unroll") for (int i = 0; i < (cnt); i++) { f[i] = ld_relaxed128((ptr) + i * 32); ok = ok && (valid); } \
                if (__all_sync(0xffffffffu, ok)) break; \
                __nanosleep(GSL); \
            } while (++n < SPIN_LIMIT); } while (0)
            {
                sleep_until((uint32_t)tstart + 6000);
                const uint4* keys = at(reinterpret_cast<const uint4*>(g_key), lane * 16);
                bool mine = false;
                int n = 0;
                do {
                    f[0] = ld_relaxed128(keys); f[1] = ld_relaxed128(keys + 32);
                    if (__all_sync(0xffffffffu, f[0].y == ep && f[0].w == ep && f[1].y == ep && f[1].w == ep)) break;
                    if (!mine) {
                        mbar_wait(BAR(B_LST), 0);
                        const uint4 k = *reinterpret_cast<const uint4*>(smem + OFF_XB);
                        if (lane == 0) st_relaxed64(at(g_key, b * 8), ((unsigned long long)ep << 32) | max(max(k.x, k.y), max(k.z, k.w)));
                        mine = true;
                    }
                    __nanosleep(GSL);
                } while (++n < SPIN_LIMIT);
                const unsigned key = __reduce_max_sync(0xffffffffu, max(max(f[0].x, f[0].z), max(f[1].x, f[1].z)));
                if (lane == 0) { *reinterpret_cast<unsigned*>(smem + OFF_SEL) = key; mbar_arrive(BAR(B_SEL)); PROF_T(8); }
            }
            if (elect_one()) {
#pragma unroll 1
                for (int cl = 0; cl < 4; cl++) {
                    uint8_t* dst = at(AB, (grp * 32 + 4 * g + KO(cl)) * SLOT);
                    const uint32_t src = sb + OFF_S + cl * SLOT, chunk = cl ? 4096 : SLOT;
                    mbar_wait(BAR(B_FS + cl), 0);
                    if (RF) fence_async_smem();
                    if (cl == 0) PROF_T(3);
                    uint32_t t0 = clock32() + (cl == 1 ? PDEL : 0);
#pragma unroll 1
                    for (uint32_t o = 0; o < SLOT; o += chunk) {
                        sleep_until(t0);
                        bulk_s2g(dst + o, src + o, chunk);
                        bulk_commit();
                        t0 += PGAP;
                    }
                    bulk_wait<0>();
                    TRACE(252 + cl);
                    if (cl < 2) mbar_arrive(BAR(B_SRD + cl));
                    else {
                        mbar_wait(BAR(B_ES + cl), 0);
                        mbar_expect_tx(BAR(B_FS + cl), SLOT);
                        tma_2d(src, &tm_x, grp * 64, g * 256 + (cl - 2) * 128, BAR(B_FS + cl));
                    }
                    if (cl) st_release8(at(g_flag, grp * 128 + cl * 8 + g), ep & 0xffu);
                    if (cl == 1) PROF_T(5);
                    if (cl == 3) PROF_T(4);
                }
            }
        }
    } else if (warp >= 8) {
        asm volatile("setmaxnreg.dec.sync.aligned.u32 %0;" ::"n"(512 - PROD_REGS - 2 * CONS_REGS));
        const int aw = warp - 8, mt = tid - 256;
        unsigned ep;
        {
            const uint8_t* rp = smem + OFF_S + aw * 2048 + lane * 16;
            const __nv_bfloat16* dp = at(c ? P.dim : P.dre, (r * 128 + g * 16 + aw * 4) * D_ * 2);
            float wf[32], sw = 0.f;
#pragma unroll
            for (int i = 0; i < 4; i++) {
                const uint4 w = __ldg(reinterpret_cast<const uint4*>(at(P.wr, lane * 16) + i * 256));
                const uint32_t wv[4] = {w.x, w.y, w.z, w.w};
#pragma unroll
                for (int e = 0; e < 4; e++) { wf[8 * i + 2 * e] = bf_lo(wv[e]); wf[8 * i + 2 * e + 1] = bf_hi(wv[e]); sw = (sw + bf_lo(wv[e])) + bf_hi(wv[e]); }
            }
            ep = load_epoch(b);
            sw = warp_sum(sw);
            CLUSTER_WAIT();
            float x0[4] = {}, s1[4] = {}, s2[4] = {}, sx[4] = {}, sd[4] = {};
#define PUSH(a, v) do { a[0] = a[1]; a[1] = a[2]; a[2] = a[3]; a[3] = v; } while (0)
#pragma unroll 1
            for (int k = 0; k < 4; k++) {
                mbar_wait(XBAR(k), 0);
                uint4 v[4];
#pragma unroll
                for (int i = 0; i < 4; i++) v[i] = *reinterpret_cast<const uint4*>(rp + k * 8192 + i * 512);
                uint32_t sh = v[0].x << 16;
                float a1s = 0.f, a2s = 0.f, axs = 0.f;
#pragma unroll
                for (int i = 0; i < 4; i++) {
                    sh = __shfl_sync(0xffffffffu, sh | (__float_as_uint(axs) & zero), 0);
                    const uint32_t xv[4] = {v[i].x, v[i].y, v[i].z, v[i].w};
#pragma unroll
                    for (int e = 0; e < 4; e++) {
                        const float a0 = bf_lo(xv[e]) - __uint_as_float(sh), a1 = bf_hi(xv[e]) - __uint_as_float(sh);
                        a1s += a0 + a1;
                        a2s = fmaf(a0, a0, fmaf(a1, a1, a2s));
                        axs = fmaf(a0, wf[8 * i + 2 * e], fmaf(a1, wf[8 * i + 2 * e + 1], axs));
                    }
                }
                PUSH(x0, __uint_as_float(sh)); PUSH(s1, a1s); PUSH(s2, a2s); PUSH(sx, axs);
                fence_async_smem();
                __syncwarp();
                if (elect_one()) {
                    const uint32_t db = XBAR(k == 3 ? 8 + aw : 4 + aw);
                    if (k == 0 || k == 3) mbar_expect_tx(db, k ? 2048 : 6144);
                    bulk_g2s(sb + OFF_S + k * 8192 + aw * 2048, dp + k * D_, 2048, db);
                }
            }
#define FOLD4(a) do { const bool u16 = lane & 16, u8 = lane & 8; \
                float p0 = (u16 ? a[2] : a[0]) + __shfl_xor_sync(0xffffffffu, u16 ? a[0] : a[2], 16); \
                float p1 = (u16 ? a[3] : a[1]) + __shfl_xor_sync(0xffffffffu, u16 ? a[1] : a[3], 16); \
                a[0] = (u8 ? p1 : p0) + __shfl_xor_sync(0xffffffffu, u8 ? p0 : p1, 8); \
                _Pragma("unroll") for (int o = 4; o; o >>= 1) a[0] += __shfl_xor_sync(0xffffffffu, a[0], o); } while (0)
#pragma unroll 1
            for (int k = 0; k < 4; k++) {
                mbar_wait(XBAR(k == 3 ? 8 + aw : 4 + aw), 0);
                float run = 0.f;
#pragma unroll
                for (int i = 0; i < 4; i++) {
                    const uint4 v = *reinterpret_cast<const uint4*>(rp + k * 8192 + i * 512);
                    const uint32_t dv[4] = {v.x, v.y, v.z, v.w};
#pragma unroll
                    for (int e = 0; e < 4; e++) run += bf_lo(dv[e]) + bf_hi(dv[e]);
                }
                PUSH(sd, run);
            }
            FOLD4(sd); FOLD4(s1); FOLD4(s2); FOLD4(sx);
            const float nb = __shfl_down_sync(0xffffffffu, sd[0], 8);
            if ((lane & 15) == 0)
                st_relaxed128(at(g_rs, (grp * 64 + g * 8 + aw * 2 + (lane >> 4)) * 16), make_uint4(__float_as_uint(sd[0]), ep, __float_as_uint(nb), ep));
            if (mt == 0) PROF_T(6);
            const int rr = lane >> 3;
            const float c0 = rr == 0 ? x0[0] : rr == 1 ? x0[1] : rr == 2 ? x0[2] : x0[3];
            const float dm = s1[0] * (1.0f / D_);
            const float mb = rbf(c0 + dm);
            const float rinv = rcp_f(rbf(sqrt_f(rbf(rbf(fmaxf(s2[0] * (1.0f / D_) - dm * dm, 0.f)) + 1e-5f))));
            if ((lane & 7) == 0) st_relaxed128(at(g_stat, (b * 16 + aw * 4 + rr) * 16), make_uint4(__float_as_uint(mb), __float_as_uint(rinv), ep, 0));
            unsigned u = __bfloat16_as_ushort(__float2bfloat16_rn((sx[0] + (c0 - mb) * sw) * rinv));
            u = (u & 0x8000u) ? (~u & 0xffffu) : (u | 0x8000u);
            u = (u << 16) | (0xffffu - (unsigned)(b * 16 + rr * 4 + aw));
            u = __reduce_max_sync(0xffffffffu, u);
            if (lane == 0) { *reinterpret_cast<unsigned*>(smem + OFF_XB + aw * 4) = u; mbar_arrive(BAR(B_LST)); }
            if (mt == 0) PROF_T(2);
            named_bar<4, 128>();
            if (mt < 12) asm volatile("mbarrier.inval.shared::cta.b64 [%0];" ::"r"(XBAR(mt)) : "memory");
            uint4 f[4];
            if (aw < 2) {
                const int t = SREC(aw * 128 + lane);
                GATHER(at(g_stat, (g * 256 + aw * 128 + lane) * 16), 4, f[i].z == ep);
#pragma unroll
                for (int i = 0; i < 4; i++) {
                    *reinterpret_cast<uint32_t*>(smem + OFF_RSTD + (POS(t) + i * 32) * 4) = f[i].y;
                    *reinterpret_cast<uint16_t*>(smem + OFF_MEAN + (POS(t) + i * 32) * 2) = (uint16_t)(f[i].x >> 16);
                }
            } else {
                const int e2 = (aw - 2) * 32 + lane;
                GATHER(at(g_rs, (grp * 64 + e2) * 16), 1, f[i].y == ep && f[i].w == ep);
#pragma unroll
                for (int i = 0; i < 2; i++) {
                    const float v = __uint_as_float(i ? f[0].z : f[0].x);
                    const float hi = rbf(v), mid = rbf(v - hi), lo = v - hi - mid;
                    *reinterpret_cast<uint4*>(smem + OFF_RS + (e2 * 2 + i) * 16) = make_uint4(pack_bf(hi, mid), pack_bf(lo, 0.f), 0, 0);
                }
            }
            fence_async_smem();
            __syncwarp();
            if (lane == 0) mbar_arrive(BAR(B_STATS));
            if (mt == 127) PROF_T(9);
        }
        const int pair = g * 7 + r;
        if (r < 7) {
            const uint64_t pol = policy_evict_first();
            const __nv_bfloat16* wp = at((aw & 1) ? P.wu : P.wg, ((c * 512 + (aw >> 1) * 256 + (lane >> 3) * 8) * F_ + pair * 64 + (lane & 7) * 8) * 2);
            uint4 b0[8], b1[8];
#define FILL(buf, str) do { _Pragma("unroll") for (int q = 0; q < 8; q++) buf[q] = ldg_stream(wp + q * (str), pol); } while (0)
            FILL(b0, F_);
            mbar_wait(BAR(B_SEL), 0);
            uint4 xn;
            {
                const int sel = 0xffff - (int)(*reinterpret_cast<volatile unsigned*>(smem + OFF_SEL) & 0xffffu);
                xn = __ldg(reinterpret_cast<const uint4*>(at(P.x, (sel * D_ + c * 512 + (aw >> 1) * 256 + (lane & 7) * 32 + (lane >> 3) * 8) * 2)));
                uint4 f[1];
                GATHER(at(g_stat, SREC(sel) * 16), 1, f[i].z == ep);
                if (NLATE && mbar_test(BAR(B_QUIET), 0)) mbar_wait_sleep(BAR(B_GO), 0);
                const float m = __uint_as_float(f[0].x), ri = __uint_as_float(f[0].y);
                xn = make_uint4(norm2(xn.x, m, ri), norm2(xn.y, m, ri), norm2(xn.z, m, ri), norm2(xn.w, m, ri));
            }
            float ag[8];
#pragma unroll
            for (int i = 0; i < 8; i++) ag[i] = 0.f;
            const uint32_t stag = (aw * 4 + (grp & 3)) * ESTAG;
            uint32_t te = clock32() + stag;
            bool paused = !QUIET;
#define ROUND(cur, nxt, rd) do { \
                if (!paused && mbar_test(BAR(B_QUIET), 0)) { mbar_wait_sleep(BAR(B_GO), 0); te = clock32() + stag; paused = true; } \
                sleep_until(te); \
                te = clock32() + (paused ? EGAP2 : EGAP1); \
                if (lane == 0) TRACE(192 + aw * 12 + (rd)); \
                if ((rd) == 7) wp = at(P.wd - 16 * D_, ((pair * 64 + (lane >> 4) * 8) * D_ + c * 512 + aw * 128 + (lane & 15) * 8) * 2); \
                wp = at(wp, ((rd) < 7 ? 64 * F_ : 32 * D_) + (cur[7].x & zero)); \
                if ((rd) < 7) FILL(nxt, F_); else if ((rd) != 8 && (rd) < 11) FILL(nxt, D_); \
                _Pragma("unroll") for (int q = 0; q < 8; q += 2) { \
                    uint32_t xw = __shfl_sync(0xffffffffu, q == 0 ? xn.x : q == 2 ? xn.y : q == 4 ? xn.z : xn.w, (lane & 24) | ((rd) & 7)); \
                    fma8(ag, cur[q], bf_lo(xw)); \
                    if (YLD > 1) { yield(ag[7], zero); xw = __shfl_sync(0xffffffffu, xw, lane); } \
                    fma8(ag, cur[q + 1], bf_hi(xw)); \
                    if (q < 6) yield(ag[7], zero); \
                } } while (0)
#pragma unroll 1
            for (int rd = 0; rd < 12; rd += 2) {
                ROUND(b0, b1, rd);
                ROUND(b1, b0, rd + 1);
                if (rd == 6) { wp += 16 * D_; FILL(b1, D_); wp -= 16 * D_; }
                if (rd == 6 || rd == 10) {
#pragma unroll
                    for (int i = 0; i < 8; i++) ag[i] += __shfl_xor_sync(0xffffffffu, ag[i], 16);
                }
                if (rd == 6) {
#pragma unroll
                    for (int i = 0; i < 8; i++) ag[i] += __shfl_xor_sync(0xffffffffu, ag[i], 8);
                    if (lane < 8) {
                        const uint32_t dst = mapa(sb + OFF_XB + (c * 4 + aw) * 128 + (lane & 3) * 32, lane >> 2), pb = mapa(BAR(B_PEER), lane >> 2);
                        st_async4(dst, __float_as_uint(ag[0]), __float_as_uint(ag[1]), __float_as_uint(ag[2]), __float_as_uint(ag[3]), pb);
                        st_async4(dst + 16, __float_as_uint(ag[4]), __float_as_uint(ag[5]), __float_as_uint(ag[6]), __float_as_uint(ag[7]), pb);
                    }
                    if (aw == 3) {
                        mbar_wait_cluster(BAR(B_PEER), 0);
                        const float* ps = reinterpret_cast<const float*>(smem + OFF_XB) + lane;
                        const float go = (ps[0] + ps[64]) + (ps[128] + ps[192]), uo = (ps[32] + ps[96]) + (ps[160] + ps[224]);
                        const float h = rbf(silu_f(rbf(go))) * rbf(uo), ho = __shfl_xor_sync(0xffffffffu, h, 1);
                        asm volatile("st.async.weak.shared::cluster.mbarrier::complete_tx::bytes.b32 [%0], %1, [%2];"
                                     ::"r"(mapa(sb + OFF_H + c * 64 + (lane >> 1) * 4, lane & 1)), "r"((lane & 1) ? pack_bf(ho, h) : pack_bf(h, ho)),
                                       "r"(mapa(BAR(B_H), lane & 1)) : "memory");
                    }
                    mbar_wait_cluster(BAR(B_H), 0);
                    xn = *reinterpret_cast<const uint4*>(smem + OFF_H + (lane & 3) * 32 + (lane >> 4) * 16);
#pragma unroll
                    for (int i = 0; i < 8; i++) ag[i] = 0.f;
                    if (mt == 0) PROF_T(10);
                }
            }
            const int hi = lane >> 4;
            st_relaxed128(at(g_part, pair * 4096 + (c * 8 + aw * 2 + ((lane >> 3) & 1)) * 256 + hi * 128 + (lane & 7) * 16),
                          make_uint4((__float_as_uint(hi ? ag[4] : ag[0]) & ~15u) | (ep & 15u), __float_as_uint(hi ? ag[5] : ag[1]),
                                     __float_as_uint(hi ? ag[6] : ag[2]), __float_as_uint(hi ? ag[7] : ag[3])));
            if (mt == 0) PROF_T(11);
        } else {
            mbar_wait_sleep(BAR(B_SEL), 0);
        }
        const int sel = 0xffff - (int)(*reinterpret_cast<volatile unsigned*>(smem + OFF_SEL) & 0xffffu);
        if ((sel >> 8) == g) {
            const int col = (lane & 7) * 8 + ((lane >> 3) & 1) * 4;
            const uint2 xv = __ldg(reinterpret_cast<const uint2*>(at(P.x, (sel * D_ + grp * 64 + col) * 2)));
            uint4 f[1];
            GATHER(at(g_stat, SREC(sel) * 16), 1, f[i].z == ep);
            const uint4 rec = f[0];
            const uint4* src = at(g_part, (aw * 14 + (lane >> 4)) * 4096 + grp * 256 + (lane & 15) * 16);
            if (r == 7) {
                int n = 0;
                while (((ld_relaxed(src) ^ ep) & 15u) != 0 && ++n < SPIN_LIMIT) __nanosleep(500);
            }
            uint4 t[7];
            int n = 0;
            bool ok;
            do {
                ok = true;
#pragma unroll
                for (int u = 0; u < 7; u++) { t[u] = ld_relaxed128(src + u * 512); ok = ok && ((t[u].x ^ ep) & 15u) == 0; }
            } while (!__all_sync(0xffffffffu, ok) && ++n < SPIN_LIMIT);
            float4 a = make_float4(0.f, 0.f, 0.f, 0.f);
#pragma unroll
            for (int u = 0; u < 7; u++) {
                a.x += __uint_as_float(t[u].x & ~15u); a.y += __uint_as_float(t[u].y); a.z += __uint_as_float(t[u].z); a.w += __uint_as_float(t[u].w);
            }
            a.x += __shfl_xor_sync(0xffffffffu, a.x, 16); a.y += __shfl_xor_sync(0xffffffffu, a.y, 16);
            a.z += __shfl_xor_sync(0xffffffffu, a.z, 16); a.w += __shfl_xor_sync(0xffffffffu, a.w, 16);
            float4* park = reinterpret_cast<float4*>(smem + OFF_XB) + (lane & 15);
            if (lane < 16) park[aw * 16] = a;
            named_bar<4, 128>();
            if (aw == 0) {
                const float4 p1 = park[16], p2 = park[32], p3 = park[48];
                a.x = (a.x + p1.x) + (p2.x + p3.x); a.y = (a.y + p1.y) + (p2.y + p3.y);
                a.z = (a.z + p1.z) + (p2.z + p3.z); a.w = (a.w + p1.w) + (p2.w + p3.w);
                unsigned u = *reinterpret_cast<volatile unsigned*>(smem + OFF_SEL) >> 16;
                u = (u & 0x8000u) ? (u & 0x7fffu) : (~u & 0xffffu);
                const float sg = rbf(__fdividef(1.0f, 1.0f + __expf(-__uint_as_float(u << 16))));
                const float m = __uint_as_float(rec.x), ri = __uint_as_float(rec.y);
                const uint32_t n0 = norm2(xv.x, m, ri), n1 = norm2(xv.y, m, ri);
                uint2 o;
                o.x = silu2(pack_bf(bf_lo(n0) + rbf(rbf(a.x) * sg), bf_hi(n0) + rbf(rbf(a.y) * sg)));
                o.y = silu2(pack_bf(bf_lo(n1) + rbf(rbf(a.z) * sg), bf_hi(n1) + rbf(rbf(a.w) * sg)));
                if (lane < 16) *reinterpret_cast<uint2*>(smem + OFF_H + col * 2) = o;
                __syncwarp();
                if (lane == 0) { mbar_arrive(BAR(B_UPD)); PROF_T(12); }
            }
        }
    } else {
        asm volatile("setmaxnreg.inc.sync.aligned.u32 %0;" ::"n"(CONS_REGS));
        CLUSTER_WAIT();
        const int wg = warp >> 2, wq = warp & 3;
        const int wt = tid & 127;
        float acc[128];
        const uint32_t fL = BAR(B_FL + 4 * wg), eL = BAR(B_EL + 4 * wg);
        const uint32_t dL = desc_lo(SB0 + OFF_L, 16) + wg * 4096;
        constexpr uint32_t dS = desc_lo(SB0 + OFF_S, 16);
        constexpr uint32_t SL = SLOT >> 4;
#define RELEASE(ls, ss) do { if (wt == 0) { mbar_arrive(eL + 8u * (ls)); mbar_arrive(BAR(B_ES + (ss))); } } while (0)
#define WAIT_FULL(ls, lph, ss, sph) do { mbar_wait(BAR(B_FS + (ss)), sph); mbar_wait(fL + 8u * (ls), lph); } while (0)
#define TURN() do { if (wg) named_bar<6, 256>(); else named_bar<5, 256>(); } while (0)
#define PASS() do { if (wg) named_arrive<5, 256>(); else named_arrive<6, 256>(); } while (0)
#define WG_BAR() do { if (wg) named_bar<2, 128>(); else named_bar<1, 128>(); } while (0)
        uint32_t held = 0, tgt = 0;
#define PEEK() do { if (wg == 0) tgt = *reinterpret_cast<volatile uint32_t*>(smem + OFF_SEL + 8); } while (0)
#define HOLD(step) do { if (tgt != held) { held = tgt; sleep_until(tgt + 1024u * (step) - 100u); \
                int n = 0; while ((int)(clock32() - tgt - 1024u * (step)) < 0 && ++n < SPIN_LIMIT) {} } } while (0)
        if (wg == 1) PASS();

#define MMA1_P(O, s, first, pass) do { _Pragma("unroll") for (int kk = 0; kk < 4; kk++) { if (kk == PK && (pass)) PASS(); \
            wgmma128<O, 0>(acc, dL + (s) * SL + kk * 2 + (O) * 8, dS + DSLOT(s) * SL + kk * 2, !((first) && kk == 0)); } \
            if (PK == 4 && (pass)) PASS(); } while (0)
#define MMA1_H(O, s, first) MMA1_P(O, s, first, false)
#define WAIT1(s, ph) WAIT_FULL(s, ph, DSLOT(s), ph)
#define PROBE(ls, lph, ss, sph) (mbar_test(BAR(B_FS + (ss)), sph) & mbar_test(fL + 8u * (ls), lph))
#define REL1(s) RELEASE(s, DSLOT(s))
#pragma unroll 1
        for (int it = 0; it < 12; it++) {
            const int s = it & 3;
            const bool ok = PROBE(s, (it >> 2) & 1, DSLOT(s), (it >> 2) & 1);
            PEEK();
            if (it) { wg_wait<0>(); REL1((it - 1) & 3); }
            if (!ok) WAIT1(s, (it >> 2) & 1);
            HOLD(it);
            TURN();
            wg_fence(); MMA1_H(0, s, it == 0); MMA1_P(64, s, it == 0, true); wg_commit();
            if (it == QJ && tid == 0) { mbar_arrive(BAR(B_QUIET)); PROF_T(15); }
            if (it == 0 && tid == 0) PROF_T(16);
        }
        TS(12);
        float rs[4] = {};
        uint32_t nm[8] = {};
#define GET_STATS() do { mbar_wait(BAR(B_STATS), 0); \
            const int p0 = POS(wg * 128 + wq * 16 + (lane >> 2));                   \
            const uint32_t msk = (lane & 3) == 0 ? 0xffffffffu : (lane & 3) == 1 ? 0x0000ffffu : 0u; \
            _Pragma("unroll") for (int i = 0; i < 4; i++) { \
                const int p = p0 + (i & 1) * 2 + (i >> 1) * 64; \
                rs[i] = *reinterpret_cast<const float*>(smem + OFF_RSTD + p * 4); \
                const uint32_t m = *reinterpret_cast<const uint16_t*>(smem + OFF_MEAN + p * 2) ^ 0x8000u; \
                nm[i + (i & 2)] = (m | (m << 16)) & msk; \
            } } while (0)
        const bool early = wg || __all_sync(0xffffffffu, mbar_test(BAR(B_STATS), 0));
        if (early && !wg) GET_STATS();
        WAIT1(0, 1);
        TS(13);
        wg_wait<0>(); REL1(3);
        if (wg) GET_STATS();
        TS(14);
        TURN();
        wg_fence();
        MMA1_H(0, 0, false);
        if (QJ == 12 && tid == 0) { mbar_arrive(BAR(B_QUIET)); PROF_T(15); }
        WAIT1(1, 1); wg_fence(); MMA1_H(0, 1, false);
        WAIT1(2, 1); wg_fence(); MMA1_H(0, 2, false); wg_commit();
        if (!early) GET_STATS();
        asm volatile("" : "+r"(nm[0]), "+r"(nm[1]), "+r"(nm[2]), "+r"(nm[3]), "+r"(nm[4]), "+r"(nm[5]), "+r"(nm[6]), "+r"(nm[7])::"memory");
        wg_fence();
        wgmma128_rs<64>(acc, nm + 4, (SB0 + OFF_RS) >> 4);
        wgmma128_rs<0>(acc, nm, (SB0 + OFF_RS) >> 4);
        WAIT1(3, 1); wg_fence(); MMA1_P(0, 3, false, true);
        wg_commit();
        const int mrow = wq * 16 + ((lane >> 3) & 1) * 8 + (lane & 7);
#define EPI1(O, slot, FREE) do { const uint32_t dst = sb + OFF_S + (slot) * SLOT + mrow * 128; \
            uint32_t pk[32]; \
            _Pragma("unroll") for (int i = 0; i < 32; i += 4) { \
                _Pragma("unroll") for (int k = 0; k < 4; k++) \
                    pk[i + k] = pack_bf(acc[(O) + 2 * (i + k)] * rs[(O) / 32 + (k & 1)], acc[(O) + 2 * (i + k) + 1] * rs[(O) / 32 + (k & 1)]); \
                if (i == EF) { FREE; } \
                if (i >= EF) { _Pragma("unroll") for (int v = (i == EF ? 0 : i); v <= i; v += 4) \
                    stmatrix4(dst + ((v >> 4) ^ c ^ 1) * 8192 + ((((v >> 1) & 7) + (lane >> 4)) ^ (lane & 7)) * 16, pk[v], pk[v + 1], pk[v + 2], pk[v + 3]); } } \
            if (!RF) fence_async_smem(); \
            WG_BAR(); \
            if (wt == 0) mbar_arrive(BAR(B_FS + (slot))); } while (0)
        TS(15);
        wg_wait<0>();
        fence_regs64<0>(acc);
        TS(16);
        {
            constexpr int EF = 0;
            EPI1(0, wg, if (wg) mbar_wait(BAR(B_FS), 0));
        }
        TS(17);
        TURN();
        wg_fence();
        MMA1_H(64, 0, false); wg_commit();
        MMA1_H(64, 1, false); wg_commit();
        MMA1_H(64, 2, false); wg_commit();
        wg_wait<2>(); REL1(0);
        MMA1_P(64, 3, false, true); wg_commit();
        TS(18);
        wg_wait<2>(); REL1(1);
        if (RF) { mbar_wait(BAR(B_FS), 0); mbar_wait(BAR(B_FS + 1), 0); fence_async_smem(); }
        wg_wait<1>(); REL1(2);
        wg_wait<0>(); REL1(3);
        fence_regs64<64>(acc);
        TS(19);
        {
            constexpr int EF = EF2;
            EPI1(64, 2 + wg, mbar_wait(BAR(B_ES + 2 + wg), 1));
        }
        TS(20);

        float ac2[128];
#define MMA2_P(O, ls, ss, first, pass) do { _Pragma("unroll") for (int kk = 0; kk < 4; kk++) { if (kk == PK && (pass)) PASS(); \
            wgmma128<O, 1>(ac2, dS + (ss) * SL + kk * 128 + (O) * 8, dL + (ls) * SL + kk * 2, !((first) && kk == 0)); } \
            if (PK == 4 && (pass)) PASS(); } while (0)
#define MMA2_H(O, ls, ss, first) MMA2_P(O, ls, ss, first, false)
#define WAIT2(j) WAIT_FULL((j) & 3, ((j) >> 2) & 1, PSLOT(j), PPAR(j))
#define MMA2(j, pass) do { wg_fence(); MMA2_H(0, (j) & 3, PSLOT(j), (j) == 0); MMA2_P(64, (j) & 3, PSLOT(j), (j) == 0, pass); wg_commit(); } while (0)
#define REL2(j) RELEASE((j) & 3, PSLOT(j))
        if (GOJ == 0 && wt == 0) mbar_arrive(BAR(B_GO));
        WAIT2(0); TURN(); MMA2(0, false);
        WAIT2(1); MMA2(1, true);
        TS(21);
        wg_wait<1>(); REL2(0);
        if (RF) { mbar_wait(BAR(B_FS + 2), 0); mbar_wait(BAR(B_FS + 3), 0); fence_async_smem(); }
        TS(22);
        {
            uint32_t sp = 1;
#pragma unroll 1
            for (int j = 2; j < XJ; j++) {
                const uint32_t ss = PSLOT(j);
                const bool ok = PROBE(j & 3, (j >> 2) & 1, ss, PPAR(j));
                PEEK();
                wg_wait<0>(); RELEASE((j - 1) & 3, sp);
                if (!ok) WAIT_FULL(j & 3, (j >> 2) & 1, ss, PPAR(j));
                HOLD(16 + j);
                TURN();
                wg_fence(); MMA2_H(0, j & 3, ss, false); MMA2_P(64, j & 3, ss, false, true); wg_commit();
                if (j == GOJ && wt == 0) { mbar_arrive(BAR(B_GO)); if (wg == 0) PROF_T(19); }
                sp = ss;
            }
        }
        if (tid == 0) PROF_T(20);
        uint32_t gt[32];
        const uint32_t xrow = sb + OFF_S + (2 + wg) * SLOT + ((lane >> 4) * 8 + (lane & 7)) * 128 + (((2 * wq + ((lane >> 3) & 1)) ^ (lane & 7)) << 4);
        const uint32_t gsign = c ? 0x80008000u : 0u;
        mbar_wait(BAR(B_FS + 2 + wg), 1);
        mbar_wait(BAR(B_SEL), 0);
        const int sel = 0xffff - (int)(*reinterpret_cast<volatile unsigned*>(smem + OFF_SEL) & 0xffffu);
        bool own = (sel >> 7) == 2 * g + wg;
#define PATCH() do { own = false; \
            const uint32_t v0 = *reinterpret_cast<const uint16_t*>(smem + OFF_H + (wq * 16 + (lane >> 2)) * 2) ^ gsign; \
            const uint32_t v1 = *reinterpret_cast<const uint16_t*>(smem + OFF_H + (wq * 16 + (lane >> 2)) * 2 + 16) ^ gsign; \
            const uint32_t pick = (lane & 3) != ((sel >> 1) & 3) ? 0x3210u : (sel & 1) ? 0x5410u : 0x3254u; \
            _Pragma("unroll") for (int i = 0; i < 16; i++) { \
                const uint32_t m = ((sel >> 3) & 15) == i ? pick : 0x3210u; \
                gt[2 * i] = __byte_perm(gt[2 * i], v0, m); \
                gt[2 * i + 1] = __byte_perm(gt[2 * i + 1], v1, m); \
            } } while (0)
#pragma unroll
        for (int v = 0; v < 28 - XJ; v++) {
            WAIT2(XJ + v); wg_wait<0>(); REL2(XJ + v - 1); TURN(); MMA2(XJ + v, true);
            constexpr int NS = 8 / (28 - XJ);
#pragma unroll
            for (int u = v * NS; u < (v + 1) * NS; u++) {
                uint32_t* o = &gt[4 * u];
                ldmatrix4t(xrow + u * 2048, o[0], o[1], o[2], o[3]);
                const float4 r4 = *reinterpret_cast<const float4*>(smem + OFF_RSTD + (wg * 128 + u * 16 + (lane & 3) * 4) * 4);
                const uint2 m2 = *reinterpret_cast<const uint2*>(smem + OFF_MEAN + (wg * 128 + u * 16 + (lane & 3) * 4) * 2);
                o[0] = gate2(o[0], m2.x, r4.x, r4.y) ^ gsign;
                o[1] = gate2(o[1], m2.x, r4.x, r4.y) ^ gsign;
                o[2] = gate2(o[2], m2.y, r4.z, r4.w) ^ gsign;
                o[3] = gate2(o[3], m2.y, r4.z, r4.w) ^ gsign;
                asm volatile("st.shared.v2.u32 [%0], {%1,%2};" ::"r"(sb + OFF_SEL + 16), "r"(o[0] ^ o[1]), "r"(o[2] ^ o[3]) : "memory");
            }
        }
        if (tid == 0) PROF_T(21);
        WAIT2(28);
        wg_wait<0>(); REL2(27);
        if (own && mbar_test(BAR(B_UPD), 0)) PATCH();
        TS(0);
        TURN();
        wg_fence(); MMA2_H(0, 0, PSLOT(28), false); wg_commit();
        if (wg == 0 || !ASYM) { wg_fence(); MMA2_H(64, 0, PSLOT(28), false); wg_commit(); }
        WAIT2(29); wg_fence(); MMA2_H(0, 1, PSLOT(29), false); wg_commit();
        WAIT2(30); wg_fence(); MMA2_H(0, 2, PSLOT(30), false); wg_commit();
        wg_wait<2>();
        if (tid == 0) mbar_arrive_cluster(mapa(BAR(B_RDY), c ^ 1));
        WAIT2(31); wg_fence(); MMA2_H(0, 3, PSLOT(31), false); wg_commit();
        TS(1);
#define KEEP(i) wgmma128<64, 1>(ac2, dS + PSLOT(29 + ((i) >> 2)) * SL + ((i) & 3) * 128 + 512, dL + (1 + ((i) >> 2)) * SL + ((i) & 3) * 2, 1)
        wg_fence();
#pragma unroll
        for (int i = 0; i < KQ; i++) KEEP(i);
        wg_commit();
        mbar_wait(BAR(B_RDY + wg), 0);
        wg_wait<1>();
        fence_regs64<0>(ac2);
        TS(2);
        wg_fence();
        {
            const uint32_t dst = mapa(sb + OFF_L + wg * SLOT + wt * 16, c ^ 1), rb = mapa(BAR(B_RECV + wg), c ^ 1);
#pragma unroll
            for (int v = 0; v < 8; v++) {
                if (KQ + v < 12) KEEP(KQ + v);
                if (KQ + v == 11) { wg_commit(); if (wg == 0) PASS(); }
                st_async4(dst + v * 2048, pack_bf(ac2[8 * v + 0], ac2[8 * v + 1]), pack_bf(ac2[8 * v + 2], ac2[8 * v + 3]),
                          pack_bf(ac2[8 * v + 4], ac2[8 * v + 5]), pack_bf(ac2[8 * v + 6], ac2[8 * v + 7]), rb);
            }
        }
        if (wg == 1 && ASYM) { wg_fence(); MMA2_H(64, 0, PSLOT(28), false); wg_commit(); }
        TS(3);
        uint32_t xr[32];
#pragma unroll
        for (int v = 0; v < 8; v++) ldmatrix4t(xrow + v * 2048, xr[4 * v], xr[4 * v + 1], xr[4 * v + 2], xr[4 * v + 3]);
        if (wg == 0) {
            wg_wait<0>();
            if (wt == 0) mbar_arrive_cluster(mapa(BAR(B_RDY + 1), c ^ 1));
        }
        TS(4);
        if (own) { mbar_wait(BAR(B_UPD), 0); PATCH(); }
        TS(5);
        mbar_wait_cluster(BAR(B_RECV + wg), 0);
        TS(6);
        uint4 rv[8];
#pragma unroll
        for (int v = 0; v < 8; v++) rv[v] = *reinterpret_cast<const uint4*>(smem + OFF_L + wg * SLOT + v * 2048 + wt * 16);
        wg_wait<0>();
        fence_regs64<64>(ac2);
        TS(7);
#pragma unroll
        for (int v = 0; v < 8; v++) {
            const float* a = &ac2[64 + 8 * v];
            stmatrix4t(xrow + v * 2048,
                       bfma2(bsub2(pack_bf(a[0], a[1]), rv[v].x), gt[4 * v + 0], xr[4 * v + 0]),
                       bfma2(bsub2(pack_bf(a[2], a[3]), rv[v].y), gt[4 * v + 1], xr[4 * v + 1]),
                       bfma2(bsub2(pack_bf(a[4], a[5]), rv[v].z), gt[4 * v + 2], xr[4 * v + 2]),
                       bfma2(bsub2(pack_bf(a[6], a[7]), rv[v].w), gt[4 * v + 3], xr[4 * v + 3]));
            if (v % OP == OP - 1) {
                __syncwarp();
                if (lane == 0) mbar_arrive(BAR((v / OP ? B_STATS : B_OUT) + wg));
                if (v == OP - 1) TS(8);
                if (v == 7) TS(9);
            }
        }
    }
}

typedef CUresult (*EncodeFn)(CUtensorMap*, CUtensorMapDataType, cuuint32_t, void*, const cuuint64_t*, const cuuint64_t*,
                             const cuuint32_t*, const cuuint32_t*, CUtensorMapInterleave, CUtensorMapSwizzle,
                             CUtensorMapL2promotion, CUtensorMapFloatOOBfill);

void make_map(EncodeFn fn, CUtensorMap* tm, const void* p, uint64_t rows, uint64_t cols, uint32_t box_rows,
              CUtensorMapL2promotion promo = CU_TENSOR_MAP_L2_PROMOTION_L2_128B) {
    cuuint64_t dims[2] = {cols, rows};
    cuuint64_t strides[1] = {cols * 2};
    cuuint32_t box[2] = {64, box_rows};
    cuuint32_t es[2] = {1, 1};
    fn(tm, CU_TENSOR_MAP_DATA_TYPE_BFLOAT16, 2, const_cast<void*>(p), dims, strides, box, es, CU_TENSOR_MAP_INTERLEAVE_NONE,
       CU_TENSOR_MAP_SWIZZLE_128B, promo, CU_TENSOR_MAP_FLOAT_OOB_FILL_NONE);
}

}

extern "C" void kernel_launch(void* const* d_in, const int* in_sizes, int n_in, void* d_out, int out_size) {
    (void)in_sizes; (void)n_in; (void)out_size;
    static EncodeFn fn = nullptr;
    if (!fn) {
        void* p = nullptr;
        cudaDriverEntryPointQueryResult q;
        cudaGetDriverEntryPoint("cuTensorMapEncodeTiled", &p, cudaEnableDefault, &q);
        fn = (EncodeFn)p;
        cudaFuncSetAttribute(fnet_fused_kernel, cudaFuncAttributeMaxDynamicSharedMemorySize, SMEM_BYTES);
    }
    CUtensorMap tx, tdre, tdim, tcre, tcim, tout;
    make_map(fn, &tx, d_in[0], S_, D_, 128, PRX);
    make_map(fn, &tcre, d_in[1], S_, S_, 128, PRC);
    make_map(fn, &tcim, d_in[2], S_, S_, 128, PRC);
    make_map(fn, &tdre, d_in[3], D_, D_, 128, PRD);
    make_map(fn, &tdim, d_in[4], D_, D_, 128, PRD);
    make_map(fn, &tout, d_out, S_, D_, 16 * OP);
    Params P;
    P.x = (const __nv_bfloat16*)d_in[0];
    P.dre = (const __nv_bfloat16*)d_in[3];
    P.dim = (const __nv_bfloat16*)d_in[4];
    P.wr = (const __nv_bfloat16*)d_in[6];
    P.wg = (const __nv_bfloat16*)d_in[7];
    P.wu = (const __nv_bfloat16*)d_in[8];
    P.wd = (const __nv_bfloat16*)d_in[9];
    P.zero = 0;
    fnet_fused_kernel<<<NCTA, NTHREADS, SMEM_BYTES, cudaStreamPerThread>>>(tx, tdre, tdim, tcre, tcim, tout, P);
}
```

```cpp
#include <cuda_runtime.h>
#include <cuda_bf16.h>
#include <cuda.h>
#include <stdint.h>

#define LDEL 0
#define XS 0x6543
#define GSL 200
#define YNS 0u
#define YLD 1
#define PDEL 2500
#define PGAP 600
#define PK 4
#define ASYM 1
#define RF 1
#define EF2 16
#define NLATE 1
#define XE 2
#define W0 12
#define PFX 1
#define KQ 5
#define OP 2
#define XJ0 20
#define EGAP1 0
#define EGAP2 0
#define ESTAG 120
#define QJ 10
#define GOJ 2
#define TANH 1
#define SYNCS 0x2200080ull
#define SYNCD 2
#define SYNCCAP 4000u
#define SYNCMIN 24u
#define SYNCLAG 820u
#define QUIET 1
#define PRX CU_TENSOR_MAP_L2_PROMOTION_L2_128B
#define PRD CU_TENSOR_MAP_L2_PROMOTION_L2_128B
#define PRC CU_TENSOR_MAP_L2_PROMOTION_L2_128B
#define SLEEP_NS 200
#define PROD_REGS 32
#define CONS_REGS 184

namespace {

constexpr int S_ = 2048, D_ = 1024, F_ = 3584;
constexpr int NCTA = 128;
constexpr int XJ = XJ0;
constexpr uint32_t SLOT = 16384;
constexpr uint32_t OFF_L = 0;
constexpr uint32_t OFF_S = 8 * SLOT;
constexpr uint32_t OFF_RS = OFF_S + SLOT;
constexpr uint32_t OFF_BAR = 14 * SLOT;
constexpr uint32_t OFF_SEL = OFF_BAR + 360;
constexpr uint32_t OFF_RSTD = OFF_BAR + 384;
constexpr uint32_t OFF_MEAN = OFF_RSTD + 1024;
constexpr uint32_t OFF_XB = OFF_MEAN + 512;
constexpr uint32_t OFF_H = OFF_XB + 1024;
constexpr uint32_t SMEM_BYTES = OFF_H + 128;
constexpr uint32_t OFF_TS = OFF_XB + 512;
constexpr uint32_t SB0 = 1024;
constexpr int NTHREADS = 512;
static_assert(SMEM_BYTES <= 232448, "smem");

enum { B_FS = 0, B_ES = 6, B_FL = 12, B_EL = 20, B_SRD = 28, B_RECV = 30  , B_RDY = 34, B_STATS = 36, B_LST = 37, B_UPD = 38,
       B_QUIET = 39, B_GO = 40, B_PEER = 41, B_SEL = 42, B_H = 43, B_COUNT = 44 };
static_assert(B_COUNT * 8 <= 360, "barriers");

__device__ __align__(1024) uint8_t g_ab[16u * 32u * SLOT];
__device__ __align__(128) uint4 g_part[56 * (D_ / 4)];
__device__ __align__(128) uint4 g_stat[S_];
__device__ __align__(128) uint4 g_rs[D_];
__device__ __align__(128) unsigned long long g_key[NCTA];
__device__ __align__(128) unsigned long long g_flag[16 * 16];
__device__ __align__(128) unsigned long long g_sync[16 * 16];
__device__ __align__(128) unsigned g_epoch[NCTA];
#define PROF_T(i) do {} while (0)
#define TRACE(i) do {} while (0)
#define PROF_G(i) do {} while (0)
#define TS(i) do {} while (0)
#define FINISH(wg) bulk_wait_read<0>()

#define MARK(it, ph) do {} while (0)

__device__ __forceinline__ uint32_t smem_u32(const void* p) { return (uint32_t)__cvta_generic_to_shared(p); }
__device__ __forceinline__ void mbar_init(uint32_t bar, uint32_t cnt) {
    asm volatile("mbarrier.init.shared::cta.b64 [%0], %1;" ::"r"(bar), "r"(cnt) : "memory");
}
__device__ __forceinline__ bool mbar_try(uint32_t bar, uint32_t parity) {
    uint32_t ok;
    asm volatile("{\n.reg .pred p;\nmbarrier.try_wait.parity.shared::cta.b64 p, [%1], %2;\nselp.u32 %0, 1, 0, p;\n}"
                 : "=r"(ok) : "r"(bar), "r"(parity) : "memory");
    return ok;
}
__device__ __forceinline__ bool mbar_test(uint32_t bar, uint32_t parity) {
    uint32_t ok;
    asm volatile("{\n.reg .pred p;\nmbarrier.test_wait.parity.shared::cta.b64 p, [%1], %2;\nselp.u32 %0, 1, 0, p;\n}"
                 : "=r"(ok) : "r"(bar), "r"(parity) : "memory");
    return ok;
}
__device__ __forceinline__ bool mbar_try_cluster(uint32_t bar, uint32_t parity) {
    uint32_t ok;
    asm volatile("{\n.reg .pred p;\nmbarrier.try_wait.parity.acquire.cluster.shared::cta.b64 p, [%1], %2;\nselp.u32 %0, 1, 0, p;\n}"
                 : "=r"(ok) : "r"(bar), "r"(parity) : "memory");
    return ok;
}
constexpr int SPIN_LIMIT = 1 << 20;
__device__ __forceinline__ void mbar_wait(uint32_t bar, uint32_t parity) {
    if (mbar_try(bar, parity)) return;
    int n = 0;
    while (!mbar_try(bar, parity) && ++n < SPIN_LIMIT) {}
}
__device__ __forceinline__ void mbar_wait_cluster(uint32_t bar, uint32_t parity) {
    int n = 0;
    while (!mbar_try_cluster(bar, parity) && ++n < SPIN_LIMIT) {}
}
__device__ __forceinline__ void mbar_wait_sleep(uint32_t bar, uint32_t parity) {
    int n = 0;
    while (!mbar_try(bar, parity) && ++n < SPIN_LIMIT) __nanosleep(SLEEP_NS);
}
__device__ __forceinline__ void mbar_arrive(uint32_t bar) {
    asm volatile("mbarrier.arrive.shared::cta.b64 _, [%0];" ::"r"(bar) : "memory");
}
__device__ __forceinline__ void mbar_arrive_cluster(uint32_t cluster_bar) {
    asm volatile("mbarrier.arrive.shared::cluster.b64 _, [%0];" ::"r"(cluster_bar) : "memory");
}
__device__ __forceinline__ void mbar_expect_tx(uint32_t bar, uint32_t bytes) {
    asm volatile("mbarrier.arrive.expect_tx.shared::cta.b64 _, [%0], %1;" ::"r"(bar), "r"(bytes) : "memory");
}
__device__ __forceinline__ bool elect_one() {
    uint32_t p;
    asm volatile("{\n.reg .pred p;\nelect.sync _|p, 0xffffffff;\nselp.u32 %0, 1, 0, p;\n}" : "=r"(p));
    return p;
}
__device__ __forceinline__ uint32_t mapa(uint32_t addr, uint32_t rank) {
    uint32_t r;
    asm("mapa.shared::cluster.u32 %0, %1, %2;" : "=r"(r) : "r"(addr), "r"(rank));
    return r;
}
__device__ __forceinline__ uint32_t clock32() { uint32_t t; asm volatile("mov.u32 %0, %%clock;" : "=r"(t)); return t; }
__device__ __forceinline__ void sleep_until(uint32_t t) {
    int n = 0;
    while ((int)(clock32() - t) < 0 && ++n < SPIN_LIMIT) __nanosleep(20);
}
__device__ __forceinline__ void yield(float last, uint32_t zero) {
    if (YLD) asm volatile("nanosleep.u32 %0;" ::"r"((__float_as_uint(last) & zero) | YNS));
}
template <typename T> __device__ __forceinline__ T* at(T* p, uint32_t bytes) {
    asm("" : "+r"(bytes));
    return reinterpret_cast<T*>(reinterpret_cast<uintptr_t>(p) + bytes);
}
__device__ __forceinline__ void tma_2d(uint32_t dst, const CUtensorMap* tm, int c0, int c1, uint32_t bar) {
    asm volatile("cp.async.bulk.tensor.2d.shared::cluster.global.mbarrier::complete_tx::bytes [%0], [%1, {%3, %4}], [%2];"
                 ::"r"(dst), "l"(tm), "r"(bar), "r"(c0), "r"(c1) : "memory");
}
__device__ __forceinline__ void tma_2d_store(const CUtensorMap* tm, int c0, int c1, uint32_t src) {
    asm volatile("cp.async.bulk.tensor.2d.global.shared::cta.bulk_group [%0, {%2, %3}], [%1];"
                 ::"l"(tm), "r"(src), "r"(c0), "r"(c1) : "memory");
}
__device__ __forceinline__ void bulk_g2s(uint32_t dst, const void* src, uint32_t bytes, uint32_t bar) {
    asm volatile("cp.async.bulk.shared::cluster.global.mbarrier::complete_tx::bytes [%0], [%1], %2, [%3];"
                 ::"r"(dst), "l"(src), "r"(bytes), "r"(bar) : "memory");
}
__device__ __forceinline__ void bulk_s2g(void* dst, uint32_t src, uint32_t bytes) {
    asm volatile("cp.async.bulk.global.shared::cta.bulk_group [%0], [%1], %2;" ::"l"(dst), "r"(src), "r"(bytes) : "memory");
}
__device__ __forceinline__ void st_async4(uint32_t dst, uint32_t a, uint32_t b, uint32_t c, uint32_t d, uint32_t bar) {
    asm volatile("st.async.weak.shared::cluster.mbarrier::complete_tx::bytes.v4.b32 [%0], {%1,%2,%3,%4}, [%5];"
                 ::"r"(dst), "r"(a), "r"(b), "r"(c), "r"(d), "r"(bar) : "memory");
}
__device__ __forceinline__ void bulk_commit() { asm volatile("cp.async.bulk.commit_group;" ::: "memory"); }
template <int N> __device__ __forceinline__ void bulk_wait_read() { asm volatile("cp.async.bulk.wait_group.read %0;" ::"n"(N) : "memory"); }
template <int N> __device__ __forceinline__ void bulk_wait() { asm volatile("cp.async.bulk.wait_group %0;" ::"n"(N) : "memory"); }
__device__ __forceinline__ void fence_async_smem() { asm volatile("fence.proxy.async.shared::cta;" ::: "memory"); }
__device__ __forceinline__ void fence_async_global() { asm volatile("fence.proxy.async.global;" ::: "memory"); }
__device__ __forceinline__ void prefetch_tmap(const CUtensorMap* tm) {
    asm volatile("prefetch.tensormap [%0];" ::"l"(tm) : "memory");
}
__device__ __forceinline__ unsigned long long ld_acquire64(const unsigned long long* p) {
    unsigned long long v; asm volatile("ld.acquire.gpu.global.u64 %0, [%1];" : "=l"(v) : "l"(p) : "memory"); return v;
}
__device__ __forceinline__ unsigned load_epoch(int b) {
    unsigned v; asm volatile("ld.global.u32 %0, [%1];" : "=r"(v) : "l"(at(g_epoch, b * 4)) : "memory"); return v + 1;
}
__device__ __forceinline__ unsigned ld_relaxed(const void* p) {
    unsigned v; asm volatile("ld.relaxed.gpu.global.u32 %0, [%1];" : "=r"(v) : "l"(p) : "memory"); return v;
}
__device__ __forceinline__ unsigned long long ld_relaxed64(const unsigned long long* p) {
    unsigned long long v; asm volatile("ld.relaxed.gpu.global.u64 %0, [%1];" : "=l"(v) : "l"(p) : "memory"); return v;
}
__device__ __forceinline__ void red_max64(unsigned long long* p, unsigned long long v) {
    asm volatile("red.relaxed.gpu.global.max.u64 [%0], %1;" ::"l"(p), "l"(v) : "memory");
}
__device__ __forceinline__ uint4 ld_relaxed128(const uint4* p) {
    uint4 v;
    asm volatile("{\n.reg .b128 t;\n.reg .b64 lo, hi;\nld.relaxed.gpu.global.b128 t, [%4];\nmov.b128 {lo, hi}, t;\n"
                 "mov.b64 {%0, %1}, lo;\nmov.b64 {%2, %3}, hi;\n}"
                 : "=r"(v.x), "=r"(v.y), "=r"(v.z), "=r"(v.w) : "l"(p) : "memory");
    return v;
}
__device__ __forceinline__ void st_relaxed128(uint4* p, const uint4& v) {
    asm volatile("{\n.reg .b128 t;\n.reg .b64 lo, hi;\nmov.b64 lo, {%1, %2};\nmov.b64 hi, {%3, %4};\nmov.b128 t, {lo, hi};\n"
                 "st.relaxed.gpu.global.b128 [%0], t;\n}"
                 ::"l"(p), "r"(v.x), "r"(v.y), "r"(v.z), "r"(v.w) : "memory");
}
__device__ __forceinline__ void st_relaxed64(unsigned long long* p, unsigned long long v) {
    asm volatile("st.relaxed.gpu.global.u64 [%0], %1;" ::"l"(p), "l"(v) : "memory");
}
__device__ __forceinline__ void st_release8(void* p, unsigned v) {
    asm volatile("st.release.gpu.global.u8 [%0], %1;" ::"l"(p), "r"(v) : "memory");
}
__device__ __forceinline__ uint64_t policy_evict_first() {
    uint64_t pol;
    asm("createpolicy.fractional.L2::evict_first.b64 %0, 1.0;" : "=l"(pol));
    return pol;
}
__device__ __forceinline__ uint4 ldg_stream(const void* p, uint64_t pol) {
    uint4 v;
    asm volatile("ld.global.nc.L1::no_allocate.L2::cache_hint.v4.u32 {%0,%1,%2,%3}, [%4], %5;"
                 : "=r"(v.x), "=r"(v.y), "=r"(v.z), "=r"(v.w) : "l"(p), "l"(pol));
    return v;
}
template <int ID, int N> __device__ __forceinline__ void named_arrive() { asm volatile("bar.arrive %0, %1;" ::"n"(ID), "n"(N) : "memory"); }
template <int ID, int N> __device__ __forceinline__ void named_bar() { asm volatile("bar.sync %0, %1;" ::"n"(ID), "n"(N) : "memory"); }

__device__ __forceinline__ float bf_lo(uint32_t u) { return __uint_as_float(u << 16); }
__device__ __forceinline__ float bf_hi(uint32_t u) { return __uint_as_float(u & 0xffff0000u); }
__device__ __forceinline__ uint32_t pack_bf(float lo, float hi) {
    uint32_t r; asm("cvt.rn.bf16x2.f32 %0, %1, %2;" : "=r"(r) : "f"(hi), "f"(lo)); return r;
}
__device__ __forceinline__ float rbf(float v) { return __uint_as_float(pack_bf(0.f, v)); }
__device__ __forceinline__ float sqrt_f(float v) { float r; asm("sqrt.approx.f32 %0, %1;" : "=f"(r) : "f"(v)); return r; }
__device__ __forceinline__ float rcp_f(float v) { float r; asm("rcp.approx.f32 %0, %1;" : "=f"(r) : "f"(v)); return r; }
__device__ __forceinline__ float silu_f(float z) { return __fdividef(z, 1.0f + __expf(-z)); }
__device__ __forceinline__ uint32_t bsub2(uint32_t a, uint32_t b) {
    uint32_t r; asm("sub.rn.bf16x2 %0, %1, %2;" : "=r"(r) : "r"(a), "r"(b)); return r;
}
__device__ __forceinline__ uint32_t bfma2(uint32_t a, uint32_t b, uint32_t c) {
    uint32_t r; asm("fma.rn.bf16x2 %0, %1, %2, %3;" : "=r"(r) : "r"(a), "r"(b), "r"(c)); return r;
}
__device__ __forceinline__ uint32_t norm2(uint32_t xv, float m, float rinv) {
    uint32_t t = pack_bf(bf_lo(xv) - m, bf_hi(xv) - m);
    return pack_bf(bf_lo(t) * rinv, bf_hi(t) * rinv);
}
__device__ __forceinline__ float gate1(float z) {
    if (TANH) {
        float t;
        const float h = 0.5f * z;
        asm("tanh.approx.f32 %0, %1;" : "=f"(t) : "f"(h));
        return fmaf(h, t, h);
    }
    float e, r;
    asm("ex2.approx.ftz.f32 %0, %1;" : "=f"(e) : "f"(z * -1.4426950408889634f));
    asm("rcp.approx.ftz.f32 %0, %1;" : "=f"(r) : "f"(1.0f + e));
    return z * r;
}
__device__ __forceinline__ uint32_t gate2(uint32_t xv, uint32_t mean2, float r0, float r1) {
    const uint32_t t = bsub2(xv, mean2);
    return pack_bf(gate1(bf_lo(t) * r0), gate1(bf_hi(t) * r1));
}
__device__ __forceinline__ uint32_t silu2(uint32_t z) { return pack_bf(silu_f(bf_lo(z)), silu_f(bf_hi(z))); }

__device__ __forceinline__ void stmatrix4(uint32_t addr, uint32_t r0, uint32_t r1, uint32_t r2, uint32_t r3) {
    asm volatile("stmatrix.sync.aligned.m8n8.x4.shared.b16 [%0], {%1,%2,%3,%4};"
                 ::"r"(addr), "r"(r0), "r"(r1), "r"(r2), "r"(r3));
}
__device__ __forceinline__ void stmatrix4t(uint32_t addr, uint32_t r0, uint32_t r1, uint32_t r2, uint32_t r3) {
    asm volatile("stmatrix.sync.aligned.m8n8.x4.trans.shared.b16 [%0], {%1,%2,%3,%4};"
                 ::"r"(addr), "r"(r0), "r"(r1), "r"(r2), "r"(r3));
}
__device__ __forceinline__ void ldmatrix4t(uint32_t addr, uint32_t& r0, uint32_t& r1, uint32_t& r2, uint32_t& r3) {
    asm volatile("ldmatrix.sync.aligned.m8n8.x4.trans.shared.b16 {%0,%1,%2,%3}, [%4];"
                 : "=r"(r0), "=r"(r1), "=r"(r2), "=r"(r3) : "r"(addr));
}

__device__ __forceinline__ void wg_fence() { asm volatile("wgmma.fence.sync.aligned;" ::: "memory"); }
__device__ __forceinline__ void wg_commit() { asm volatile("wgmma.commit_group.sync.aligned;" ::: "memory"); }
template <int N> __device__ __forceinline__ void wg_wait() { asm volatile("wgmma.wait_group.sync.aligned %0;" ::"n"(N) : "memory"); }

__host__ __device__ constexpr uint32_t desc_lo(uint32_t addr, uint32_t lbo) { return ((addr & 0x3FFFF) >> 4) | ((lbo >> 4) << 16); }
#define DESC_HI "0x40000040"

#define R8(a, o) "+f"(a[(o) + 0]), "+f"(a[(o) + 1]), "+f"(a[(o) + 2]), "+f"(a[(o) + 3]), \
                 "+f"(a[(o) + 4]), "+f"(a[(o) + 5]), "+f"(a[(o) + 6]), "+f"(a[(o) + 7])
#define R64(a, o) R8(a, (o) + 0), R8(a, (o) + 8), R8(a, (o) + 16), R8(a, (o) + 24), \
                  R8(a, (o) + 32), R8(a, (o) + 40), R8(a, (o) + 48), R8(a, (o) + 56)

template <int O, int TA>
__device__ __forceinline__ void wgmma128(float (&a)[128], uint32_t da, uint32_t db, int scale_d) {
    asm volatile(
        "{\n.reg .pred p;\n.reg .b64 da, db;\nsetp.ne.b32 p, %66, 0;\n"
        "mov.b64 da, {%64, " DESC_HI "};\nmov.b64 db, {%65, " DESC_HI "};\n"
        "wgmma.mma_async.sync.aligned.m64n128k16.f32.bf16.bf16 "
        "{%0,%1,%2,%3,%4,%5,%6,%7,%8,%9,%10,%11,%12,%13,%14,%15,"
        "%16,%17,%18,%19,%20,%21,%22,%23,%24,%25,%26,%27,%28,%29,%30,%31,"
        "%32,%33,%34,%35,%36,%37,%38,%39,%40,%41,%42,%43,%44,%45,%46,%47,"
        "%48,%49,%50,%51,%52,%53,%54,%55,%56,%57,%58,%59,%60,%61,%62,%63},"
        "da, db, p, 1, 1, %67, 0;\n}"
        : R64(a, O)
        : "r"(da), "r"(db), "r"(scale_d), "n"(TA));
}
template <int O>
__device__ __forceinline__ void wgmma128_rs(float (&a)[128], const uint32_t* f, uint32_t db) {
    asm volatile(
        "{\n.reg .b64 db;\nmov.b64 db, {%68, 8};\n"
        "wgmma.mma_async.sync.aligned.m64n128k16.f32.bf16.bf16 "
        "{%0,%1,%2,%3,%4,%5,%6,%7,%8,%9,%10,%11,%12,%13,%14,%15,"
        "%16,%17,%18,%19,%20,%21,%22,%23,%24,%25,%26,%27,%28,%29,%30,%31,"
        "%32,%33,%34,%35,%36,%37,%38,%39,%40,%41,%42,%43,%44,%45,%46,%47,"
        "%48,%49,%50,%51,%52,%53,%54,%55,%56,%57,%58,%59,%60,%61,%62,%63},"
        "{%64, %65, %66, %67}, db, 1, 1, 1, 0;\n}"
        : R64(a, O)
        : "r"(f[0]), "r"(f[1]), "r"(f[2]), "r"(f[3]), "r"(db));
}
template <int O>
__device__ __forceinline__ void fence_regs64(float (&a)[128]) {
    asm volatile("" : R64(a, O)::"memory");
}

struct Params {
    const __nv_bfloat16* x;
    const __nv_bfloat16* dre;
    const __nv_bfloat16* dim;
    const __nv_bfloat16* wr;
    const __nv_bfloat16* wg;
    const __nv_bfloat16* wu;
    const __nv_bfloat16* wd;
    uint32_t zero;
#define AB g_ab
};

__device__ __forceinline__ float warp_sum(float v) {
#pragma unroll
    for (int o = 16; o; o >>= 1) v += __shfl_xor_sync(0xffffffffu, v, o);
    return v;
}
__device__ __forceinline__ void fma8(float* acc, const uint4& w, float s) {
    acc[0] += s * bf_lo(w.x); acc[1] += s * bf_hi(w.x); acc[2] += s * bf_lo(w.y); acc[3] += s * bf_hi(w.y);
    acc[4] += s * bf_lo(w.z); acc[5] += s * bf_hi(w.z); acc[6] += s * bf_lo(w.w); acc[7] += s * bf_hi(w.w);
}
__device__ __forceinline__ int POS(int t) { return (t & ~15) | ((t & 6) << 1) | ((t & 8) >> 2) | (t & 1); }
__host__ __device__ constexpr int PSLOT(int j) { return j < 4 ? j : (j & 1) + ((j & 2) ? 0 : 4); }
__host__ __device__ constexpr int PPAR(int j) { return j < 4 ? 0 : ((j >> 2) ^ (j >> 1) ^ 1) & 1; }
__host__ __device__ constexpr int DSLOT(int it) { return (it & 3) + 2; }
__device__ __forceinline__ int SREC(int t) { return (t & ~15) | ((t & 3) << 2) | ((t >> 2) & 3); }
__device__ __forceinline__ int KO(int cl) { return ((cl & 1) << 1) | (cl >> 1); }

__device__ __forceinline__ unsigned long long* sync_words() {
    uint32_t t;
    asm volatile("mov.u32 %0, %%smid;" : "=r"(t));
    t >>= 1;
    const uint32_t u = t - 32;
    return at(g_sync, (t < 32 ? t & 7 : t < 60 ? 8 + u - 7 * ((u * 37) >> 8) : 15) * 128);
}

__global__ void __cluster_dims__(2, 1, 1) __launch_bounds__(NTHREADS, 1)
fnet_fused_kernel(const __grid_constant__ CUtensorMap tm_x, const __grid_constant__ CUtensorMap tm_dre,
                  const __grid_constant__ CUtensorMap tm_dim, const __grid_constant__ CUtensorMap tm_cre,
                  const __grid_constant__ CUtensorMap tm_cim, const __grid_constant__ CUtensorMap tm_out,
                  const Params P) {
    extern __shared__ __align__(1024) uint8_t smem[];
    const unsigned long long tstart = clock64();
    const uint32_t sb = smem_u32(smem);
    const int tid = threadIdx.x, lane = tid & 31;
    const int warp = __shfl_sync(0xffffffffu, tid >> 5, 0);
    const int pr = blockIdx.x >> 1, p7 = ((pr - 36) * 37) >> 8;
    const int c = blockIdx.x & 1;
    const int g = pr < 4 ? 0 : pr < 36 ? (pr - 4) & 7 : pr - 35 - 7 * p7;
    const int r = pr < 4 ? 4 + pr : pr < 36 ? (pr - 4) >> 3 : 4 + p7;
    const int grp = 2 * r + c;
    const int b = g * 16 + grp;
    const uint32_t bar0 = sb + OFF_BAR;
    const uint32_t zero = P.zero;
#define BAR(i) (bar0 + 8u * (i))
#define XBAR(i) (sb + OFF_XB + 64 + 8u * (i))
#define CLUSTER_ARRIVE() asm volatile("barrier.cluster.arrive.relaxed.aligned;" ::: "memory")
#define CLUSTER_WAIT() asm volatile("barrier.cluster.wait.aligned;" ::: "memory")
    if ((sb & 0xffffffu) != SB0) return;

#define LOAD0(it) do { \
            mbar_expect_tx(BAR(B_FS + DSLOT(it)), SLOT); tma_2d(sb + OFF_S + DSLOT(it) * SLOT, tmD, (it) * 64, r * 128, BAR(B_FS + DSLOT(it))); \
            mbar_expect_tx(BAR(B_FL + (it)), SLOT); tma_2d(sb + OFF_L + (it) * SLOT, &tm_x, (it) * 64, g * 256, BAR(B_FL + (it))); \
            mbar_expect_tx(BAR(B_FL + 4 + (it)), SLOT); tma_2d(sb + OFF_L + (4 + (it)) * SLOT, &tm_x, (it) * 64, g * 256 + 128, BAR(B_FL + 4 + (it))); \
        } while (0)
    if (warp == W0) {
        if (elect_one()) {
            const CUtensorMap* tmD = c ? &tm_dim : &tm_dre;
            if (PFX & 2) prefetch_tmap(tmD);
            if (PFX & 1) prefetch_tmap(&tm_x);
            mbar_init(BAR(B_FS + 2), 1); mbar_init(BAR(B_FL), 1); mbar_init(BAR(B_FL + 4), 1);
            asm volatile("fence.mbarrier_init.release.cluster;" ::: "memory");
            LOAD0(0);
        }
        __syncwarp();
    }
    if (warp == 12) {
        if (elect_one()) {
#pragma unroll
            for (int i = 0; i < B_COUNT; i++)
                if (i != B_FS + 2 && i != B_FL && i != B_FL + 4)
                    mbar_init(BAR(i), (i >= B_ES && i < B_FL) || i == B_GO ? 2 : i == B_STATS || i == B_LST ? 4 : 1);
#pragma unroll
            for (int i = 0; i < 12; i++) mbar_init(XBAR(i), 1);
#pragma unroll
            for (int i = 0; i < 4; i++) mbar_expect_tx(BAR(B_RECV + i), SLOT / 2);
            mbar_expect_tx(BAR(B_PEER), 1024); mbar_expect_tx(BAR(B_H), 128);
            *reinterpret_cast<volatile uint32_t*>(smem + OFF_SEL + 8) = 0;
            asm volatile("fence.mbarrier_init.release.cluster;" ::: "memory");
            fence_async_smem();
        }
        __syncwarp();
    }
    CLUSTER_ARRIVE();

    if (warp >= 12) {
        asm volatile("setmaxnreg.dec.sync.aligned.u32 %0;" ::"n"(PROD_REGS));
        CLUSTER_WAIT();
        if (warp == 12) {
            if (elect_one()) {
                const CUtensorMap* tmD = c ? &tm_dim : &tm_dre;
                if (LDEL) sleep_until((uint32_t)tstart + LDEL);
#define XROWS(k) do { mbar_expect_tx(XBAR(k), 8192); bulk_g2s(sb + OFF_S + (k) * 8192, at(P.x, (b * 16 + (k) * 4) * D_ * 2), 8192, XBAR(k)); } while (0)
                int k = 0;
#pragma unroll 1
                for (int it = 1; it < 16; it++) {
                    if (it < 4) LOAD0(it);
                    else {
                        const int s = DSLOT(it);
                        mbar_wait(BAR(B_ES + s), ((it >> 2) & 1) ^ 1);
                        TRACE(it);
                        mbar_expect_tx(BAR(B_FS + s), SLOT);
                        tma_2d(sb + OFF_S + s * SLOT, tmD, it * 64, r * 128, BAR(B_FS + s));
                    }
                    while (((XS >> (4 * k)) & 15) == it) { XROWS(k); k++; }
                }
                const unsigned ep = load_epoch(b), e8 = ep & 0xffu;
                const uint8_t* abg = at(AB, grp * 32 * SLOT);
                const unsigned long long* fl = at(g_flag, grp * 128);
                unsigned long long rdy = ld_acquire64(fl);
                mbar_wait(BAR(B_SRD), 0);
                st_release8(at(g_flag, grp * 128 + g), e8);
                PROF_T(7);
                int j = 4;
#pragma unroll 1
                for (int cl = 0; cl < 4; cl++) {
                    if (cl) rdy = ld_acquire64(fl + cl);
                    fence_async_global();
#pragma unroll 1
                    for (int n = 1; n < 8; n++, j++) {
                        const int q = (g + n) & 7, s = (j & 1) + ((j & 2) ? 0 : 4);
                        mbar_wait(BAR(B_ES + s), ((j >> 2) ^ (j >> 1)) & 1);
                        if (j == 7) mbar_wait(BAR(B_SRD + 1), 0);
                        if (((unsigned)(rdy >> (8 * q)) & 0xffu) != e8) {
                            int m = 0;
                            do { rdy = ld_acquire64(fl + cl); } while (((unsigned)(rdy >> (8 * q)) & 0xffu) != e8 && ++m < SPIN_LIMIT);
                            fence_async_global();
                        }
                        TRACE(16 + j);
                        mbar_expect_tx(BAR(B_FS + s), SLOT);
                        bulk_g2s(sb + OFF_S + s * SLOT, at(abg, (4 * q + KO(cl)) * SLOT), SLOT, BAR(B_FS + s));
                    }
                }
                *at(g_epoch, b * 4) = ep;
            }
        } else if (warp < 15) {
            if (elect_one()) {
                const int w = warp - 13, row0 = g * 256 + w * 128;
                const CUtensorMap* tmC = c ? &tm_cim : &tm_cre;
                const uint32_t fb = BAR(B_FL + 4 * w), eb = BAR(B_EL + 4 * w), dst = sb + OFF_L + w * 4 * SLOT;
                prefetch_tmap(w ? &tm_out : tmC);
                unsigned long long* sy = sync_words();
#define ADOPT(ph, lag) do { const unsigned long long v = ld_relaxed64(sy++); \
                    if (v - (ph) - SYNCMIN < SYNCCAP) *reinterpret_cast<volatile uint32_t*>(smem + OFF_SEL + 8) = (uint32_t)v - (lag); } while (0)
                [[maybe_unused]] unsigned long long mk = 0;
                int n = 0, cl = 0;
#pragma unroll 1
                for (int it = 4; it < 48; it++) {
                    const int s = it & 3;
                    mbar_wait(eb + 8 * s, ((it >> 2) & 1) ^ 1);
                    const unsigned long long ph = clock64() - 1024u * (it - 4);
                    TRACE(64 + w * 64 + it - 4);
                    MARK(it, ph);
                    mbar_expect_tx(fb + 8 * s, SLOT);
                    tma_2d(dst + s * SLOT, it < 16 ? &tm_x : tmC, (it < 16 ? it : 4 * ((g + n) & 7) + KO(cl)) * 64, row0, fb + 8 * s);
                    if (it >= 16) {
                        if (it == 19) { n = 1; cl = 0; } else if (it < 19) cl++; else if (++n == 8) { n = 1; cl++; }
                    }
                    if (w == 0) {
                        if (((SYNCS << 4) >> it) & 1) red_max64(sy, ph);
                        if (((SYNCS << (4 + SYNCD)) >> it) & 1) ADOPT(ph, SYNCLAG);
                    }
                }
                {
#pragma unroll 1
                    for (int h = 0; h < 8 / OP; h++) {
                        mbar_wait(eb + 8 * h, 1);
                        fence_async_smem();
                        tma_2d_store(&tm_out, grp * 64, row0 + h * OP * 16, sb + OFF_S + (2 + w) * SLOT + h * OP * 2048);
                        bulk_commit();
                    }
                    FINISH(w);
                }
            }
        } else {
            const unsigned ep = load_epoch(b);
            uint4 f[4];
#define GATHER(ptr, cnt, valid) do { int n = 0; bool ok; do { ok = true; \
                _Pragma("unroll") for (int i = 0; i < (cnt); i++) { f[i] = ld_relaxed128((ptr) + i * 32); ok = ok && (valid); } \
                if (__all_sync(0xffffffffu, ok)) break; \
                __nanosleep(GSL); \
            } while (++n < SPIN_LIMIT); } while (0)
            {
                sleep_until((uint32_t)tstart + 6000);
                const uint4* keys = at(reinterpret_cast<const uint4*>(g_key), lane * 16);
                bool mine = false;
                int n = 0;
                do {
                    f[0] = ld_relaxed128(keys); f[1] = ld_relaxed128(keys + 32);
                    if (__all_sync(0xffffffffu, f[0].y == ep && f[0].w == ep && f[1].y == ep && f[1].w == ep)) break;
                    if (!mine) {
                        mbar_wait(BAR(B_LST), 0);
                        const uint4 k = *reinterpret_cast<const uint4*>(smem + OFF_XB);
                        if (lane == 0) st_relaxed64(at(g_key, b * 8), ((unsigned long long)ep << 32) | max(max(k.x, k.y), max(k.z, k.w)));
                        mine = true;
                    }
                    __nanosleep(GSL);
                } while (++n < SPIN_LIMIT);
                const unsigned key = __reduce_max_sync(0xffffffffu, max(max(f[0].x, f[0].z), max(f[1].x, f[1].z)));
                if (lane == 0) { *reinterpret_cast<unsigned*>(smem + OFF_SEL) = key; mbar_arrive(BAR(B_SEL)); PROF_T(8); }
            }
            if (elect_one()) {
#pragma unroll 1
                for (int cl = 0; cl < 4; cl++) {
                    uint8_t* dst = at(AB, (grp * 32 + 4 * g + KO(cl)) * SLOT);
                    const uint32_t src = sb + OFF_S + cl * SLOT, chunk = cl ? 4096 : SLOT;
                    mbar_wait(BAR(B_FS + cl), 0);
                    if (RF) fence_async_smem();
                    if (cl == 0) PROF_T(3);
                    uint32_t t0 = clock32() + (cl == 1 ? PDEL : 0);
#pragma unroll 1
                    for (uint32_t o = 0; o < SLOT; o += chunk) {
                        sleep_until(t0);
                        bulk_s2g(dst + o, src + o, chunk);
                        bulk_commit();
                        t0 += PGAP;
                    }
                    bulk_wait<0>();
                    TRACE(252 + cl);
                    if (cl < 2) mbar_arrive(BAR(B_SRD + cl));
                    else {
                        mbar_wait(BAR(B_ES + cl), 0);
                        mbar_expect_tx(BAR(B_FS + cl), SLOT);
                        tma_2d(src, &tm_x, grp * 64, g * 256 + (cl - 2) * 128, BAR(B_FS + cl));
                    }
                    if (cl) st_release8(at(g_flag, grp * 128 + cl * 8 + g), ep & 0xffu);
                    if (cl == 1) PROF_T(5);
                    if (cl == 3) PROF_T(4);
                }
            }
        }
    } else if (warp >= 8) {
        asm volatile("setmaxnreg.dec.sync.aligned.u32 %0;" ::"n"(512 - PROD_REGS - 2 * CONS_REGS));
        const int aw = warp - 8, mt = tid - 256;
        unsigned ep;
        {
            const uint8_t* rp = smem + OFF_S + aw * 2048 + lane * 16;
            const __nv_bfloat16* dp = at(c ? P.dim : P.dre, (r * 128 + g * 16 + aw * 4) * D_ * 2);
            float wf[32], sw = 0.f;
#pragma unroll
            for (int i = 0; i < 4; i++) {
                const uint4 w = __ldg(reinterpret_cast<const uint4*>(at(P.wr, lane * 16) + i * 256));
                const uint32_t wv[4] = {w.x, w.y, w.z, w.w};
#pragma unroll
                for (int e = 0; e < 4; e++) { wf[8 * i + 2 * e] = bf_lo(wv[e]); wf[8 * i + 2 * e + 1] = bf_hi(wv[e]); sw = (sw + bf_lo(wv[e])) + bf_hi(wv[e]); }
            }
            ep = load_epoch(b);
            sw = warp_sum(sw);
            CLUSTER_WAIT();
            float x0[4] = {}, s1[4] = {}, s2[4] = {}, sx[4] = {}, sd[4] = {};
#define PUSH(a, v) do { a[0] = a[1]; a[1] = a[2]; a[2] = a[3]; a[3] = v; } while (0)
#pragma unroll 1
            for (int k = 0; k < 4; k++) {
                mbar_wait(XBAR(k), 0);
                uint4 v[4];
#pragma unroll
                for (int i = 0; i < 4; i++) v[i] = *reinterpret_cast<const uint4*>(rp + k * 8192 + i * 512);
                uint32_t sh = v[0].x << 16;
                float a1s = 0.f, a2s = 0.f, axs = 0.f;
#pragma unroll
                for (int i = 0; i < 4; i++) {
                    sh = __shfl_sync(0xffffffffu, sh | (__float_as_uint(axs) & zero), 0);
                    const uint32_t xv[4] = {v[i].x, v[i].y, v[i].z, v[i].w};
#pragma unroll
                    for (int e = 0; e < 4; e++) {
                        const float a0 = bf_lo(xv[e]) - __uint_as_float(sh), a1 = bf_hi(xv[e]) - __uint_as_float(sh);
                        a1s += a0 + a1;
                        a2s = fmaf(a0, a0, fmaf(a1, a1, a2s));
                        axs = fmaf(a0, wf[8 * i + 2 * e], fmaf(a1, wf[8 * i + 2 * e + 1], axs));
                    }
                }
                PUSH(x0, __uint_as_float(sh)); PUSH(s1, a1s); PUSH(s2, a2s); PUSH(sx, axs);
                fence_async_smem();
                __syncwarp();
                if (elect_one()) {
                    const uint32_t db = XBAR(k == 3 ? 8 + aw : 4 + aw);
                    if (k == 0 || k == 3) mbar_expect_tx(db, k ? 2048 : 6144);
                    bulk_g2s(sb + OFF_S + k * 8192 + aw * 2048, dp + k * D_, 2048, db);
                }
            }
#define FOLD4(a) do { const bool u16 = lane & 16, u8 = lane & 8; \
                float p0 = (u16 ? a[2] : a[0]) + __shfl_xor_sync(0xffffffffu, u16 ? a[0] : a[2], 16); \
                float p1 = (u16 ? a[3] : a[1]) + __shfl_xor_sync(0xffffffffu, u16 ? a[1] : a[3], 16); \
                a[0] = (u8 ? p1 : p0) + __shfl_xor_sync(0xffffffffu, u8 ? p0 : p1, 8); \
                _Pragma("unroll") for (int o = 4; o; o >>= 1) a[0] += __shfl_xor_sync(0xffffffffu, a[0], o); } while (0)
#pragma unroll 1
            for (int k = 0; k < 4; k++) {
                mbar_wait(XBAR(k == 3 ? 8 + aw : 4 + aw), 0);
                float run = 0.f;
#pragma unroll
                for (int i = 0; i < 4; i++) {
                    const uint4 v = *reinterpret_cast<const uint4*>(rp + k * 8192 + i * 512);
                    const uint32_t dv[4] = {v.x, v.y, v.z, v.w};
#pragma unroll
                    for (int e = 0; e < 4; e++) run += bf_lo(dv[e]) + bf_hi(dv[e]);
                }
                PUSH(sd, run);
            }
            FOLD4(sd); FOLD4(s1); FOLD4(s2); FOLD4(sx);
            const float nb = __shfl_down_sync(0xffffffffu, sd[0], 8);
            if ((lane & 15) == 0)
                st_relaxed128(at(g_rs, (grp * 64 + g * 8 + aw * 2 + (lane >> 4)) * 16), make_uint4(__float_as_uint(sd[0]), ep, __float_as_uint(nb), ep));
            if (mt == 0) PROF_T(6);
            const int rr = lane >> 3;
            const float c0 = rr == 0 ? x0[0] : rr == 1 ? x0[1] : rr == 2 ? x0[2] : x0[3];
            const float dm = s1[0] * (1.0f / D_);
            const float mb = rbf(c0 + dm);
            const float rinv = rcp_f(rbf(sqrt_f(rbf(rbf(fmaxf(s2[0] * (1.0f / D_) - dm * dm, 0.f)) + 1e-5f))));
            if ((lane & 7) == 0) st_relaxed128(at(g_stat, (b * 16 + aw * 4 + rr) * 16), make_uint4(__float_as_uint(mb), __float_as_uint(rinv), ep, 0));
            unsigned u = __bfloat16_as_ushort(__float2bfloat16_rn((sx[0] + (c0 - mb) * sw) * rinv));
            u = (u & 0x8000u) ? (~u & 0xffffu) : (u | 0x8000u);
            u = (u << 16) | (0xffffu - (unsigned)(b * 16 + rr * 4 + aw));
            u = __reduce_max_sync(0xffffffffu, u);
            if (lane == 0) { *reinterpret_cast<unsigned*>(smem + OFF_XB + aw * 4) = u; mbar_arrive(BAR(B_LST)); }
            if (mt == 0) PROF_T(2);
            named_bar<4, 128>();
            if (mt < 12) asm volatile("mbarrier.inval.shared::cta.b64 [%0];" ::"r"(XBAR(mt)) : "memory");
            uint4 f[4];
            if (aw < 2) {
                const int t = SREC(aw * 128 + lane);
                GATHER(at(g_stat, (g * 256 + aw * 128 + lane) * 16), 4, f[i].z == ep);
#pragma unroll
                for (int i = 0; i < 4; i++) {
                    *reinterpret_cast<uint32_t*>(smem + OFF_RSTD + (POS(t) + i * 32) * 4) = f[i].y;
                    *reinterpret_cast<uint16_t*>(smem + OFF_MEAN + (POS(t) + i * 32) * 2) = (uint16_t)(f[i].x >> 16);
                }
            } else {
                const int e2 = (aw - 2) * 32 + lane;
                GATHER(at(g_rs, (grp * 64 + e2) * 16), 1, f[i].y == ep && f[i].w == ep);
#pragma unroll
                for (int i = 0; i < 2; i++) {
                    const float v = __uint_as_float(i ? f[0].z : f[0].x);
                    const float hi = rbf(v), mid = rbf(v - hi), lo = v - hi - mid;
                    *reinterpret_cast<uint4*>(smem + OFF_RS + (e2 * 2 + i) * 16) = make_uint4(pack_bf(hi, mid), pack_bf(lo, 0.f), 0, 0);
                }
            }
            fence_async_smem();
            __syncwarp();
            if (lane == 0) mbar_arrive(BAR(B_STATS));
            if (mt == 127) PROF_T(9);
        }
        const int pair = g * 7 + r;
        if (r < 7) {
            const uint64_t pol = policy_evict_first();
            const __nv_bfloat16* wp = at((aw & 1) ? P.wu : P.wg, ((c * 512 + (aw >> 1) * 256 + (lane >> 3) * 8) * F_ + pair * 64 + (lane & 7) * 8) * 2);
            uint4 b0[8], b1[8];
#define FILL(buf, str) do { _Pragma("unroll") for (int q = 0; q < 8; q++) buf[q] = ldg_stream(wp + q * (str), pol); } while (0)
            FILL(b0, F_);
            mbar_wait(BAR(B_SEL), 0);
            uint4 xn;
            {
                const int sel = 0xffff - (int)(*reinterpret_cast<volatile unsigned*>(smem + OFF_SEL) & 0xffffu);
                xn = __ldg(reinterpret_cast<const uint4*>(at(P.x, (sel * D_ + c * 512 + (aw >> 1) * 256 + (lane & 7) * 32 + (lane >> 3) * 8) * 2)));
                uint4 f[1];
                GATHER(at(g_stat, SREC(sel) * 16), 1, f[i].z == ep);
                if (NLATE && mbar_test(BAR(B_QUIET), 0)) mbar_wait_sleep(BAR(B_GO), 0);
                const float m = __uint_as_float(f[0].x), ri = __uint_as_float(f[0].y);
                xn = make_uint4(norm2(xn.x, m, ri), norm2(xn.y, m, ri), norm2(xn.z, m, ri), norm2(xn.w, m, ri));
            }
            float ag[8];
#pragma unroll
            for (int i = 0; i < 8; i++) ag[i] = 0.f;
            const uint32_t stag = (aw * 4 + (grp & 3)) * ESTAG;
            uint32_t te = clock32() + stag;
            bool paused = !QUIET;
#define ROUND(cur, nxt, rd) do { \
                if (!paused && mbar_test(BAR(B_QUIET), 0)) { mbar_wait_sleep(BAR(B_GO), 0); te = clock32() + stag; paused = true; } \
                sleep_until(te); \
                te = clock32() + (paused ? EGAP2 : EGAP1); \
                if (lane == 0) TRACE(192 + aw * 12 + (rd)); \
                if ((rd) == 7) wp = at(P.wd - 16 * D_, ((pair * 64 + (lane >> 4) * 8) * D_ + c * 512 + aw * 128 + (lane & 15) * 8) * 2); \
                wp = at(wp, ((rd) < 7 ? 64 * F_ : 32 * D_) + (cur[7].x & zero)); \
                if ((rd) < 7) FILL(nxt, F_); else if ((rd) != 8 && (rd) < 11) FILL(nxt, D_); \
                _Pragma("unroll") for (int q = 0; q < 8; q += 2) { \
                    uint32_t xw = __shfl_sync(0xffffffffu, q == 0 ? xn.x : q == 2 ? xn.y : q == 4 ? xn.z : xn.w, (lane & 24) | ((rd) & 7)); \
                    fma8(ag, cur[q], bf_lo(xw)); \
                    if (YLD > 1) { yield(ag[7], zero); xw = __shfl_sync(0xffffffffu, xw, lane); } \
                    fma8(ag, cur[q + 1], bf_hi(xw)); \
                    if (q < 6) yield(ag[7], zero); \
                } } while (0)
#pragma unroll 1
            for (int rd = 0; rd < 12; rd += 2) {
                ROUND(b0, b1, rd);
                ROUND(b1, b0, rd + 1);
                if (rd == 6) { wp += 16 * D_; FILL(b1, D_); wp -= 16 * D_; }
                if (rd == 6 || rd == 10) {
#pragma unroll
                    for (int i = 0; i < 8; i++) ag[i] += __shfl_xor_sync(0xffffffffu, ag[i], 16);
                }
                if (rd == 6) {
#pragma unroll
                    for (int i = 0; i < 8; i++) ag[i] += __shfl_xor_sync(0xffffffffu, ag[i], 8);
                    if (lane < 8) {
                        const uint32_t dst = mapa(sb + OFF_XB + (c * 4 + aw) * 128 + (lane & 3) * 32, lane >> 2), pb = mapa(BAR(B_PEER), lane >> 2);
                        st_async4(dst, __float_as_uint(ag[0]), __float_as_uint(ag[1]), __float_as_uint(ag[2]), __float_as_uint(ag[3]), pb);
                        st_async4(dst + 16, __float_as_uint(ag[4]), __float_as_uint(ag[5]), __float_as_uint(ag[6]), __float_as_uint(ag[7]), pb);
                    }
                    if (aw == 3) {
                        mbar_wait_cluster(BAR(B_PEER), 0);
                        const float* ps = reinterpret_cast<const float*>(smem + OFF_XB) + lane;
                        const float go = (ps[0] + ps[64]) + (ps[128] + ps[192]), uo = (ps[32] + ps[96]) + (ps[160] + ps[224]);
                        const float h = rbf(silu_f(rbf(go))) * rbf(uo), ho = __shfl_xor_sync(0xffffffffu, h, 1);
                        asm volatile("st.async.weak.shared::cluster.mbarrier::complete_tx::bytes.b32 [%0], %1, [%2];"
                                     ::"r"(mapa(sb + OFF_H + c * 64 + (lane >> 1) * 4, lane & 1)), "r"((lane & 1) ? pack_bf(ho, h) : pack_bf(h, ho)),
                                       "r"(mapa(BAR(B_H), lane & 1)) : "memory");
                    }
                    mbar_wait_cluster(BAR(B_H), 0);
                    xn = *reinterpret_cast<const uint4*>(smem + OFF_H + (lane & 3) * 32 + (lane >> 4) * 16);
#pragma unroll
                    for (int i = 0; i < 8; i++) ag[i] = 0.f;
                    if (mt == 0) PROF_T(10);
                }
            }
            const int hi = lane >> 4;
            st_relaxed128(at(g_part, pair * 4096 + (c * 8 + aw * 2 + ((lane >> 3) & 1)) * 256 + hi * 128 + (lane & 7) * 16),
                          make_uint4((__float_as_uint(hi ? ag[4] : ag[0]) & ~15u) | (ep & 15u), __float_as_uint(hi ? ag[5] : ag[1]),
                                     __float_as_uint(hi ? ag[6] : ag[2]), __float_as_uint(hi ? ag[7] : ag[3])));
            if (mt == 0) PROF_T(11);
        } else {
            mbar_wait_sleep(BAR(B_SEL), 0);
        }
        const int sel = 0xffff - (int)(*reinterpret_cast<volatile unsigned*>(smem + OFF_SEL) & 0xffffu);
        if ((sel >> 8) == g) {
            const int col = (lane & 7) * 8 + ((lane >> 3) & 1) * 4;
            const uint2 xv = __ldg(reinterpret_cast<const uint2*>(at(P.x, (sel * D_ + grp * 64 + col) * 2)));
            uint4 f[1];
            GATHER(at(g_stat, SREC(sel) * 16), 1, f[i].z == ep);
            const uint4 rec = f[0];
            const uint4* src = at(g_part, (aw * 14 + (lane >> 4)) * 4096 + grp * 256 + (lane & 15) * 16);
            if (r == 7) {
                int n = 0;
                while (((ld_relaxed(src) ^ ep) & 15u) != 0 && ++n < SPIN_LIMIT) __nanosleep(500);
            }
            uint4 t[7];
            int n = 0;
            bool ok;
            do {
                ok = true;
#pragma unroll
                for (int u = 0; u < 7; u++) { t[u] = ld_relaxed128(src + u * 512); ok = ok && ((t[u].x ^ ep) & 15u) == 0; }
            } while (!__all_sync(0xffffffffu, ok) && ++n < SPIN_LIMIT);
            float4 a = make_float4(0.f, 0.f, 0.f, 0.f);
#pragma unroll
            for (int u = 0; u < 7; u++) {
                a.x += __uint_as_float(t[u].x & ~15u); a.y += __uint_as_float(t[u].y); a.z += __uint_as_float(t[u].z); a.w += __uint_as_float(t[u].w);
            }
            a.x += __shfl_xor_sync(0xffffffffu, a.x, 16); a.y += __shfl_xor_sync(0xffffffffu, a.y, 16);
            a.z += __shfl_xor_sync(0xffffffffu, a.z, 16); a.w += __shfl_xor_sync(0xffffffffu, a.w, 16);
            float4* park = reinterpret_cast<float4*>(smem + OFF_XB) + (lane & 15);
            if (lane < 16) park[aw * 16] = a;
            named_bar<4, 128>();
            if (aw == 0) {
                const float4 p1 = park[16], p2 = park[32], p3 = park[48];
                a.x = (a.x + p1.x) + (p2.x + p3.x); a.y = (a.y + p1.y) + (p2.y + p3.y);
                a.z = (a.z + p1.z) + (p2.z + p3.z); a.w = (a.w + p1.w) + (p2.w + p3.w);
                unsigned u = *reinterpret_cast<volatile unsigned*>(smem + OFF_SEL) >> 16;
                u = (u & 0x8000u) ? (u & 0x7fffu) : (~u & 0xffffu);
                const float sg = rbf(__fdividef(1.0f, 1.0f + __expf(-__uint_as_float(u << 16))));
                const float m = __uint_as_float(rec.x), ri = __uint_as_float(rec.y);
                const uint32_t n0 = norm2(xv.x, m, ri), n1 = norm2(xv.y, m, ri);
                uint2 o;
                o.x = silu2(pack_bf(bf_lo(n0) + rbf(rbf(a.x) * sg), bf_hi(n0) + rbf(rbf(a.y) * sg)));
                o.y = silu2(pack_bf(bf_lo(n1) + rbf(rbf(a.z) * sg), bf_hi(n1) + rbf(rbf(a.w) * sg)));
                if (lane < 16) *reinterpret_cast<uint2*>(smem + OFF_H + col * 2) = o;
                __syncwarp();
                if (lane == 0) { mbar_arrive(BAR(B_UPD)); PROF_T(12); }
            }
        }
    } else {
        asm volatile("setmaxnreg.inc.sync.aligned.u32 %0;" ::"n"(CONS_REGS));
        CLUSTER_WAIT();
        const int wg = warp >> 2, wq = warp & 3;
        const int wt = tid & 127;
        float acc[128];
        const uint32_t fL = BAR(B_FL + 4 * wg), eL = BAR(B_EL + 4 * wg);
        const uint32_t dL = desc_lo(SB0 + OFF_L, 16) + wg * 4096;
        constexpr uint32_t dS = desc_lo(SB0 + OFF_S, 16);
        constexpr uint32_t SL = SLOT >> 4;
#define RELEASE(ls, ss) do { if (wt == 0) { mbar_arrive(eL + 8u * (ls)); mbar_arrive(BAR(B_ES + (ss))); } } while (0)
#define WAIT_FULL(ls, lph, ss, sph) do { mbar_wait(BAR(B_FS + (ss)), sph); mbar_wait(fL + 8u * (ls), lph); } while (0)
#define TURN() do { if (wg) named_bar<6, 256>(); else named_bar<5, 256>(); } while (0)
#define PASS() do { if (wg) named_arrive<5, 256>(); else named_arrive<6, 256>(); } while (0)
#define WG_BAR() do { if (wg) named_bar<2, 128>(); else named_bar<1, 128>(); } while (0)
        uint32_t held = 0, tgt = 0;
#define PEEK() do { if (wg == 0) tgt = *reinterpret_cast<volatile uint32_t*>(smem + OFF_SEL + 8); } while (0)
#define HOLD(step) do { if (tgt != held) { held = tgt; sleep_until(tgt + 1024u * (step) - 100u); \
                int n = 0; while ((int)(clock32() - tgt - 1024u * (step)) < 0 && ++n < SPIN_LIMIT) {} } } while (0)
        if (wg == 1) PASS();

#define MMA1_P(O, s, first, pass) do { _Pragma("unroll") for (int kk = 0; kk < 4; kk++) { if (kk == PK && (pass)) PASS(); \
            wgmma128<O, 0>(acc, dL + (s) * SL + kk * 2 + (O) * 8, dS + DSLOT(s) * SL + kk * 2, !((first) && kk == 0)); } \
            if (PK == 4 && (pass)) PASS(); } while (0)
#define MMA1_H(O, s, first) MMA1_P(O, s, first, false)
#define WAIT1(s, ph) WAIT_FULL(s, ph, DSLOT(s), ph)
#define PROBE(ls, lph, ss, sph) (mbar_test(BAR(B_FS + (ss)), sph) & mbar_test(fL + 8u * (ls), lph))
#define REL1(s) RELEASE(s, DSLOT(s))
#pragma unroll 1
        for (int it = 0; it < 12; it++) {
            const int s = it & 3;
            const bool ok = PROBE(s, (it >> 2) & 1, DSLOT(s), (it >> 2) & 1);
            PEEK();
            if (it) { wg_wait<0>(); REL1((it - 1) & 3); }
            if (!ok) WAIT1(s, (it >> 2) & 1);
            HOLD(it);
            TURN();
            wg_fence(); MMA1_H(0, s, it == 0); MMA1_H(64, s, it == 0); wg_commit();
            PASS();
            if (it == QJ && tid == 0) { mbar_arrive(BAR(B_QUIET)); PROF_T(15); }
            if (it == 0 && tid == 0) PROF_T(16);
        }
        TS(12);
        float rs[4] = {};
        uint32_t nm[8] = {};
#define GET_STATS() do { mbar_wait(BAR(B_STATS), 0); \
            const int p0 = POS(wg * 128 + wq * 16 + (lane >> 2));                   \
            const uint32_t msk = (lane & 3) == 0 ? 0xffffffffu : (lane & 3) == 1 ? 0x0000ffffu : 0u; \
            _Pragma("unroll") for (int i = 0; i < 4; i++) { \
                const int p = p0 + (i & 1) * 2 + (i >> 1) * 64; \
                rs[i] = *reinterpret_cast<const float*>(smem + OFF_RSTD + p * 4); \
                const uint32_t m = *reinterpret_cast<const uint16_t*>(smem + OFF_MEAN + p * 2) ^ 0x8000u; \
                nm[i + (i & 2)] = (m | (m << 16)) & msk; \
            } } while (0)
        const bool early = wg || __all_sync(0xffffffffu, mbar_test(BAR(B_STATS), 0));
        if (early && !wg) GET_STATS();
        WAIT1(0, 1);
        TS(13);
        wg_wait<0>(); REL1(3);
        if (wg) GET_STATS();
        TS(14);
        TURN();
        wg_fence();
        MMA1_H(0, 0, false);
        if (QJ == 12 && tid == 0) { mbar_arrive(BAR(B_QUIET)); PROF_T(15); }
        WAIT1(1, 1); wg_fence(); MMA1_H(0, 1, false);
        WAIT1(2, 1); wg_fence(); MMA1_H(0, 2, false); wg_commit();
        if (!early) GET_STATS();
        asm volatile("" : "+r"(nm[0]), "+r"(nm[1]), "+r"(nm[2]), "+r"(nm[3]), "+r"(nm[4]), "+r"(nm[5]), "+r"(nm[6]), "+r"(nm[7])::"memory");
        wg_fence();
        wgmma128_rs<64>(acc, nm + 4, (SB0 + OFF_RS) >> 4);
        wgmma128_rs<0>(acc, nm, (SB0 + OFF_RS) >> 4);
        WAIT1(3, 1); wg_fence(); MMA1_P(0, 3, false, true);
        wg_commit();
        const int mrow = wq * 16 + ((lane >> 3) & 1) * 8 + (lane & 7);
#define EPI1(O, slot, FREE) do { const uint32_t dst = sb + OFF_S + (slot) * SLOT + mrow * 128; \
            uint32_t pk[32]; \
            _Pragma("unroll") for (int i = 0; i < 32; i += 4) { \
                _Pragma("unroll") for (int k = 0; k < 4; k++) \
                    pk[i + k] = pack_bf(acc[(O) + 2 * (i + k)] * rs[(O) / 32 + (k & 1)], acc[(O) + 2 * (i + k) + 1] * rs[(O) / 32 + (k & 1)]); \
                if (i == EF) { FREE; } \
                if (i >= EF) { _Pragma("unroll") for (int v = (i == EF ? 0 : i); v <= i; v += 4) \
                    stmatrix4(dst + ((v >> 4) ^ c ^ 1) * 8192 + ((((v >> 1) & 7) + (lane >> 4)) ^ (lane & 7)) * 16, pk[v], pk[v + 1], pk[v + 2], pk[v + 3]); } } \
            if (!RF) fence_async_smem(); \
            WG_BAR(); \
            if (wt == 0) mbar_arrive(BAR(B_FS + (slot))); } while (0)
        TS(15);
        wg_wait<0>();
        fence_regs64<0>(acc);
        TS(16);
        {
            constexpr int EF = 0;
            EPI1(0, wg, if (wg) mbar_wait(BAR(B_FS), 0));
        }
        TS(17);
        TURN();
        wg_fence();
        MMA1_H(64, 0, false); wg_commit();
        MMA1_H(64, 1, false); wg_commit();
        MMA1_H(64, 2, false); wg_commit();
        wg_wait<2>(); REL1(0);
        MMA1_P(64, 3, false, true); wg_commit();
        TS(18);
        wg_wait<2>(); REL1(1);
        if (RF) { mbar_wait(BAR(B_FS), 0); mbar_wait(BAR(B_FS + 1), 0); fence_async_smem(); }
        wg_wait<1>(); REL1(2);
        wg_wait<0>(); REL1(3);
        fence_regs64<64>(acc);
        TS(19);
        {
            constexpr int EF = EF2;
            EPI1(64, 2 + wg, mbar_wait(BAR(B_ES + 2 + wg), 1));
        }
        TS(20);

        float ac2[128];
#define MMA2_P(O, ls, ss, first, pass) do { _Pragma("unroll") for (int kk = 0; kk < 4; kk++) { if (kk == PK && (pass)) PASS(); \
            wgmma128<O, 1>(ac2, dS + (ss) * SL + kk * 128 + (O) * 8, dL + (ls) * SL + kk * 2, !((first) && kk == 0)); } \
            if (PK == 4 && (pass)) PASS(); } while (0)
#define MMA2_H(O, ls, ss, first) MMA2_P(O, ls, ss, first, false)
#define WAIT2(j) WAIT_FULL((j) & 3, ((j) >> 2) & 1, PSLOT(j), PPAR(j))
#define MMA2(j, pass) do { wg_fence(); MMA2_H(0, (j) & 3, PSLOT(j), (j) == 0); MMA2_P(64, (j) & 3, PSLOT(j), (j) == 0, pass); wg_commit(); } while (0)
#define REL2(j) RELEASE((j) & 3, PSLOT(j))
        if (GOJ == 0 && wt == 0) mbar_arrive(BAR(B_GO));
        WAIT2(0); TURN(); MMA2(0, false);
        WAIT2(1); MMA2(1, true);
        TS(21);
        wg_wait<1>(); REL2(0);
        if (RF) { mbar_wait(BAR(B_FS + 2), 0); mbar_wait(BAR(B_FS + 3), 0); fence_async_smem(); }
        TS(22);
        {
            uint32_t sp = 1;
#pragma unroll 1
            for (int j = 2; j < XJ; j++) {
                const uint32_t ss = PSLOT(j);
                const bool ok = PROBE(j & 3, (j >> 2) & 1, ss, PPAR(j));
                PEEK();
                wg_wait<0>(); RELEASE((j - 1) & 3, sp);
                if (!ok) WAIT_FULL(j & 3, (j >> 2) & 1, ss, PPAR(j));
                HOLD(16 + j);
                TURN();
                wg_fence(); MMA2_H(0, j & 3, ss, false); MMA2_P(64, j & 3, ss, false, true); wg_commit();
                if (j == GOJ && wt == 0) { mbar_arrive(BAR(B_GO)); if (wg == 0) PROF_T(19); }
                sp = ss;
            }
        }
        if (tid == 0) PROF_T(20);
        uint32_t gt[32];
        const uint32_t xrow = sb + OFF_S + (2 + wg) * SLOT + ((lane >> 4) * 8 + (lane & 7)) * 128 + (((2 * wq + ((lane >> 3) & 1)) ^ (lane & 7)) << 4);
        const uint32_t gsign = c ? 0x80008000u : 0u;
        mbar_wait(BAR(B_FS + 2 + wg), 1);
        mbar_wait(BAR(B_SEL), 0);
        const int sel = 0xffff - (int)(*reinterpret_cast<volatile unsigned*>(smem + OFF_SEL) & 0xffffu);
        bool own = (sel >> 7) == 2 * g + wg;
#define PATCH() do { own = false; \
            const uint32_t v0 = *reinterpret_cast<const uint16_t*>(smem + OFF_H + (wq * 16 + (lane >> 2)) * 2) ^ gsign; \
            const uint32_t v1 = *reinterpret_cast<const uint16_t*>(smem + OFF_H + (wq * 16 + (lane >> 2)) * 2 + 16) ^ gsign; \
            const uint32_t pick = (lane & 3) != ((sel >> 1) & 3) ? 0x3210u : (sel & 1) ? 0x5410u : 0x3254u; \
            _Pragma("unroll") for (int i = 0; i < 16; i++) { \
                const uint32_t m = ((sel >> 3) & 15) == i ? pick : 0x3210u; \
                gt[2 * i] = __byte_perm(gt[2 * i], v0, m); \
                gt[2 * i + 1] = __byte_perm(gt[2 * i + 1], v1, m); \
            } } while (0)
#pragma unroll
        for (int v = 0; v < 28 - XJ; v++) {
            WAIT2(XJ + v); wg_wait<0>(); REL2(XJ + v - 1); TURN(); MMA2(XJ + v, true);
            constexpr int NS = 8 / (28 - XJ);
#pragma unroll
            for (int u = v * NS; u < (v + 1) * NS; u++) {
                uint32_t* o = &gt[4 * u];
                ldmatrix4t(xrow + u * 2048, o[0], o[1], o[2], o[3]);
                const float4 r4 = *reinterpret_cast<const float4*>(smem + OFF_RSTD + (wg * 128 + u * 16 + (lane & 3) * 4) * 4);
                const uint2 m2 = *reinterpret_cast<const uint2*>(smem + OFF_MEAN + (wg * 128 + u * 16 + (lane & 3) * 4) * 2);
                o[0] = gate2(o[0], m2.x, r4.x, r4.y) ^ gsign;
                o[1] = gate2(o[1], m2.x, r4.x, r4.y) ^ gsign;
                o[2] = gate2(o[2], m2.y, r4.z, r4.w) ^ gsign;
                o[3] = gate2(o[3], m2.y, r4.z, r4.w) ^ gsign;
                asm volatile("st.shared.v2.u32 [%0], {%1,%2};" ::"r"(sb + OFF_SEL + 16), "r"(o[0] ^ o[1]), "r"(o[2] ^ o[3]) : "memory");
            }
        }
        if (tid == 0) PROF_T(21);
        WAIT2(28);
        wg_wait<0>(); REL2(27);
        if (own) {
            const uint32_t t0 = clock32();
            bool ok;
            while (!(ok = mbar_test(BAR(B_UPD), 0)) && clock32() - t0 < wg * 1400u) __nanosleep(50);
            if (__all_sync(0xffffffffu, ok)) PATCH();
        }
        TS(0);
        TURN();
        wg_fence(); MMA2_H(0, 0, PSLOT(28), false); wg_commit();
        if (wg == 0 || !ASYM) { wg_fence(); MMA2_H(64, 0, PSLOT(28), false); wg_commit(); }
        WAIT2(29); wg_fence(); MMA2_H(0, 1, PSLOT(29), false); wg_commit();
        WAIT2(30); wg_fence(); MMA2_H(0, 2, PSLOT(30), false); wg_commit();
        wg_wait<2>();
        if (tid == 0) mbar_arrive_cluster(mapa(BAR(B_RDY), c ^ 1));
        WAIT2(31); wg_fence(); MMA2_H(0, 3, PSLOT(31), false); wg_commit();
        TS(1);
#define KEEP(i) wgmma128<64, 1>(ac2, dS + PSLOT(29 + ((i) >> 2)) * SL + ((i) & 3) * 128 + 512, dL + (1 + ((i) >> 2)) * SL + ((i) & 3) * 2, 1)
        wg_fence();
#pragma unroll
        for (int i = 0; i < KQ; i++) KEEP(i);
        wg_commit();
        mbar_wait(BAR(B_RDY + wg), 0);
        wg_wait<1>();
        fence_regs64<0>(ac2);
        TS(2);
        wg_fence();
        {
            const uint32_t dst = mapa(sb + OFF_L + wg * SLOT + wt * 16, c ^ 1), rb = mapa(BAR(B_RECV + 2 * wg), c ^ 1);
#pragma unroll
            for (int v = 0; v < 8; v++) {
                if (KQ + v < 12) KEEP(KQ + v);
                if (KQ + v == 11) { wg_commit(); if (wg == 0) PASS(); }
                st_async4(dst + v * 2048, pack_bf(ac2[8 * v + 0], ac2[8 * v + 1]), pack_bf(ac2[8 * v + 2], ac2[8 * v + 3]),
                          pack_bf(ac2[8 * v + 4], ac2[8 * v + 5]), pack_bf(ac2[8 * v + 6], ac2[8 * v + 7]), rb + (v >> 2) * 8);
            }
        }
        if (wg == 1 && ASYM) { wg_fence(); MMA2_H(64, 0, PSLOT(28), false); wg_commit(); }
        TS(3);
        uint32_t xr[32];
#define LDX(v) ldmatrix4t(xrow + (v) * 2048, xr[4 * (v)], xr[4 * (v) + 1], xr[4 * (v) + 2], xr[4 * (v) + 3])
#pragma unroll
        for (int v = 0; v < XE; v++) LDX(v);
        if (wg == 0) {
            wg_wait<0>();
            if (wt == 0) mbar_arrive_cluster(mapa(BAR(B_RDY + 1), c ^ 1));
        }
        TS(4);
        if (own) { mbar_wait(BAR(B_UPD), 0); PATCH(); }
        TS(5);
        uint4 rv[8];
#define FETCH(v0) do { if ((v0) == 0 || (v0) == 4) mbar_wait_cluster(BAR(B_RECV + 2 * wg + (v0) / 4), 0); \
            _Pragma("unroll") for (int v = (v0); v < (v0) + OP; v++) { \
                asm volatile("ld.shared.v4.u32 {%0,%1,%2,%3}, [%4];" : "=r"(rv[v].x), "=r"(rv[v].y), "=r"(rv[v].z), "=r"(rv[v].w) \
                             : "r"(sb + OFF_L + wg * SLOT + v * 2048 + wt * 16) : "memory"); \
                if (v >= XE) LDX(v); } } while (0)
        FETCH(0);
        TS(6);
        wg_wait<0>();
        fence_regs64<64>(ac2);
        TS(7);
#pragma unroll
        for (int v0 = 0; v0 < 8; v0 += OP) {
#pragma unroll
            for (int v = v0; v < v0 + OP; v++) {
                const float* a = &ac2[64 + 8 * v];
                stmatrix4t(xrow + v * 2048,
                           bfma2(bsub2(pack_bf(a[0], a[1]), rv[v].x), gt[4 * v + 0], xr[4 * v + 0]),
                           bfma2(bsub2(pack_bf(a[2], a[3]), rv[v].y), gt[4 * v + 1], xr[4 * v + 1]),
                           bfma2(bsub2(pack_bf(a[4], a[5]), rv[v].z), gt[4 * v + 2], xr[4 * v + 2]),
                           bfma2(bsub2(pack_bf(a[6], a[7]), rv[v].w), gt[4 * v + 3], xr[4 * v + 3]));
            }
            WG_BAR();
            if (wt == 0) mbar_arrive(eL + 8 * (v0 / OP));
            if (v0 + OP < 8) FETCH(v0 + OP);
            if (v0 == 0) TS(8);
        }
        TS(9);
    }
}

typedef CUresult (*EncodeFn)(CUtensorMap*, CUtensorMapDataType, cuuint32_t, void*, const cuuint64_t*, const cuuint64_t*,
                             const cuuint32_t*, const cuuint32_t*, CUtensorMapInterleave, CUtensorMapSwizzle,
                             CUtensorMapL2promotion, CUtensorMapFloatOOBfill);

void make_map(EncodeFn fn, CUtensorMap* tm, const void* p, uint64_t rows, uint64_t cols, uint32_t box_rows,
              CUtensorMapL2promotion promo = CU_TENSOR_MAP_L2_PROMOTION_L2_128B) {
    cuuint64_t dims[2] = {cols, rows};
    cuuint64_t strides[1] = {cols * 2};
    cuuint32_t box[2] = {64, box_rows};
    cuuint32_t es[2] = {1, 1};
    fn(tm, CU_TENSOR_MAP_DATA_TYPE_BFLOAT16, 2, const_cast<void*>(p), dims, strides, box, es, CU_TENSOR_MAP_INTERLEAVE_NONE,
       CU_TENSOR_MAP_SWIZZLE_128B, promo, CU_TENSOR_MAP_FLOAT_OOB_FILL_NONE);
}

}

extern "C" void kernel_launch(void* const* d_in, const int* in_sizes, int n_in, void* d_out, int out_size) {
    (void)in_sizes; (void)n_in; (void)out_size;
    static EncodeFn fn = nullptr;
    if (!fn) {
        void* p = nullptr;
        cudaDriverEntryPointQueryResult q;
        cudaGetDriverEntryPoint("cuTensorMapEncodeTiled", &p, cudaEnableDefault, &q);
        fn = (EncodeFn)p;
        cudaFuncSetAttribute(fnet_fused_kernel, cudaFuncAttributeMaxDynamicSharedMemorySize, SMEM_BYTES);
    }
    CUtensorMap tx, tdre, tdim, tcre, tcim, tout;
    make_map(fn, &tx, d_in[0], S_, D_, 128, PRX);
    make_map(fn, &tcre, d_in[1], S_, S_, 128, PRC);
    make_map(fn, &tcim, d_in[2], S_, S_, 128, PRC);
    make_map(fn, &tdre, d_in[3], D_, D_, 128, PRD);
    make_map(fn, &tdim, d_in[4], D_, D_, 128, PRD);
    make_map(fn, &tout, d_out, S_, D_, 16 * OP);
    Params P;
    P.x = (const __nv_bfloat16*)d_in[0];
    P.dre = (const __nv_bfloat16*)d_in[3];
    P.dim = (const __nv_bfloat16*)d_in[4];
    P.wr = (const __nv_bfloat16*)d_in[6];
    P.wg = (const __nv_bfloat16*)d_in[7];
    P.wu = (const __nv_bfloat16*)d_in[8];
    P.wd = (const __nv_bfloat16*)d_in[9];
    P.zero = 0;
    fnet_fused_kernel<<<NCTA, NTHREADS, SMEM_BYTES, cudaStreamPerThread>>>(tx, tdre, tdim, tcre, tcim, tout, P);
}
```

```cpp
#include <cuda_runtime.h>
#include <cuda_bf16.h>
#include <cuda.h>
#include <stdint.h>

#define LDEL 0
#define LGAP 0
#define XS 0x5432
#define GSL 200
#define YNS 0u
#define YLD 1
#define PDEL 2500
#define PGAP 600
#define PK 4
#define ASYM 1
#define RF 1
#define EF2 16
#define NLATE 1
#define XE 2
#define W0 12
#define PFX 1
#define PFJ 0
#define MAPD 1
#define ORD 1
#define SDOM 0
#define KQ 5
#define OP 2
#define XJ0 20
#define EGAP1 0
#define EGAP2 0
#define ESTAG 120
#define QJ 10
#define GOJ 2
#define TANH 1
#define SYNCS 0x2200080ull
#define SYNCD 2
#define SYNCCAP 4000u
#define SYNCMIN 24u
#define SYNCLAG 820u
#define QUIET 1
#define PRX CU_TENSOR_MAP_L2_PROMOTION_L2_128B
#define PRD CU_TENSOR_MAP_L2_PROMOTION_L2_128B
#define PRC CU_TENSOR_MAP_L2_PROMOTION_L2_128B
#define SLEEP_NS 200
#define PROD_REGS 32
#define CONS_REGS 184

namespace {

constexpr int S_ = 2048, D_ = 1024, F_ = 3584;
constexpr int NCTA = 128;
constexpr int XJ = XJ0;
constexpr uint32_t SLOT = 16384;
constexpr uint32_t OFF_L = 0;
constexpr uint32_t OFF_S = 8 * SLOT;
constexpr uint32_t OFF_RS = OFF_S + SLOT;
constexpr uint32_t OFF_BAR = 14 * SLOT;
constexpr uint32_t OFF_SEL = OFF_BAR + 360;
constexpr uint32_t OFF_RSTD = OFF_BAR + 384;
constexpr uint32_t OFF_MEAN = OFF_RSTD + 1024;
constexpr uint32_t OFF_XB = OFF_MEAN + 512;
constexpr uint32_t OFF_H = OFF_XB + 1024;
constexpr uint32_t SMEM_BYTES = OFF_H + 128;
constexpr uint32_t OFF_TS = OFF_XB + 512;
constexpr uint32_t SB0 = 1024;
constexpr int NTHREADS = 512;
static_assert(SMEM_BYTES <= 232448, "smem");

enum { B_FS = 0, B_ES = 6, B_FL = 12, B_EL = 20, B_SRD = 28, B_RECV = 30  , B_RDY = 34, B_STATS = 36, B_LST = 37, B_UPD = 38,
       B_QUIET = 39, B_GO = 40, B_PEER = 41, B_SEL = 42, B_H = 43, B_COUNT = 44 };
static_assert(B_COUNT * 8 <= 360, "barriers");

__device__ __align__(1024) uint8_t g_ab[16u * 32u * SLOT];
__device__ __align__(128) uint4 g_part[56 * (D_ / 4)];
__device__ __align__(128) uint4 g_stat[S_];
__device__ __align__(128) uint4 g_rs[D_];
__device__ __align__(128) unsigned long long g_key[NCTA];
__device__ __align__(128) unsigned long long g_flag[16 * 16];
__device__ __align__(128) unsigned long long g_sync[16 * 16];
__device__ __align__(128) unsigned g_epoch[NCTA];
#define PROF_T(i) do {} while (0)
#define TRACE(i) do {} while (0)
#define PROF_G(i) do {} while (0)
#define TS(i) do {} while (0)
#define FINISH(wg) bulk_wait_read<0>()

#define MARK(it, ph) do {} while (0)

__device__ __forceinline__ uint32_t smem_u32(const void* p) { return (uint32_t)__cvta_generic_to_shared(p); }
__device__ __forceinline__ void mbar_init(uint32_t bar, uint32_t cnt) {
    asm volatile("mbarrier.init.shared::cta.b64 [%0], %1;" ::"r"(bar), "r"(cnt) : "memory");
}
__device__ __forceinline__ bool mbar_try(uint32_t bar, uint32_t parity) {
    uint32_t ok;
    asm volatile("{\n.reg .pred p;\nmbarrier.try_wait.parity.shared::cta.b64 p, [%1], %2;\nselp.u32 %0, 1, 0, p;\n}"
                 : "=r"(ok) : "r"(bar), "r"(parity) : "memory");
    return ok;
}
__device__ __forceinline__ bool mbar_test(uint32_t bar, uint32_t parity) {
    uint32_t ok;
    asm volatile("{\n.reg .pred p;\nmbarrier.test_wait.parity.shared::cta.b64 p, [%1], %2;\nselp.u32 %0, 1, 0, p;\n}"
                 : "=r"(ok) : "r"(bar), "r"(parity) : "memory");
    return ok;
}
__device__ __forceinline__ bool mbar_try_cluster(uint32_t bar, uint32_t parity) {
    uint32_t ok;
    asm volatile("{\n.reg .pred p;\nmbarrier.try_wait.parity.acquire.cluster.shared::cta.b64 p, [%1], %2;\nselp.u32 %0, 1, 0, p;\n}"
                 : "=r"(ok) : "r"(bar), "r"(parity) : "memory");
    return ok;
}
constexpr int SPIN_LIMIT = 1 << 20;
__device__ __forceinline__ void mbar_wait(uint32_t bar, uint32_t parity) {
    if (mbar_try(bar, parity)) return;
    int n = 0;
    while (!mbar_try(bar, parity) && ++n < SPIN_LIMIT) {}
}
__device__ __forceinline__ void mbar_wait_cluster(uint32_t bar, uint32_t parity) {
    int n = 0;
    while (!mbar_try_cluster(bar, parity) && ++n < SPIN_LIMIT) {}
}
__device__ __forceinline__ void mbar_wait_sleep(uint32_t bar, uint32_t parity) {
    int n = 0;
    while (!mbar_try(bar, parity) && ++n < SPIN_LIMIT) __nanosleep(SLEEP_NS);
}
__device__ __forceinline__ void mbar_arrive(uint32_t bar) {
    asm volatile("mbarrier.arrive.shared::cta.b64 _, [%0];" ::"r"(bar) : "memory");
}
__device__ __forceinline__ void mbar_arrive_cluster(uint32_t cluster_bar) {
    asm volatile("mbarrier.arrive.shared::cluster.b64 _, [%0];" ::"r"(cluster_bar) : "memory");
}
__device__ __forceinline__ void mbar_expect_tx(uint32_t bar, uint32_t bytes) {
    asm volatile("mbarrier.arrive.expect_tx.shared::cta.b64 _, [%0], %1;" ::"r"(bar), "r"(bytes) : "memory");
}
__device__ __forceinline__ bool elect_one() {
    uint32_t p;
    asm volatile("{\n.reg .pred p;\nelect.sync _|p, 0xffffffff;\nselp.u32 %0, 1, 0, p;\n}" : "=r"(p));
    return p;
}
__device__ __forceinline__ uint32_t mapa(uint32_t addr, uint32_t rank) {
    uint32_t r;
    asm("mapa.shared::cluster.u32 %0, %1, %2;" : "=r"(r) : "r"(addr), "r"(rank));
    return r;
}
__device__ __forceinline__ uint32_t clock32() { uint32_t t; asm volatile("mov.u32 %0, %%clock;" : "=r"(t)); return t; }
__device__ __forceinline__ void sleep_until(uint32_t t) {
    int n = 0;
    while ((int)(clock32() - t) < 0 && ++n < SPIN_LIMIT) __nanosleep(20);
}
__device__ __forceinline__ void yield(float last, uint32_t zero) {
    if (YLD) asm volatile("nanosleep.u32 %0;" ::"r"((__float_as_uint(last) & zero) | YNS));
}
template <typename T> __device__ __forceinline__ T* at(T* p, uint32_t bytes) {
    asm("" : "+r"(bytes));
    return reinterpret_cast<T*>(reinterpret_cast<uintptr_t>(p) + bytes);
}
__device__ __forceinline__ void tma_2d(uint32_t dst, const CUtensorMap* tm, int c0, int c1, uint32_t bar) {
    asm volatile("cp.async.bulk.tensor.2d.shared::cluster.global.mbarrier::complete_tx::bytes [%0], [%1, {%3, %4}], [%2];"
                 ::"r"(dst), "l"(tm), "r"(bar), "r"(c0), "r"(c1) : "memory");
}
__device__ __forceinline__ void tma_2d_prefetch(const CUtensorMap* tm, int c0, int c1) {
    asm volatile("cp.async.bulk.prefetch.tensor.2d.L2.global [%0, {%1, %2}];" ::"l"(tm), "r"(c0), "r"(c1) : "memory");
}
__device__ __forceinline__ void tma_2d_store(const CUtensorMap* tm, int c0, int c1, uint32_t src) {
    asm volatile("cp.async.bulk.tensor.2d.global.shared::cta.bulk_group [%0, {%2, %3}], [%1];"
                 ::"l"(tm), "r"(src), "r"(c0), "r"(c1) : "memory");
}
__device__ __forceinline__ void bulk_g2s(uint32_t dst, const void* src, uint32_t bytes, uint32_t bar) {
    asm volatile("cp.async.bulk.shared::cluster.global.mbarrier::complete_tx::bytes [%0], [%1], %2, [%3];"
                 ::"r"(dst), "l"(src), "r"(bytes), "r"(bar) : "memory");
}
__device__ __forceinline__ void bulk_s2g(void* dst, uint32_t src, uint32_t bytes) {
    asm volatile("cp.async.bulk.global.shared::cta.bulk_group [%0], [%1], %2;" ::"l"(dst), "r"(src), "r"(bytes) : "memory");
}
__device__ __forceinline__ void st_async4(uint32_t dst, uint32_t a, uint32_t b, uint32_t c, uint32_t d, uint32_t bar) {
    asm volatile("st.async.weak.shared::cluster.mbarrier::complete_tx::bytes.v4.b32 [%0], {%1,%2,%3,%4}, [%5];"
                 ::"r"(dst), "r"(a), "r"(b), "r"(c), "r"(d), "r"(bar) : "memory");
}
__device__ __forceinline__ void bulk_commit() { asm volatile("cp.async.bulk.commit_group;" ::: "memory"); }
template <int N> __device__ __forceinline__ void bulk_wait_read() { asm volatile("cp.async.bulk.wait_group.read %0;" ::"n"(N) : "memory"); }
template <int N> __device__ __forceinline__ void bulk_wait() { asm volatile("cp.async.bulk.wait_group %0;" ::"n"(N) : "memory"); }
__device__ __forceinline__ void fence_async_smem() { asm volatile("fence.proxy.async.shared::cta;" ::: "memory"); }
__device__ __forceinline__ void fence_async_global() { asm volatile("fence.proxy.async.global;" ::: "memory"); }
__device__ __forceinline__ void prefetch_tmap(const CUtensorMap* tm) {
    asm volatile("prefetch.tensormap [%0];" ::"l"(tm) : "memory");
}
__device__ __forceinline__ unsigned long long ld_acquire64(const unsigned long long* p) {
    unsigned long long v; asm volatile("ld.acquire.gpu.global.u64 %0, [%1];" : "=l"(v) : "l"(p) : "memory"); return v;
}
__device__ __forceinline__ unsigned load_epoch(int b) {
    unsigned v; asm volatile("ld.global.u32 %0, [%1];" : "=r"(v) : "l"(at(g_epoch, b * 4)) : "memory"); return v + 1;
}
__device__ __forceinline__ unsigned ld_relaxed(const void* p) {
    unsigned v; asm volatile("ld.relaxed.gpu.global.u32 %0, [%1];" : "=r"(v) : "l"(p) : "memory"); return v;
}
__device__ __forceinline__ unsigned long long ld_relaxed64(const unsigned long long* p) {
    unsigned long long v; asm volatile("ld.relaxed.gpu.global.u64 %0, [%1];" : "=l"(v) : "l"(p) : "memory"); return v;
}
__device__ __forceinline__ void red_max64(unsigned long long* p, unsigned long long v) {
    asm volatile("red.relaxed.gpu.global.max.u64 [%0], %1;" ::"l"(p), "l"(v) : "memory");
}
__device__ __forceinline__ uint4 ld_relaxed128(const uint4* p) {
    uint4 v;
    asm volatile("{\n.reg .b128 t;\n.reg .b64 lo, hi;\nld.relaxed.gpu.global.b128 t, [%4];\nmov.b128 {lo, hi}, t;\n"
                 "mov.b64 {%0, %1}, lo;\nmov.b64 {%2, %3}, hi;\n}"
                 : "=r"(v.x), "=r"(v.y), "=r"(v.z), "=r"(v.w) : "l"(p) : "memory");
    return v;
}
__device__ __forceinline__ void st_relaxed128(uint4* p, const uint4& v) {
    asm volatile("{\n.reg .b128 t;\n.reg .b64 lo, hi;\nmov.b64 lo, {%1, %2};\nmov.b64 hi, {%3, %4};\nmov.b128 t, {lo, hi};\n"
                 "st.relaxed.gpu.global.b128 [%0], t;\n}"
                 ::"l"(p), "r"(v.x), "r"(v.y), "r"(v.z), "r"(v.w) : "memory");
}
__device__ __forceinline__ void st_relaxed64(unsigned long long* p, unsigned long long v) {
    asm volatile("st.relaxed.gpu.global.u64 [%0], %1;" ::"l"(p), "l"(v) : "memory");
}
__device__ __forceinline__ void st_release8(void* p, unsigned v) {
    asm volatile("st.release.gpu.global.u8 [%0], %1;" ::"l"(p), "r"(v) : "memory");
}
__device__ __forceinline__ uint64_t policy_evict_first() {
    uint64_t pol;
    asm("createpolicy.fractional.L2::evict_first.b64 %0, 1.0;" : "=l"(pol));
    return pol;
}
__device__ __forceinline__ uint4 ldg_stream(const void* p, uint64_t pol) {
    uint4 v;
    asm volatile("ld.global.nc.L1::no_allocate.L2::cache_hint.v4.u32 {%0,%1,%2,%3}, [%4], %5;"
                 : "=r"(v.x), "=r"(v.y), "=r"(v.z), "=r"(v.w) : "l"(p), "l"(pol));
    return v;
}
template <int ID, int N> __device__ __forceinline__ void named_arrive() { asm volatile("bar.arrive %0, %1;" ::"n"(ID), "n"(N) : "memory"); }
template <int ID, int N> __device__ __forceinline__ void named_bar() { asm volatile("bar.sync %0, %1;" ::"n"(ID), "n"(N) : "memory"); }

__device__ __forceinline__ float bf_lo(uint32_t u) { return __uint_as_float(u << 16); }
__device__ __forceinline__ float bf_hi(uint32_t u) { return __uint_as_float(u & 0xffff0000u); }
__device__ __forceinline__ uint32_t pack_bf(float lo, float hi) {
    uint32_t r; asm("cvt.rn.bf16x2.f32 %0, %1, %2;" : "=r"(r) : "f"(hi), "f"(lo)); return r;
}
__device__ __forceinline__ float rbf(float v) { return __uint_as_float(pack_bf(0.f, v)); }
__device__ __forceinline__ float sqrt_f(float v) { float r; asm("sqrt.approx.f32 %0, %1;" : "=f"(r) : "f"(v)); return r; }
__device__ __forceinline__ float rcp_f(float v) { float r; asm("rcp.approx.f32 %0, %1;" : "=f"(r) : "f"(v)); return r; }
__device__ __forceinline__ float silu_f(float z) { return __fdividef(z, 1.0f + __expf(-z)); }
__device__ __forceinline__ uint32_t bsub2(uint32_t a, uint32_t b) {
    uint32_t r; asm("sub.rn.bf16x2 %0, %1, %2;" : "=r"(r) : "r"(a), "r"(b)); return r;
}
__device__ __forceinline__ uint32_t bfma2(uint32_t a, uint32_t b, uint32_t c) {
    uint32_t r; asm("fma.rn.bf16x2 %0, %1, %2, %3;" : "=r"(r) : "r"(a), "r"(b), "r"(c)); return r;
}
__device__ __forceinline__ uint32_t norm2(uint32_t xv, float m, float rinv) {
    uint32_t t = pack_bf(bf_lo(xv) - m, bf_hi(xv) - m);
    return pack_bf(bf_lo(t) * rinv, bf_hi(t) * rinv);
}
__device__ __forceinline__ float gate1(float z) {
    if (TANH) {
        float t;
        const float h = 0.5f * z;
        asm("tanh.approx.f32 %0, %1;" : "=f"(t) : "f"(h));
        return fmaf(h, t, h);
    }
    float e, r;
    asm("ex2.approx.ftz.f32 %0, %1;" : "=f"(e) : "f"(z * -1.4426950408889634f));
    asm("rcp.approx.ftz.f32 %0, %1;" : "=f"(r) : "f"(1.0f + e));
    return z * r;
}
__device__ __forceinline__ uint32_t gate2(uint32_t xv, uint32_t mean2, float r0, float r1) {
    const uint32_t t = bsub2(xv, mean2);
    return pack_bf(gate1(bf_lo(t) * r0), gate1(bf_hi(t) * r1));
}
__device__ __forceinline__ uint32_t silu2(uint32_t z) { return pack_bf(silu_f(bf_lo(z)), silu_f(bf_hi(z))); }

__device__ __forceinline__ void stmatrix4(uint32_t addr, uint32_t r0, uint32_t r1, uint32_t r2, uint32_t r3) {
    asm volatile("stmatrix.sync.aligned.m8n8.x4.shared.b16 [%0], {%1,%2,%3,%4};"
                 ::"r"(addr), "r"(r0), "r"(r1), "r"(r2), "r"(r3));
}
__device__ __forceinline__ void stmatrix4t(uint32_t addr, uint32_t r0, uint32_t r1, uint32_t r2, uint32_t r3) {
    asm volatile("stmatrix.sync.aligned.m8n8.x4.trans.shared.b16 [%0], {%1,%2,%3,%4};"
                 ::"r"(addr), "r"(r0), "r"(r1), "r"(r2), "r"(r3));
}
__device__ __forceinline__ void ldmatrix4t(uint32_t addr, uint32_t& r0, uint32_t& r1, uint32_t& r2, uint32_t& r3) {
    asm volatile("ldmatrix.sync.aligned.m8n8.x4.trans.shared.b16 {%0,%1,%2,%3}, [%4];"
                 : "=r"(r0), "=r"(r1), "=r"(r2), "=r"(r3) : "r"(addr));
}

__device__ __forceinline__ void wg_fence() { asm volatile("wgmma.fence.sync.aligned;" ::: "memory"); }
__device__ __forceinline__ void wg_commit() { asm volatile("wgmma.commit_group.sync.aligned;" ::: "memory"); }
template <int N> __device__ __forceinline__ void wg_wait() { asm volatile("wgmma.wait_group.sync.aligned %0;" ::"n"(N) : "memory"); }

__host__ __device__ constexpr uint32_t desc_lo(uint32_t addr, uint32_t lbo) { return ((addr & 0x3FFFF) >> 4) | ((lbo >> 4) << 16); }
#define DESC_HI "0x40000040"

#define R8(a, o) "+f"(a[(o) + 0]), "+f"(a[(o) + 1]), "+f"(a[(o) + 2]), "+f"(a[(o) + 3]), \
                 "+f"(a[(o) + 4]), "+f"(a[(o) + 5]), "+f"(a[(o) + 6]), "+f"(a[(o) + 7])
#define R64(a, o) R8(a, (o) + 0), R8(a, (o) + 8), R8(a, (o) + 16), R8(a, (o) + 24), \
                  R8(a, (o) + 32), R8(a, (o) + 40), R8(a, (o) + 48), R8(a, (o) + 56)

template <int O, int TA>
__device__ __forceinline__ void wgmma128(float (&a)[128], uint32_t da, uint32_t db, int scale_d) {
    asm volatile(
        "{\n.reg .pred p;\n.reg .b64 da, db;\nsetp.ne.b32 p, %66, 0;\n"
        "mov.b64 da, {%64, " DESC_HI "};\nmov.b64 db, {%65, " DESC_HI "};\n"
        "wgmma.mma_async.sync.aligned.m64n128k16.f32.bf16.bf16 "
        "{%0,%1,%2,%3,%4,%5,%6,%7,%8,%9,%10,%11,%12,%13,%14,%15,"
        "%16,%17,%18,%19,%20,%21,%22,%23,%24,%25,%26,%27,%28,%29,%30,%31,"
        "%32,%33,%34,%35,%36,%37,%38,%39,%40,%41,%42,%43,%44,%45,%46,%47,"
        "%48,%49,%50,%51,%52,%53,%54,%55,%56,%57,%58,%59,%60,%61,%62,%63},"
        "da, db, p, 1, 1, %67, 0;\n}"
        : R64(a, O)
        : "r"(da), "r"(db), "r"(scale_d), "n"(TA));
}
template <int O>
__device__ __forceinline__ void wgmma128_rs(float (&a)[128], const uint32_t* f, uint32_t db) {
    asm volatile(
        "{\n.reg .b64 db;\nmov.b64 db, {%68, 8};\n"
        "wgmma.mma_async.sync.aligned.m64n128k16.f32.bf16.bf16 "
        "{%0,%1,%2,%3,%4,%5,%6,%7,%8,%9,%10,%11,%12,%13,%14,%15,"
        "%16,%17,%18,%19,%20,%21,%22,%23,%24,%25,%26,%27,%28,%29,%30,%31,"
        "%32,%33,%34,%35,%36,%37,%38,%39,%40,%41,%42,%43,%44,%45,%46,%47,"
        "%48,%49,%50,%51,%52,%53,%54,%55,%56,%57,%58,%59,%60,%61,%62,%63},"
        "{%64, %65, %66, %67}, db, 1, 1, 1, 0;\n}"
        : R64(a, O)
        : "r"(f[0]), "r"(f[1]), "r"(f[2]), "r"(f[3]), "r"(db));
}
template <int O>
__device__ __forceinline__ void fence_regs64(float (&a)[128]) {
    asm volatile("" : R64(a, O)::"memory");
}

struct Params {
    const __nv_bfloat16* x;
    const __nv_bfloat16* dre;
    const __nv_bfloat16* dim;
    const __nv_bfloat16* wr;
    const __nv_bfloat16* wg;
    const __nv_bfloat16* wu;
    const __nv_bfloat16* wd;
    uint32_t zero;
#define AB g_ab
};

__device__ __forceinline__ float warp_sum(float v) {
#pragma unroll
    for (int o = 16; o; o >>= 1) v += __shfl_xor_sync(0xffffffffu, v, o);
    return v;
}
__device__ __forceinline__ void fma8(float* acc, const uint4& w, float s) {
    acc[0] += s * bf_lo(w.x); acc[1] += s * bf_hi(w.x); acc[2] += s * bf_lo(w.y); acc[3] += s * bf_hi(w.y);
    acc[4] += s * bf_lo(w.z); acc[5] += s * bf_hi(w.z); acc[6] += s * bf_lo(w.w); acc[7] += s * bf_hi(w.w);
}
__device__ __forceinline__ int POS(int t) { return (t & ~15) | ((t & 6) << 1) | ((t & 8) >> 2) | (t & 1); }
__host__ __device__ constexpr int PSLOT(int j) { return j < 4 ? j : (j & 1) + ((j & 2) ? 0 : 4); }
__host__ __device__ constexpr int PPAR(int j) { return j < 4 ? 0 : ((j >> 2) ^ (j >> 1) ^ 1) & 1; }
__host__ __device__ constexpr int DSLOT(int it) { return (it & 3) + 2; }
__device__ __forceinline__ int SREC(int t) { return (t & ~15) | ((t & 3) << 2) | ((t >> 2) & 3); }
__device__ __forceinline__ int KO(int cl) { return ((cl & 1) << 1) | (cl >> 1); }

__device__ __forceinline__ unsigned long long* sync_words() {
    uint32_t t;
    asm volatile("mov.u32 %0, %%smid;" : "=r"(t));
    t >>= 1;
    const uint32_t u = t - 32;
    return at(g_sync, (t < 32 ? t & 7 : t < 60 ? (SDOM ? 1 : 8) + u - 7 * ((u * 37) >> 8) : 15) * 128);
}

__global__ void __cluster_dims__(2, 1, 1) __launch_bounds__(NTHREADS, 1)
fnet_fused_kernel(const __grid_constant__ CUtensorMap tm_x, const __grid_constant__ CUtensorMap tm_dre,
                  const __grid_constant__ CUtensorMap tm_dim, const __grid_constant__ CUtensorMap tm_cre,
                  const __grid_constant__ CUtensorMap tm_cim, const __grid_constant__ CUtensorMap tm_out,
                  const Params P) {
    extern __shared__ __align__(1024) uint8_t smem[];
    const unsigned long long tstart = clock64();
    const uint32_t sb = smem_u32(smem);
    const int tid = threadIdx.x, lane = tid & 31;
    const int warp = __shfl_sync(0xffffffffu, tid >> 5, 0);
    const int pr = blockIdx.x >> 1, p7 = ((pr - 36) * 37) >> 8;
    const int c = blockIdx.x & 1;
    const int gi = pr < 4 ? 7 : pr < 36 ? 2 * ((pr - 4) & 7) + (((pr - 4) >> 2) & 1) : 2 * (pr - 36 - 7 * p7) + 1 + (pr - 36 - 7 * p7 > 2);
    const int g = gi & 7;
    const int r = (gi >> 3) * 4 + (pr < 4 ? pr : pr < 36 ? (pr - 4) >> 3 : p7);
#define BLK(n) (ORD ? (n) - ((n) <= g) : (g + (n)) & 7)
    const int grp = 2 * r + c;
    const int b = g * 16 + grp;
    const uint32_t bar0 = sb + OFF_BAR;
    const uint32_t zero = P.zero;
#define BAR(i) (bar0 + 8u * (i))
#define XBAR(i) (sb + OFF_XB + 64 + 8u * (i))
#define CLUSTER_ARRIVE() asm volatile("barrier.cluster.arrive.relaxed.aligned;" ::: "memory")
#define CLUSTER_WAIT() asm volatile("barrier.cluster.wait.aligned;" ::: "memory")
    if ((sb & 0xffffffu) != SB0) return;

#define LOAD0(it) do { \
            mbar_expect_tx(BAR(B_FS + DSLOT(it)), SLOT); tma_2d(sb + OFF_S + DSLOT(it) * SLOT, tmD, (it) * 64, r * 128, BAR(B_FS + DSLOT(it))); \
            mbar_expect_tx(BAR(B_FL + (it)), SLOT); tma_2d(sb + OFF_L + (it) * SLOT, &tm_x, (it) * 64, g * 256, BAR(B_FL + (it))); \
            mbar_expect_tx(BAR(B_FL + 4 + (it)), SLOT); tma_2d(sb + OFF_L + (4 + (it)) * SLOT, &tm_x, (it) * 64, g * 256 + 128, BAR(B_FL + 4 + (it))); \
        } while (0)
    if (warp == W0) {
        if (elect_one()) {
            const CUtensorMap* tmD = c ? &tm_dim : &tm_dre;
            if (PFX & 2) prefetch_tmap(tmD);
            if (PFX & 1) prefetch_tmap(&tm_x);
            mbar_init(BAR(B_FS + 2), 1); mbar_init(BAR(B_FL), 1); mbar_init(BAR(B_FL + 4), 1);
            asm volatile("fence.mbarrier_init.release.cluster;" ::: "memory");
            LOAD0(0);
        }
        __syncwarp();
    }
    if (warp == 12) {
        if (elect_one()) {
#pragma unroll
            for (int i = 0; i < B_COUNT; i++)
                if (i != B_FS + 2 && i != B_FL && i != B_FL + 4)
                    mbar_init(BAR(i), (i >= B_ES && i < B_FL) || i == B_GO ? 2 : i == B_STATS || i == B_LST ? 4 : 1);
#pragma unroll
            for (int i = 0; i < 12; i++) mbar_init(XBAR(i), 1);
#pragma unroll
            for (int i = 0; i < 4; i++) mbar_expect_tx(BAR(B_RECV + i), SLOT / 2);
            mbar_expect_tx(BAR(B_PEER), 1024); mbar_expect_tx(BAR(B_H), 128);
            *reinterpret_cast<volatile uint32_t*>(smem + OFF_SEL + 8) = 0;
            asm volatile("fence.mbarrier_init.release.cluster;" ::: "memory");
            fence_async_smem();
        }
        __syncwarp();
    }
    CLUSTER_ARRIVE();

    if (warp >= 12) {
        asm volatile("setmaxnreg.dec.sync.aligned.u32 %0;" ::"n"(PROD_REGS));
        CLUSTER_WAIT();
        if (warp == 12) {
            if (elect_one()) {
                const CUtensorMap* tmD = c ? &tm_dim : &tm_dre;
#define XROWS(k) do { mbar_expect_tx(XBAR(k), 8192); bulk_g2s(sb + OFF_S + (k) * 8192, at(P.x, (b * 16 + (k) * 4) * D_ * 2), 8192, XBAR(k)); } while (0)
                int k = 0;
#pragma unroll 1
                for (int it = 1; it < 16; it++) {
                    if (it < 4) { if (LDEL) sleep_until((uint32_t)tstart + LDEL + (it - 1) * LGAP); LOAD0(it); }
                    else {
                        const int s = DSLOT(it);
                        mbar_wait(BAR(B_ES + s), ((it >> 2) & 1) ^ 1);
                        TRACE(it);
                        mbar_expect_tx(BAR(B_FS + s), SLOT);
                        tma_2d(sb + OFF_S + s * SLOT, tmD, it * 64, r * 128, BAR(B_FS + s));
                    }
                    while (((XS >> (4 * k)) & 15) == it) { XROWS(k); k++; }
                }
                const unsigned ep = load_epoch(b), e8 = ep & 0xffu;
                const uint8_t* abg = at(AB, grp * 32 * SLOT);
                const unsigned long long* fl = at(g_flag, grp * 128);
                unsigned long long rdy = ld_acquire64(fl);
                mbar_wait(BAR(B_SRD), 0);
                st_release8(at(g_flag, grp * 128 + g), e8);
                PROF_T(7);
                int j = 4;
#pragma unroll 1
                for (int cl = 0; cl < 4; cl++) {
                    if (cl) rdy = ld_acquire64(fl + cl);
                    fence_async_global();
#pragma unroll 1
                    for (int n = 1; n < 8; n++, j++) {
                        const int q = BLK(n), s = (j & 1) + ((j & 2) ? 0 : 4);
                        mbar_wait(BAR(B_ES + s), ((j >> 2) ^ (j >> 1)) & 1);
                        if (j == 7) mbar_wait(BAR(B_SRD + 1), 0);
                        if (((unsigned)(rdy >> (8 * q)) & 0xffu) != e8) {
                            int m = 0;
                            do { rdy = ld_acquire64(fl + cl); } while (((unsigned)(rdy >> (8 * q)) & 0xffu) != e8 && ++m < SPIN_LIMIT);
                            fence_async_global();
                        }
                        TRACE(16 + j);
                        mbar_expect_tx(BAR(B_FS + s), SLOT);
                        bulk_g2s(sb + OFF_S + s * SLOT, at(abg, (4 * q + KO(cl)) * SLOT), SLOT, BAR(B_FS + s));
                    }
                }
                *at(g_epoch, b * 4) = ep;
            }
        } else if (warp < 15) {
            if (elect_one()) {
                const int w = warp - 13, row0 = g * 256 + w * 128;
                const CUtensorMap* tmC = c ? &tm_cim : &tm_cre;
                const uint32_t fb = BAR(B_FL + 4 * w), eb = BAR(B_EL + 4 * w), dst = sb + OFF_L + w * 4 * SLOT;
                prefetch_tmap(w ? &tm_out : tmC);
                unsigned long long* sy = sync_words();
#define ADOPT(ph, lag) do { const unsigned long long v = ld_relaxed64(sy++); \
                    if (v - (ph) - SYNCMIN < SYNCCAP) *reinterpret_cast<volatile uint32_t*>(smem + OFF_SEL + 8) = (uint32_t)v - (lag); } while (0)
                [[maybe_unused]] unsigned long long mk = 0;
                int n = 0, cl = 0;
#pragma unroll 1
                for (int it = 4; it < 48; it++) {
                    const int s = it & 3;
                    mbar_wait(eb + 8 * s, ((it >> 2) & 1) ^ 1);
                    const unsigned long long ph = clock64() - 1024u * (it - 4);
                    TRACE(64 + w * 64 + it - 4);
                    MARK(it, ph);
                    mbar_expect_tx(fb + 8 * s, SLOT);
                    tma_2d(dst + s * SLOT, it < 16 ? &tm_x : tmC, (it < 16 ? it : 4 * (n ? BLK(n) : g) + KO(cl)) * 64, row0, fb + 8 * s);
                    if (it == PFJ) tma_2d_prefetch(tmC, (4 * g + (r & 3)) * 64, row0);
                    if (it >= 16) {
                        if (it == 19) { n = 1; cl = 0; } else if (it < 19) cl++; else if (++n == 8) { n = 1; cl++; }
                    }
                    if (w == 0) {
                        if (((SYNCS << 4) >> it) & 1) red_max64(sy, ph);
                        if (((SYNCS << (4 + SYNCD)) >> it) & 1) ADOPT(ph, SYNCLAG);
                    }
                }
                {
#pragma unroll 1
                    for (int h = 0; h < 8 / OP; h++) {
                        mbar_wait(eb + 8 * h, 1);
                        fence_async_smem();
                        tma_2d_store(&tm_out, grp * 64, row0 + h * OP * 16, sb + OFF_S + (2 + w) * SLOT + h * OP * 2048);
                        bulk_commit();
                    }
                    FINISH(w);
                }
            }
        } else {
            const unsigned ep = load_epoch(b);
            uint4 f[4];
#define GATHER(ptr, cnt, valid) do { int n = 0; bool ok; do { ok = true; \
                _Pragma("unroll") for (int i = 0; i < (cnt); i++) { f[i] = ld_relaxed128((ptr) + i * 32); ok = ok && (valid); } \
                if (__all_sync(0xffffffffu, ok)) break; \
                __nanosleep(GSL); \
            } while (++n < SPIN_LIMIT); } while (0)
            {
                sleep_until((uint32_t)tstart + 6000);
                const uint4* keys = at(reinterpret_cast<const uint4*>(g_key), lane * 16);
                bool mine = false;
                int n = 0;
                do {
                    f[0] = ld_relaxed128(keys); f[1] = ld_relaxed128(keys + 32);
                    if (__all_sync(0xffffffffu, f[0].y == ep && f[0].w == ep && f[1].y == ep && f[1].w == ep)) break;
                    if (!mine) {
                        mbar_wait(BAR(B_LST), 0);
                        const uint4 k = *reinterpret_cast<const uint4*>(smem + OFF_XB);
                        if (lane == 0) st_relaxed64(at(g_key, b * 8), ((unsigned long long)ep << 32) | max(max(k.x, k.y), max(k.z, k.w)));
                        mine = true;
                    }
                    __nanosleep(GSL);
                } while (++n < SPIN_LIMIT);
                const unsigned key = __reduce_max_sync(0xffffffffu, max(max(f[0].x, f[0].z), max(f[1].x, f[1].z)));
                if (lane == 0) { *reinterpret_cast<unsigned*>(smem + OFF_SEL) = key; mbar_arrive(BAR(B_SEL)); PROF_T(8); }
            }
            if (elect_one()) {
#pragma unroll 1
                for (int cl = 0; cl < 4; cl++) {
                    uint8_t* dst = at(AB, (grp * 32 + 4 * g + KO(cl)) * SLOT);
                    const uint32_t src = sb + OFF_S + cl * SLOT, chunk = cl ? 4096 : SLOT;
                    mbar_wait(BAR(B_FS + cl), 0);
                    if (RF) fence_async_smem();
                    if (cl == 0) PROF_T(3);
                    uint32_t t0 = clock32() + (cl == 1 ? PDEL : 0);
#pragma unroll 1
                    for (uint32_t o = 0; o < SLOT; o += chunk) {
                        sleep_until(t0);
                        bulk_s2g(dst + o, src + o, chunk);
                        bulk_commit();
                        t0 += PGAP;
                    }
                    bulk_wait<0>();
                    TRACE(252 + cl);
                    if (cl < 2) mbar_arrive(BAR(B_SRD + cl));
                    else {
                        mbar_wait(BAR(B_ES + cl), 0);
                        mbar_expect_tx(BAR(B_FS + cl), SLOT);
                        tma_2d(src, &tm_x, grp * 64, g * 256 + (cl - 2) * 128, BAR(B_FS + cl));
                    }
                    if (cl) st_release8(at(g_flag, grp * 128 + cl * 8 + g), ep & 0xffu);
                    if (cl == 1) PROF_T(5);
                    if (cl == 3) PROF_T(4);
                }
            }
        }
    } else if (warp >= 8) {
        asm volatile("setmaxnreg.dec.sync.aligned.u32 %0;" ::"n"(512 - PROD_REGS - 2 * CONS_REGS));
        const int aw = warp - 8, mt = tid - 256;
        unsigned ep;
        {
            const uint8_t* rp = smem + OFF_S + aw * 2048 + lane * 16;
            const __nv_bfloat16* dp = at(c ? P.dim : P.dre, (r * 128 + g * 16 + aw * 4) * D_ * 2);
            float wf[32], sw = 0.f;
#pragma unroll
            for (int i = 0; i < 4; i++) {
                const uint4 w = __ldg(reinterpret_cast<const uint4*>(at(P.wr, lane * 16) + i * 256));
                const uint32_t wv[4] = {w.x, w.y, w.z, w.w};
#pragma unroll
                for (int e = 0; e < 4; e++) { wf[8 * i + 2 * e] = bf_lo(wv[e]); wf[8 * i + 2 * e + 1] = bf_hi(wv[e]); sw = (sw + bf_lo(wv[e])) + bf_hi(wv[e]); }
            }
            ep = load_epoch(b);
            sw = warp_sum(sw);
            CLUSTER_WAIT();
            float x0[4] = {}, s1[4] = {}, s2[4] = {}, sx[4] = {}, sd[4] = {};
#define PUSH(a, v) do { a[0] = a[1]; a[1] = a[2]; a[2] = a[3]; a[3] = v; } while (0)
#pragma unroll 1
            for (int k = 0; k < 4; k++) {
                mbar_wait(XBAR(k), 0);
                uint4 v[4];
#pragma unroll
                for (int i = 0; i < 4; i++) v[i] = *reinterpret_cast<const uint4*>(rp + k * 8192 + i * 512);
                uint32_t sh = v[0].x << 16;
                float a1s = 0.f, a2s = 0.f, axs = 0.f;
#pragma unroll
                for (int i = 0; i < 4; i++) {
                    sh = __shfl_sync(0xffffffffu, sh | (__float_as_uint(axs) & zero), 0);
                    const uint32_t xv[4] = {v[i].x, v[i].y, v[i].z, v[i].w};
#pragma unroll
                    for (int e = 0; e < 4; e++) {
                        const float a0 = bf_lo(xv[e]) - __uint_as_float(sh), a1 = bf_hi(xv[e]) - __uint_as_float(sh);
                        a1s += a0 + a1;
                        a2s = fmaf(a0, a0, fmaf(a1, a1, a2s));
                        axs = fmaf(a0, wf[8 * i + 2 * e], fmaf(a1, wf[8 * i + 2 * e + 1], axs));
                    }
                }
                PUSH(x0, __uint_as_float(sh)); PUSH(s1, a1s); PUSH(s2, a2s); PUSH(sx, axs);
                fence_async_smem();
                __syncwarp();
                if (elect_one()) {
                    const uint32_t db = XBAR(k == 3 ? 8 + aw : 4 + aw);
                    if (k == 0 || k == 3) mbar_expect_tx(db, k ? 2048 : 6144);
                    bulk_g2s(sb + OFF_S + k * 8192 + aw * 2048, dp + k * D_, 2048, db);
                }
            }
#define FOLD4(a) do { const bool u16 = lane & 16, u8 = lane & 8; \
                float p0 = (u16 ? a[2] : a[0]) + __shfl_xor_sync(0xffffffffu, u16 ? a[0] : a[2], 16); \
                float p1 = (u16 ? a[3] : a[1]) + __shfl_xor_sync(0xffffffffu, u16 ? a[1] : a[3], 16); \
                a[0] = (u8 ? p1 : p0) + __shfl_xor_sync(0xffffffffu, u8 ? p0 : p1, 8); \
                _Pragma("unroll") for (int o = 4; o; o >>= 1) a[0] += __shfl_xor_sync(0xffffffffu, a[0], o); } while (0)
#pragma unroll 1
            for (int k = 0; k < 4; k++) {
                mbar_wait(XBAR(k == 3 ? 8 + aw : 4 + aw), 0);
                float run = 0.f;
#pragma unroll
                for (int i = 0; i < 4; i++) {
                    const uint4 v = *reinterpret_cast<const uint4*>(rp + k * 8192 + i * 512);
                    const uint32_t dv[4] = {v.x, v.y, v.z, v.w};
#pragma unroll
                    for (int e = 0; e < 4; e++) run += bf_lo(dv[e]) + bf_hi(dv[e]);
                }
                PUSH(sd, run);
            }
            FOLD4(sd); FOLD4(s1); FOLD4(s2); FOLD4(sx);
            const float nb = __shfl_down_sync(0xffffffffu, sd[0], 8);
            if ((lane & 15) == 0)
                st_relaxed128(at(g_rs, (grp * 64 + g * 8 + aw * 2 + (lane >> 4)) * 16), make_uint4(__float_as_uint(sd[0]), ep, __float_as_uint(nb), ep));
            if (mt == 0) PROF_T(6);
            const int rr = lane >> 3;
            const float c0 = rr == 0 ? x0[0] : rr == 1 ? x0[1] : rr == 2 ? x0[2] : x0[3];
            const float dm = s1[0] * (1.0f / D_);
            const float mb = rbf(c0 + dm);
            const float rinv = rcp_f(rbf(sqrt_f(rbf(rbf(fmaxf(s2[0] * (1.0f / D_) - dm * dm, 0.f)) + 1e-5f))));
            if ((lane & 7) == 0) st_relaxed128(at(g_stat, (b * 16 + aw * 4 + rr) * 16), make_uint4(__float_as_uint(mb), __float_as_uint(rinv), ep, 0));
            unsigned u = __bfloat16_as_ushort(__float2bfloat16_rn((sx[0] + (c0 - mb) * sw) * rinv));
            u = (u & 0x8000u) ? (~u & 0xffffu) : (u | 0x8000u);
            u = (u << 16) | (0xffffu - (unsigned)(b * 16 + rr * 4 + aw));
            u = __reduce_max_sync(0xffffffffu, u);
            if (lane == 0) { *reinterpret_cast<unsigned*>(smem + OFF_XB + aw * 4) = u; mbar_arrive(BAR(B_LST)); }
            if (mt == 0) PROF_T(2);
            named_bar<4, 128>();
            if (mt < 12) asm volatile("mbarrier.inval.shared::cta.b64 [%0];" ::"r"(XBAR(mt)) : "memory");
            uint4 f[4];
            if (aw < 2) {
                const int t = SREC(aw * 128 + lane);
                GATHER(at(g_stat, (g * 256 + aw * 128 + lane) * 16), 4, f[i].z == ep);
#pragma unroll
                for (int i = 0; i < 4; i++) {
                    *reinterpret_cast<uint32_t*>(smem + OFF_RSTD + (POS(t) + i * 32) * 4) = f[i].y;
                    *reinterpret_cast<uint16_t*>(smem + OFF_MEAN + (POS(t) + i * 32) * 2) = (uint16_t)(f[i].x >> 16);
                }
            } else {
                const int e2 = (aw - 2) * 32 + lane;
                GATHER(at(g_rs, (grp * 64 + e2) * 16), 1, f[i].y == ep && f[i].w == ep);
#pragma unroll
                for (int i = 0; i < 2; i++) {
                    const float v = __uint_as_float(i ? f[0].z : f[0].x);
                    const float hi = rbf(v), mid = rbf(v - hi), lo = v - hi - mid;
                    *reinterpret_cast<uint4*>(smem + OFF_RS + (e2 * 2 + i) * 16) = make_uint4(pack_bf(hi, mid), pack_bf(lo, 0.f), 0, 0);
                }
            }
            fence_async_smem();
            __syncwarp();
            if (lane == 0) mbar_arrive(BAR(B_STATS));
            if (mt == 127) PROF_T(9);
        }
        const int pair = g * 7 + r;
        if (r < 7) {
            const uint64_t pol = policy_evict_first();
            const __nv_bfloat16* wp = at((aw & 1) ? P.wu : P.wg, ((c * 512 + (aw >> 1) * 256 + (lane >> 3) * 8) * F_ + pair * 64 + (lane & 7) * 8) * 2);
            uint4 b0[8], b1[8];
#define FILL(buf, str) do { _Pragma("unroll") for (int q = 0; q < 8; q++) buf[q] = ldg_stream(wp + q * (str), pol); } while (0)
            FILL(b0, F_);
            mbar_wait(BAR(B_SEL), 0);
            uint4 xn;
            {
                const int sel = 0xffff - (int)(*reinterpret_cast<volatile unsigned*>(smem + OFF_SEL) & 0xffffu);
                xn = __ldg(reinterpret_cast<const uint4*>(at(P.x, (sel * D_ + c * 512 + (aw >> 1) * 256 + (lane & 7) * 32 + (lane >> 3) * 8) * 2)));
                uint4 f[1];
                GATHER(at(g_stat, SREC(sel) * 16), 1, f[i].z == ep);
                if (NLATE && mbar_test(BAR(B_QUIET), 0)) mbar_wait_sleep(BAR(B_GO), 0);
                const float m = __uint_as_float(f[0].x), ri = __uint_as_float(f[0].y);
                xn = make_uint4(norm2(xn.x, m, ri), norm2(xn.y, m, ri), norm2(xn.z, m, ri), norm2(xn.w, m, ri));
            }
            float ag[8];
#pragma unroll
            for (int i = 0; i < 8; i++) ag[i] = 0.f;
            const uint32_t stag = (aw * 4 + (grp & 3)) * ESTAG;
            uint32_t te = clock32() + stag;
            bool paused = !QUIET;
#define ROUND(cur, nxt, rd) do { \
                if (!paused && mbar_test(BAR(B_QUIET), 0)) { mbar_wait_sleep(BAR(B_GO), 0); te = clock32() + stag; paused = true; } \
                sleep_until(te); \
                te = clock32() + (paused ? EGAP2 : EGAP1); \
                if (lane == 0) TRACE(192 + aw * 12 + (rd)); \
                if ((rd) == 7) wp = at(P.wd - 16 * D_, ((pair * 64 + (lane >> 4) * 8) * D_ + c * 512 + aw * 128 + (lane & 15) * 8) * 2); \
                wp = at(wp, ((rd) < 7 ? 64 * F_ : 32 * D_) + (cur[7].x & zero)); \
                if ((rd) < 7) FILL(nxt, F_); else if ((rd) != 8 && (rd) < 11) FILL(nxt, D_); \
                _Pragma("unroll") for (int q = 0; q < 8; q += 2) { \
                    uint32_t xw = __shfl_sync(0xffffffffu, q == 0 ? xn.x : q == 2 ? xn.y : q == 4 ? xn.z : xn.w, (lane & 24) | ((rd) & 7)); \
                    fma8(ag, cur[q], bf_lo(xw)); \
                    if (YLD > 1) { yield(ag[7], zero); xw = __shfl_sync(0xffffffffu, xw, lane); } \
                    fma8(ag, cur[q + 1], bf_hi(xw)); \
                    if (q < 6) yield(ag[7], zero); \
                } } while (0)
#pragma unroll 1
            for (int rd = 0; rd < 12; rd += 2) {
                ROUND(b0, b1, rd);
                ROUND(b1, b0, rd + 1);
                if (rd == 6) { wp += 16 * D_; FILL(b1, D_); wp -= 16 * D_; }
                if (rd == 6 || rd == 10) {
#pragma unroll
                    for (int i = 0; i < 8; i++) ag[i] += __shfl_xor_sync(0xffffffffu, ag[i], 16);
                }
                if (rd == 6) {
#pragma unroll
                    for (int i = 0; i < 8; i++) ag[i] += __shfl_xor_sync(0xffffffffu, ag[i], 8);
                    if (lane < 8) {
                        const uint32_t dst = mapa(sb + OFF_XB + (c * 4 + aw) * 128 + (lane & 3) * 32, lane >> 2), pb = mapa(BAR(B_PEER), lane >> 2);
                        st_async4(dst, __float_as_uint(ag[0]), __float_as_uint(ag[1]), __float_as_uint(ag[2]), __float_as_uint(ag[3]), pb);
                        st_async4(dst + 16, __float_as_uint(ag[4]), __float_as_uint(ag[5]), __float_as_uint(ag[6]), __float_as_uint(ag[7]), pb);
                    }
                    if (aw == 3) {
                        mbar_wait_cluster(BAR(B_PEER), 0);
                        const float* ps = reinterpret_cast<const float*>(smem + OFF_XB) + lane;
                        const float go = (ps[0] + ps[64]) + (ps[128] + ps[192]), uo = (ps[32] + ps[96]) + (ps[160] + ps[224]);
                        const float h = rbf(silu_f(rbf(go))) * rbf(uo), ho = __shfl_xor_sync(0xffffffffu, h, 1);
                        asm volatile("st.async.weak.shared::cluster.mbarrier::complete_tx::bytes.b32 [%0], %1, [%2];"
                                     ::"r"(mapa(sb + OFF_H + c * 64 + (lane >> 1) * 4, lane & 1)), "r"((lane & 1) ? pack_bf(ho, h) : pack_bf(h, ho)),
                                       "r"(mapa(BAR(B_H), lane & 1)) : "memory");
                    }
                    mbar_wait_cluster(BAR(B_H), 0);
                    xn = *reinterpret_cast<const uint4*>(smem + OFF_H + (lane & 3) * 32 + (lane >> 4) * 16);
#pragma unroll
                    for (int i = 0; i < 8; i++) ag[i] = 0.f;
                    if (mt == 0) PROF_T(10);
                }
            }
            const int hi = lane >> 4;
            st_relaxed128(at(g_part, pair * 4096 + (c * 8 + aw * 2 + ((lane >> 3) & 1)) * 256 + hi * 128 + (lane & 7) * 16),
                          make_uint4((__float_as_uint(hi ? ag[4] : ag[0]) & ~15u) | (ep & 15u), __float_as_uint(hi ? ag[5] : ag[1]),
                                     __float_as_uint(hi ? ag[6] : ag[2]), __float_as_uint(hi ? ag[7] : ag[3])));
            if (mt == 0) PROF_T(11);
        } else {
            mbar_wait_sleep(BAR(B_SEL), 0);
        }
        const int sel = 0xffff - (int)(*reinterpret_cast<volatile unsigned*>(smem + OFF_SEL) & 0xffffu);
        if ((sel >> 8) == g) {
            const int col = (lane & 7) * 8 + ((lane >> 3) & 1) * 4;
            const uint2 xv = __ldg(reinterpret_cast<const uint2*>(at(P.x, (sel * D_ + grp * 64 + col) * 2)));
            uint4 f[1];
            GATHER(at(g_stat, SREC(sel) * 16), 1, f[i].z == ep);
            const uint4 rec = f[0];
            const uint4* src = at(g_part, (aw * 14 + (lane >> 4)) * 4096 + grp * 256 + (lane & 15) * 16);
            if (r == 7) {
                int n = 0;
                while (((ld_relaxed(src) ^ ep) & 15u) != 0 && ++n < SPIN_LIMIT) __nanosleep(500);
            }
            uint4 t[7];
            int n = 0;
            bool ok;
            do {
                ok = true;
#pragma unroll
                for (int u = 0; u < 7; u++) { t[u] = ld_relaxed128(src + u * 512); ok = ok && ((t[u].x ^ ep) & 15u) == 0; }
            } while (!__all_sync(0xffffffffu, ok) && ++n < SPIN_LIMIT);
            float4 a = make_float4(0.f, 0.f, 0.f, 0.f);
#pragma unroll
            for (int u = 0; u < 7; u++) {
                a.x += __uint_as_float(t[u].x & ~15u); a.y += __uint_as_float(t[u].y); a.z += __uint_as_float(t[u].z); a.w += __uint_as_float(t[u].w);
            }
            a.x += __shfl_xor_sync(0xffffffffu, a.x, 16); a.y += __shfl_xor_sync(0xffffffffu, a.y, 16);
            a.z += __shfl_xor_sync(0xffffffffu, a.z, 16); a.w += __shfl_xor_sync(0xffffffffu, a.w, 16);
            float4* park = reinterpret_cast<float4*>(smem + OFF_XB) + (lane & 15);
            if (lane < 16) park[aw * 16] = a;
            named_bar<4, 128>();
            if (aw == 0) {
                const float4 p1 = park[16], p2 = park[32], p3 = park[48];
                a.x = (a.x + p1.x) + (p2.x + p3.x); a.y = (a.y + p1.y) + (p2.y + p3.y);
                a.z = (a.z + p1.z) + (p2.z + p3.z); a.w = (a.w + p1.w) + (p2.w + p3.w);
                unsigned u = *reinterpret_cast<volatile unsigned*>(smem + OFF_SEL) >> 16;
                u = (u & 0x8000u) ? (u & 0x7fffu) : (~u & 0xffffu);
                const float sg = rbf(__fdividef(1.0f, 1.0f + __expf(-__uint_as_float(u << 16))));
                const float m = __uint_as_float(rec.x), ri = __uint_as_float(rec.y);
                const uint32_t n0 = norm2(xv.x, m, ri), n1 = norm2(xv.y, m, ri);
                uint2 o;
                o.x = silu2(pack_bf(bf_lo(n0) + rbf(rbf(a.x) * sg), bf_hi(n0) + rbf(rbf(a.y) * sg)));
                o.y = silu2(pack_bf(bf_lo(n1) + rbf(rbf(a.z) * sg), bf_hi(n1) + rbf(rbf(a.w) * sg)));
                if (lane < 16) *reinterpret_cast<uint2*>(smem + OFF_H + col * 2) = o;
                __syncwarp();
                if (lane == 0) { mbar_arrive(BAR(B_UPD)); PROF_T(12); }
            }
        }
    } else {
        asm volatile("setmaxnreg.inc.sync.aligned.u32 %0;" ::"n"(CONS_REGS));
        CLUSTER_WAIT();
        const int wg = warp >> 2, wq = warp & 3;
        const int wt = tid & 127;
        float acc[128];
        const uint32_t fL = BAR(B_FL + 4 * wg), eL = BAR(B_EL + 4 * wg);
        const uint32_t dL = desc_lo(SB0 + OFF_L, 16) + wg * 4096;
        constexpr uint32_t dS = desc_lo(SB0 + OFF_S, 16);
        constexpr uint32_t SL = SLOT >> 4;
#define RELEASE(ls, ss) do { if (wt == 0) { mbar_arrive(eL + 8u * (ls)); mbar_arrive(BAR(B_ES + (ss))); } } while (0)
#define WAIT_FULL(ls, lph, ss, sph) do { mbar_wait(BAR(B_FS + (ss)), sph); mbar_wait(fL + 8u * (ls), lph); } while (0)
#define TURN() do { if (wg) named_bar<6, 256>(); else named_bar<5, 256>(); } while (0)
#define PASS() do { if (wg) named_arrive<5, 256>(); else named_arrive<6, 256>(); } while (0)
#define WG_BAR() do { if (wg) named_bar<2, 128>(); else named_bar<1, 128>(); } while (0)
        uint32_t held = 0, tgt = 0;
#define PEEK() do { if (wg == 0) tgt = *reinterpret_cast<volatile uint32_t*>(smem + OFF_SEL + 8); } while (0)
#define HOLD(step) do { if (tgt != held) { held = tgt; sleep_until(tgt + 1024u * (step) - 100u); \
                int n = 0; while ((int)(clock32() - tgt - 1024u * (step)) < 0 && ++n < SPIN_LIMIT) {} } } while (0)
        if (wg == 1) PASS();

#define MMA1_P(O, s, first, pass) do { _Pragma("unroll") for (int kk = 0; kk < 4; kk++) { if (kk == PK && (pass)) PASS(); \
            wgmma128<O, 0>(acc, dL + (s) * SL + kk * 2 + (O) * 8, dS + DSLOT(s) * SL + kk * 2, !((first) && kk == 0)); } \
            if (PK == 4 && (pass)) PASS(); } while (0)
#define MMA1_H(O, s, first) MMA1_P(O, s, first, false)
#define WAIT1(s, ph) WAIT_FULL(s, ph, DSLOT(s), ph)
#define PROBE(ls, lph, ss, sph) (mbar_test(BAR(B_FS + (ss)), sph) & mbar_test(fL + 8u * (ls), lph))
#define REL1(s) RELEASE(s, DSLOT(s))
#pragma unroll 1
        for (int it = 0; it < 12; it++) {
            const int s = it & 3;
            const bool ok = PROBE(s, (it >> 2) & 1, DSLOT(s), (it >> 2) & 1);
            PEEK();
            if (it) { wg_wait<0>(); REL1((it - 1) & 3); }
            if (!ok) WAIT1(s, (it >> 2) & 1);
            HOLD(it);
            TURN();
            wg_fence(); MMA1_H(0, s, it == 0); MMA1_H(64, s, it == 0); wg_commit();
            PASS();
            if (it == QJ && tid == 0) { mbar_arrive(BAR(B_QUIET)); PROF_T(15); }
            if (it == 0 && tid == 0) PROF_T(16);
        }
        TS(12);
        float rs[4] = {};
        uint32_t nm[8] = {};
#define GET_STATS() do { mbar_wait(BAR(B_STATS), 0); \
            const int p0 = POS(wg * 128 + wq * 16 + (lane >> 2));                   \
            const uint32_t msk = (lane & 3) == 0 ? 0xffffffffu : (lane & 3) == 1 ? 0x0000ffffu : 0u; \
            _Pragma("unroll") for (int i = 0; i < 4; i++) { \
                const int p = p0 + (i & 1) * 2 + (i >> 1) * 64; \
                rs[i] = *reinterpret_cast<const float*>(smem + OFF_RSTD + p * 4); \
                const uint32_t m = *reinterpret_cast<const uint16_t*>(smem + OFF_MEAN + p * 2) ^ 0x8000u; \
                nm[i + (i & 2)] = (m | (m << 16)) & msk; \
            } } while (0)
        const bool early = wg || __all_sync(0xffffffffu, mbar_test(BAR(B_STATS), 0));
        if (early && !wg) GET_STATS();
        WAIT1(0, 1);
        TS(13);
        wg_wait<0>(); REL1(3);
        if (wg) GET_STATS();
        TS(14);
        TURN();
        wg_fence();
        MMA1_H(0, 0, false);
        if (QJ == 12 && tid == 0) { mbar_arrive(BAR(B_QUIET)); PROF_T(15); }
        WAIT1(1, 1); wg_fence(); MMA1_H(0, 1, false);
        WAIT1(2, 1); wg_fence(); MMA1_H(0, 2, false); wg_commit();
        if (!early) GET_STATS();
        asm volatile("" : "+r"(nm[0]), "+r"(nm[1]), "+r"(nm[2]), "+r"(nm[3]), "+r"(nm[4]), "+r"(nm[5]), "+r"(nm[6]), "+r"(nm[7])::"memory");
        wg_fence();
        wgmma128_rs<64>(acc, nm + 4, (SB0 + OFF_RS) >> 4);
        wgmma128_rs<0>(acc, nm, (SB0 + OFF_RS) >> 4);
        WAIT1(3, 1); wg_fence(); MMA1_P(0, 3, false, true);
        wg_commit();
        const int mrow = wq * 16 + ((lane >> 3) & 1) * 8 + (lane & 7);
#define EPI1(O, slot, FREE) do { const uint32_t dst = sb + OFF_S + (slot) * SLOT + mrow * 128; \
            uint32_t pk[32]; \
            _Pragma("unroll") for (int i = 0; i < 32; i += 4) { \
                _Pragma("unroll") for (int k = 0; k < 4; k++) \
                    pk[i + k] = pack_bf(acc[(O) + 2 * (i + k)] * rs[(O) / 32 + (k & 1)], acc[(O) + 2 * (i + k) + 1] * rs[(O) / 32 + (k & 1)]); \
                if (i == EF) { FREE; } \
                if (i >= EF) { _Pragma("unroll") for (int v = (i == EF ? 0 : i); v <= i; v += 4) \
                    stmatrix4(dst + ((v >> 4) ^ c ^ 1) * 8192 + ((((v >> 1) & 7) + (lane >> 4)) ^ (lane & 7)) * 16, pk[v], pk[v + 1], pk[v + 2], pk[v + 3]); } } \
            if (!RF) fence_async_smem(); \
            WG_BAR(); \
            if (wt == 0) mbar_arrive(BAR(B_FS + (slot))); } while (0)
        TS(15);
        wg_wait<0>();
        fence_regs64<0>(acc);
        TS(16);
        {
            constexpr int EF = 0;
            EPI1(0, wg, if (wg) mbar_wait(BAR(B_FS), 0));
        }
        TS(17);
        TURN();
        wg_fence();
        MMA1_H(64, 0, false); wg_commit();
        MMA1_H(64, 1, false); wg_commit();
        MMA1_H(64, 2, false); wg_commit();
        wg_wait<2>(); REL1(0);
        MMA1_P(64, 3, false, true); wg_commit();
        TS(18);
        wg_wait<2>(); REL1(1);
        if (RF) { mbar_wait(BAR(B_FS), 0); mbar_wait(BAR(B_FS + 1), 0); fence_async_smem(); }
        wg_wait<1>(); REL1(2);
        wg_wait<0>(); REL1(3);
        fence_regs64<64>(acc);
        TS(19);
        {
            constexpr int EF = EF2;
            EPI1(64, 2 + wg, mbar_wait(BAR(B_ES + 2 + wg), 1));
        }
        TS(20);

        float ac2[128];
#define MMA2_P(O, ls, ss, first, pass) do { _Pragma("unroll") for (int kk = 0; kk < 4; kk++) { if (kk == PK && (pass)) PASS(); \
            wgmma128<O, 1>(ac2, dS + (ss) * SL + kk * 128 + (O) * 8, dL + (ls) * SL + kk * 2, !((first) && kk == 0)); } \
            if (PK == 4 && (pass)) PASS(); } while (0)
#define MMA2_H(O, ls, ss, first) MMA2_P(O, ls, ss, first, false)
#define WAIT2(j) WAIT_FULL((j) & 3, ((j) >> 2) & 1, PSLOT(j), PPAR(j))
#define MMA2(j, pass) do { wg_fence(); MMA2_H(0, (j) & 3, PSLOT(j), (j) == 0); MMA2_P(64, (j) & 3, PSLOT(j), (j) == 0, pass); wg_commit(); } while (0)
#define REL2(j) RELEASE((j) & 3, PSLOT(j))
        if (GOJ == 0 && wt == 0) mbar_arrive(BAR(B_GO));
        WAIT2(0); TURN(); MMA2(0, false);
        WAIT2(1); MMA2(1, true);
        TS(21);
        wg_wait<1>(); REL2(0);
        if (RF) { mbar_wait(BAR(B_FS + 2), 0); mbar_wait(BAR(B_FS + 3), 0); fence_async_smem(); }
        TS(22);
        {
            uint32_t sp = 1;
#pragma unroll 1
            for (int j = 2; j < XJ; j++) {
                const uint32_t ss = PSLOT(j);
                const bool ok = PROBE(j & 3, (j >> 2) & 1, ss, PPAR(j));
                PEEK();
                wg_wait<0>(); RELEASE((j - 1) & 3, sp);
                if (!ok) WAIT_FULL(j & 3, (j >> 2) & 1, ss, PPAR(j));
                HOLD(16 + j);
                TURN();
                wg_fence(); MMA2_H(0, j & 3, ss, false); MMA2_P(64, j & 3, ss, false, true); wg_commit();
                if (j == GOJ && wt == 0) { mbar_arrive(BAR(B_GO)); if (wg == 0) PROF_T(19); }
                sp = ss;
            }
        }
        if (tid == 0) PROF_T(20);
        uint32_t gt[32];
        const uint32_t xrow = sb + OFF_S + (2 + wg) * SLOT + ((lane >> 4) * 8 + (lane & 7)) * 128 + (((2 * wq + ((lane >> 3) & 1)) ^ (lane & 7)) << 4);
        const uint32_t gsign = c ? 0x80008000u : 0u;
        mbar_wait(BAR(B_FS + 2 + wg), 1);
        mbar_wait(BAR(B_SEL), 0);
        const int sel = 0xffff - (int)(*reinterpret_cast<volatile unsigned*>(smem + OFF_SEL) & 0xffffu);
        bool own = (sel >> 7) == 2 * g + wg;
#define PATCH() do { own = false; \
            const uint32_t v0 = *reinterpret_cast<const uint16_t*>(smem + OFF_H + (wq * 16 + (lane >> 2)) * 2) ^ gsign; \
            const uint32_t v1 = *reinterpret_cast<const uint16_t*>(smem + OFF_H + (wq * 16 + (lane >> 2)) * 2 + 16) ^ gsign; \
            const uint32_t pick = (lane & 3) != ((sel >> 1) & 3) ? 0x3210u : (sel & 1) ? 0x5410u : 0x3254u; \
            _Pragma("unroll") for (int i = 0; i < 16; i++) { \
                const uint32_t m = ((sel >> 3) & 15) == i ? pick : 0x3210u; \
                gt[2 * i] = __byte_perm(gt[2 * i], v0, m); \
                gt[2 * i + 1] = __byte_perm(gt[2 * i + 1], v1, m); \
            } } while (0)
#pragma unroll
        for (int v = 0; v < 28 - XJ; v++) {
            WAIT2(XJ + v); wg_wait<0>(); REL2(XJ + v - 1); TURN(); MMA2(XJ + v, true);
            constexpr int NS = 8 / (28 - XJ);
#pragma unroll
            for (int u = v * NS; u < (v + 1) * NS; u++) {
                uint32_t* o = &gt[4 * u];
                ldmatrix4t(xrow + u * 2048, o[0], o[1], o[2], o[3]);
                const float4 r4 = *reinterpret_cast<const float4*>(smem + OFF_RSTD + (wg * 128 + u * 16 + (lane & 3) * 4) * 4);
                const uint2 m2 = *reinterpret_cast<const uint2*>(smem + OFF_MEAN + (wg * 128 + u * 16 + (lane & 3) * 4) * 2);
                o[0] = gate2(o[0], m2.x, r4.x, r4.y) ^ gsign;
                o[1] = gate2(o[1], m2.x, r4.x, r4.y) ^ gsign;
                o[2] = gate2(o[2], m2.y, r4.z, r4.w) ^ gsign;
                o[3] = gate2(o[3], m2.y, r4.z, r4.w) ^ gsign;
                asm volatile("st.shared.v2.u32 [%0], {%1,%2};" ::"r"(sb + OFF_SEL + 16), "r"(o[0] ^ o[1]), "r"(o[2] ^ o[3]) : "memory");
            }
        }
        if (tid == 0) PROF_T(21);
        WAIT2(28);
        wg_wait<0>(); REL2(27);
        if (own) {
            const uint32_t t0 = clock32();
            bool ok;
            while (!(ok = mbar_test(BAR(B_UPD), 0)) && clock32() - t0 < wg * 1400u) __nanosleep(50);
            if (__all_sync(0xffffffffu, ok)) PATCH();
        }
        TS(0);
        TURN();
        wg_fence(); MMA2_H(0, 0, PSLOT(28), false); wg_commit();
        if (wg == 0 || !ASYM) { wg_fence(); MMA2_H(64, 0, PSLOT(28), false); wg_commit(); }
        WAIT2(29); wg_fence(); MMA2_H(0, 1, PSLOT(29), false); wg_commit();
        WAIT2(30); wg_fence(); MMA2_H(0, 2, PSLOT(30), false); wg_commit();
        wg_wait<2>();
        if (tid == 0) mbar_arrive_cluster(mapa(BAR(B_RDY), c ^ 1));
        WAIT2(31); wg_fence(); MMA2_H(0, 3, PSLOT(31), false); wg_commit();
        TS(1);
#define KEEP(i) wgmma128<64, 1>(ac2, dS + PSLOT(29 + ((i) >> 2)) * SL + ((i) & 3) * 128 + 512, dL + (1 + ((i) >> 2)) * SL + ((i) & 3) * 2, 1)
        wg_fence();
#pragma unroll
        for (int i = 0; i < KQ; i++) KEEP(i);
        wg_commit();
        mbar_wait(BAR(B_RDY + wg), 0);
        wg_wait<1>();
        fence_regs64<0>(ac2);
        TS(2);
        wg_fence();
        {
            const uint32_t dst = mapa(sb + OFF_L + wg * SLOT + wt * 16, c ^ 1), rb = mapa(BAR(B_RECV + 2 * wg), c ^ 1);
#pragma unroll
            for (int v = 0; v < 8; v++) {
                if (KQ + v < 12) KEEP(KQ + v);
                if (KQ + v == 11) { wg_commit(); if (wg == 0) PASS(); }
                st_async4(dst + v * 2048, pack_bf(ac2[8 * v + 0], ac2[8 * v + 1]), pack_bf(ac2[8 * v + 2], ac2[8 * v + 3]),
                          pack_bf(ac2[8 * v + 4], ac2[8 * v + 5]), pack_bf(ac2[8 * v + 6], ac2[8 * v + 7]), rb + (v >> 2) * 8);
            }
        }
        if (wg == 1 && ASYM) { wg_fence(); MMA2_H(64, 0, PSLOT(28), false); wg_commit(); }
        TS(3);
        uint32_t xr[32];
#define LDX(v) ldmatrix4t(xrow + (v) * 2048, xr[4 * (v)], xr[4 * (v) + 1], xr[4 * (v) + 2], xr[4 * (v) + 3])
#pragma unroll
        for (int v = 0; v < XE; v++) LDX(v);
        if (wg == 0) {
            wg_wait<0>();
            if (wt == 0) mbar_arrive_cluster(mapa(BAR(B_RDY + 1), c ^ 1));
        }
        TS(4);
        if (own) { mbar_wait(BAR(B_UPD), 0); PATCH(); }
        TS(5);
        uint4 rv[8];
#define FETCH(v0) do { if ((v0) == 0 || (v0) == 4) mbar_wait_cluster(BAR(B_RECV + 2 * wg + (v0) / 4), 0); \
            _Pragma("unroll") for (int v = (v0); v < (v0) + OP; v++) { \
                asm volatile("ld.shared.v4.u32 {%0,%1,%2,%3}, [%4];" : "=r"(rv[v].x), "=r"(rv[v].y), "=r"(rv[v].z), "=r"(rv[v].w) \
                             : "r"(sb + OFF_L + wg * SLOT + v * 2048 + wt * 16) : "memory"); \
                if (v >= XE) LDX(v); } } while (0)
        FETCH(0);
        TS(6);
        wg_wait<0>();
        fence_regs64<64>(ac2);
        TS(7);
#pragma unroll
        for (int v0 = 0; v0 < 8; v0 += OP) {
#pragma unroll
            for (int v = v0; v < v0 + OP; v++) {
                const float* a = &ac2[64 + 8 * v];
                stmatrix4t(xrow + v * 2048,
                           bfma2(bsub2(pack_bf(a[0], a[1]), rv[v].x), gt[4 * v + 0], xr[4 * v + 0]),
                           bfma2(bsub2(pack_bf(a[2], a[3]), rv[v].y), gt[4 * v + 1], xr[4 * v + 1]),
                           bfma2(bsub2(pack_bf(a[4], a[5]), rv[v].z), gt[4 * v + 2], xr[4 * v + 2]),
                           bfma2(bsub2(pack_bf(a[6], a[7]), rv[v].w), gt[4 * v + 3], xr[4 * v + 3]));
            }
            WG_BAR();
            if (wt == 0) mbar_arrive(eL + 8 * (v0 / OP));
            if (v0 + OP < 8) FETCH(v0 + OP);
            if (v0 == 0) TS(8);
        }
        TS(9);
    }
}

typedef CUresult (*EncodeFn)(CUtensorMap*, CUtensorMapDataType, cuuint32_t, void*, const cuuint64_t*, const cuuint64_t*,
                             const cuuint32_t*, const cuuint32_t*, CUtensorMapInterleave, CUtensorMapSwizzle,
                             CUtensorMapL2promotion, CUtensorMapFloatOOBfill);

void make_map(EncodeFn fn, CUtensorMap* tm, const void* p, uint64_t rows, uint64_t cols, uint32_t box_rows,
              CUtensorMapL2promotion promo = CU_TENSOR_MAP_L2_PROMOTION_L2_128B) {
    cuuint64_t dims[2] = {cols, rows};
    cuuint64_t strides[1] = {cols * 2};
    cuuint32_t box[2] = {64, box_rows};
    cuuint32_t es[2] = {1, 1};
    fn(tm, CU_TENSOR_MAP_DATA_TYPE_BFLOAT16, 2, const_cast<void*>(p), dims, strides, box, es, CU_TENSOR_MAP_INTERLEAVE_NONE,
       CU_TENSOR_MAP_SWIZZLE_128B, promo, CU_TENSOR_MAP_FLOAT_OOB_FILL_NONE);
}

}

extern "C" void kernel_launch(void* const* d_in, const int* in_sizes, int n_in, void* d_out, int out_size) {
    (void)in_sizes; (void)n_in; (void)out_size;
    static EncodeFn fn = nullptr;
    if (!fn) {
        void* p = nullptr;
        cudaDriverEntryPointQueryResult q;
        cudaGetDriverEntryPoint("cuTensorMapEncodeTiled", &p, cudaEnableDefault, &q);
        fn = (EncodeFn)p;
        cudaFuncSetAttribute(fnet_fused_kernel, cudaFuncAttributeMaxDynamicSharedMemorySize, SMEM_BYTES);
    }
    CUtensorMap tx, tdre, tdim, tcre, tcim, tout;
    make_map(fn, &tx, d_in[0], S_, D_, 128, PRX);
    make_map(fn, &tcre, d_in[1], S_, S_, 128, PRC);
    make_map(fn, &tcim, d_in[2], S_, S_, 128, PRC);
    make_map(fn, &tdre, d_in[3], D_, D_, 128, PRD);
    make_map(fn, &tdim, d_in[4], D_, D_, 128, PRD);
    make_map(fn, &tout, d_out, S_, D_, 16 * OP);
    Params P;
    P.x = (const __nv_bfloat16*)d_in[0];
    P.dre = (const __nv_bfloat16*)d_in[3];
    P.dim = (const __nv_bfloat16*)d_in[4];
    P.wr = (const __nv_bfloat16*)d_in[6];
    P.wg = (const __nv_bfloat16*)d_in[7];
    P.wu = (const __nv_bfloat16*)d_in[8];
    P.wd = (const __nv_bfloat16*)d_in[9];
    P.zero = 0;
    fnet_fused_kernel<<<NCTA, NTHREADS, SMEM_BYTES, cudaStreamPerThread>>>(tx, tdre, tdim, tcre, tcim, tout, P);
}
```

```cpp
#include <cuda_runtime.h>
#include <cuda_bf16.h>
#include <cuda.h>
#include <stdint.h>

#define LDEL 0
#define LGAP 0
#define XS 0x5432
#define GSL 200
#define YNS 0u
#define YLD 1
#define PDEL 2500
#define PGAP 600
#define PK 4
#define ASYM 1
#define RF 1
#define EF2 16
#define NLATE 1
#define XE 2
#define W0 12
#define PFX 1
#define PFJ 0
#define MAPD 1
#define ORD 1
#define SDOM 0
#define PRE2 1
#define KQ 5
#define OP 2
#define XJ0 20
#define EGAP1 0
#define EGAP2 0
#define ESTAG 0
#define QJ 12
#define GOJ 2
#define TANH 1
#define SYNCS 0x80ull
#define SYNCD 2
#define SYNCCAP 4000u
#define SYNCMIN 24u
#define SYNCLAG 820u
#define QUIET 1
#define PRX CU_TENSOR_MAP_L2_PROMOTION_L2_128B
#define PRD CU_TENSOR_MAP_L2_PROMOTION_L2_128B
#define PRC CU_TENSOR_MAP_L2_PROMOTION_L2_128B
#define SLEEP_NS 200
#define PROD_REGS 32
#define CONS_REGS 184

namespace {

constexpr int S_ = 2048, D_ = 1024, F_ = 3584;
constexpr int NCTA = 128;
constexpr int XJ = XJ0;
constexpr uint32_t SLOT = 16384;
constexpr uint32_t OFF_L = 0;
constexpr uint32_t OFF_S = 8 * SLOT;
constexpr uint32_t OFF_RS = OFF_S + SLOT;
constexpr uint32_t OFF_BAR = 14 * SLOT;
constexpr uint32_t OFF_SEL = OFF_BAR + 360;
constexpr uint32_t OFF_RSTD = OFF_BAR + 384;
constexpr uint32_t OFF_MEAN = OFF_RSTD + 1024;
constexpr uint32_t OFF_XB = OFF_MEAN + 512;
constexpr uint32_t OFF_H = OFF_XB + 1024;
constexpr uint32_t SMEM_BYTES = OFF_H + 128;
constexpr uint32_t OFF_TS = OFF_XB + 512;
constexpr uint32_t SB0 = 1024;
constexpr int NTHREADS = 512;
static_assert(SMEM_BYTES <= 232448, "smem");

enum { B_FS = 0, B_ES = 6, B_FL = 12, B_EL = 20, B_SRD = 28, B_RECV = 30  , B_RDY = 34, B_STATS = 36, B_LST = 37, B_UPD = 38,
       B_QUIET = 39, B_GO = 40, B_PEER = 41, B_SEL = 42, B_H = 43, B_COUNT = 44 };
static_assert(B_COUNT * 8 <= 360, "barriers");

__device__ __align__(1024) uint8_t g_ab[16u * 32u * SLOT];
__device__ __align__(128) uint4 g_part[56 * (D_ / 4)];
__device__ __align__(128) uint4 g_stat[S_];
__device__ __align__(128) uint4 g_rs[D_];
__device__ __align__(128) unsigned long long g_key[NCTA];
__device__ __align__(128) unsigned long long g_flag[16 * 16];
__device__ __align__(128) unsigned long long g_sync[16 * 16];
__device__ __align__(128) unsigned g_epoch[NCTA];
#define PROF_T(i) do {} while (0)
#define TRACE(i) do {} while (0)
#define PROF_G(i) do {} while (0)
#define TS(i) do {} while (0)
#define FINISH(wg) bulk_wait_read<0>()

#define MARK(it, ph) do {} while (0)

__device__ __forceinline__ uint32_t smem_u32(const void* p) { return (uint32_t)__cvta_generic_to_shared(p); }
__device__ __forceinline__ void mbar_init(uint32_t bar, uint32_t cnt) {
    asm volatile("mbarrier.init.shared::cta.b64 [%0], %1;" ::"r"(bar), "r"(cnt) : "memory");
}
__device__ __forceinline__ bool mbar_try(uint32_t bar, uint32_t parity) {
    uint32_t ok;
    asm volatile("{\n.reg .pred p;\nmbarrier.try_wait.parity.shared::cta.b64 p, [%1], %2;\nselp.u32 %0, 1, 0, p;\n}"
                 : "=r"(ok) : "r"(bar), "r"(parity) : "memory");
    return ok;
}
__device__ __forceinline__ bool mbar_test(uint32_t bar, uint32_t parity) {
    uint32_t ok;
    asm volatile("{\n.reg .pred p;\nmbarrier.test_wait.parity.shared::cta.b64 p, [%1], %2;\nselp.u32 %0, 1, 0, p;\n}"
                 : "=r"(ok) : "r"(bar), "r"(parity) : "memory");
    return ok;
}
__device__ __forceinline__ bool mbar_try_cluster(uint32_t bar, uint32_t parity) {
    uint32_t ok;
    asm volatile("{\n.reg .pred p;\nmbarrier.try_wait.parity.acquire.cluster.shared::cta.b64 p, [%1], %2;\nselp.u32 %0, 1, 0, p;\n}"
                 : "=r"(ok) : "r"(bar), "r"(parity) : "memory");
    return ok;
}
constexpr int SPIN_LIMIT = 1 << 20;
__device__ __forceinline__ void mbar_wait(uint32_t bar, uint32_t parity) {
    if (mbar_try(bar, parity)) return;
    int n = 0;
    while (!mbar_try(bar, parity) && ++n < SPIN_LIMIT) {}
}
__device__ __forceinline__ void mbar_wait_cluster(uint32_t bar, uint32_t parity) {
    int n = 0;
    while (!mbar_try_cluster(bar, parity) && ++n < SPIN_LIMIT) {}
}
__device__ __forceinline__ void mbar_wait_sleep(uint32_t bar, uint32_t parity) {
    int n = 0;
    while (!mbar_try(bar, parity) && ++n < SPIN_LIMIT) __nanosleep(SLEEP_NS);
}
__device__ __forceinline__ void mbar_arrive(uint32_t bar) {
    asm volatile("mbarrier.arrive.shared::cta.b64 _, [%0];" ::"r"(bar) : "memory");
}
__device__ __forceinline__ void mbar_arrive_cluster(uint32_t cluster_bar) {
    asm volatile("mbarrier.arrive.shared::cluster.b64 _, [%0];" ::"r"(cluster_bar) : "memory");
}
__device__ __forceinline__ void mbar_expect_tx(uint32_t bar, uint32_t bytes) {
    asm volatile("mbarrier.arrive.expect_tx.shared::cta.b64 _, [%0], %1;" ::"r"(bar), "r"(bytes) : "memory");
}
__device__ __forceinline__ bool elect_one() {
    uint32_t p;
    asm volatile("{\n.reg .pred p;\nelect.sync _|p, 0xffffffff;\nselp.u32 %0, 1, 0, p;\n}" : "=r"(p));
    return p;
}
__device__ __forceinline__ uint32_t mapa(uint32_t addr, uint32_t rank) {
    uint32_t r;
    asm("mapa.shared::cluster.u32 %0, %1, %2;" : "=r"(r) : "r"(addr), "r"(rank));
    return r;
}
__device__ __forceinline__ uint32_t clock32() { uint32_t t; asm volatile("mov.u32 %0, %%clock;" : "=r"(t)); return t; }
__device__ __forceinline__ void sleep_until(uint32_t t) {
    int n = 0;
    while ((int)(clock32() - t) < 0 && ++n < SPIN_LIMIT) __nanosleep(20);
}
__device__ __forceinline__ void yield(float last, uint32_t zero) {
    if (YLD) asm volatile("nanosleep.u32 %0;" ::"r"((__float_as_uint(last) & zero) | YNS));
}
template <typename T> __device__ __forceinline__ T* at(T* p, uint32_t bytes) {
    asm("" : "+r"(bytes));
    return reinterpret_cast<T*>(reinterpret_cast<uintptr_t>(p) + bytes);
}
__device__ __forceinline__ void tma_2d(uint32_t dst, const CUtensorMap* tm, int c0, int c1, uint32_t bar) {
    asm volatile("cp.async.bulk.tensor.2d.shared::cluster.global.mbarrier::complete_tx::bytes [%0], [%1, {%3, %4}], [%2];"
                 ::"r"(dst), "l"(tm), "r"(bar), "r"(c0), "r"(c1) : "memory");
}
__device__ __forceinline__ void tma_2d_prefetch(const CUtensorMap* tm, int c0, int c1) {
    asm volatile("cp.async.bulk.prefetch.tensor.2d.L2.global [%0, {%1, %2}];" ::"l"(tm), "r"(c0), "r"(c1) : "memory");
}
__device__ __forceinline__ void tma_2d_store(const CUtensorMap* tm, int c0, int c1, uint32_t src) {
    asm volatile("cp.async.bulk.tensor.2d.global.shared::cta.bulk_group [%0, {%2, %3}], [%1];"
                 ::"l"(tm), "r"(src), "r"(c0), "r"(c1) : "memory");
}
__device__ __forceinline__ void bulk_g2s(uint32_t dst, const void* src, uint32_t bytes, uint32_t bar) {
    asm volatile("cp.async.bulk.shared::cluster.global.mbarrier::complete_tx::bytes [%0], [%1], %2, [%3];"
                 ::"r"(dst), "l"(src), "r"(bytes), "r"(bar) : "memory");
}
__device__ __forceinline__ void bulk_s2g(void* dst, uint32_t src, uint32_t bytes) {
    asm volatile("cp.async.bulk.global.shared::cta.bulk_group [%0], [%1], %2;" ::"l"(dst), "r"(src), "r"(bytes) : "memory");
}
__device__ __forceinline__ void st_async4(uint32_t dst, uint32_t a, uint32_t b, uint32_t c, uint32_t d, uint32_t bar) {
    asm volatile("st.async.weak.shared::cluster.mbarrier::complete_tx::bytes.v4.b32 [%0], {%1,%2,%3,%4}, [%5];"
                 ::"r"(dst), "r"(a), "r"(b), "r"(c), "r"(d), "r"(bar) : "memory");
}
__device__ __forceinline__ void bulk_commit() { asm volatile("cp.async.bulk.commit_group;" ::: "memory"); }
template <int N> __device__ __forceinline__ void bulk_wait_read() { asm volatile("cp.async.bulk.wait_group.read %0;" ::"n"(N) : "memory"); }
template <int N> __device__ __forceinline__ void bulk_wait() { asm volatile("cp.async.bulk.wait_group %0;" ::"n"(N) : "memory"); }
__device__ __forceinline__ void fence_async_smem() { asm volatile("fence.proxy.async.shared::cta;" ::: "memory"); }
__device__ __forceinline__ void fence_async_global() { asm volatile("fence.proxy.async.global;" ::: "memory"); }
__device__ __forceinline__ void prefetch_tmap(const CUtensorMap* tm) {
    asm volatile("prefetch.tensormap [%0];" ::"l"(tm) : "memory");
}
__device__ __forceinline__ unsigned long long ld_acquire64(const unsigned long long* p) {
    unsigned long long v; asm volatile("ld.acquire.gpu.global.u64 %0, [%1];" : "=l"(v) : "l"(p) : "memory"); return v;
}
__device__ __forceinline__ unsigned load_epoch(int b) {
    unsigned v; asm volatile("ld.global.u32 %0, [%1];" : "=r"(v) : "l"(at(g_epoch, b * 4)) : "memory"); return v + 1;
}
__device__ __forceinline__ unsigned ld_relaxed(const void* p) {
    unsigned v; asm volatile("ld.relaxed.gpu.global.u32 %0, [%1];" : "=r"(v) : "l"(p) : "memory"); return v;
}
__device__ __forceinline__ unsigned long long ld_relaxed64(const unsigned long long* p) {
    unsigned long long v; asm volatile("ld.relaxed.gpu.global.u64 %0, [%1];" : "=l"(v) : "l"(p) : "memory"); return v;
}
__device__ __forceinline__ void red_max64(unsigned long long* p, unsigned long long v) {
    asm volatile("red.relaxed.gpu.global.max.u64 [%0], %1;" ::"l"(p), "l"(v) : "memory");
}
__device__ __forceinline__ uint4 ld_relaxed128(const uint4* p) {
    uint4 v;
    asm volatile("{\n.reg .b128 t;\n.reg .b64 lo, hi;\nld.relaxed.gpu.global.b128 t, [%4];\nmov.b128 {lo, hi}, t;\n"
                 "mov.b64 {%0, %1}, lo;\nmov.b64 {%2, %3}, hi;\n}"
                 : "=r"(v.x), "=r"(v.y), "=r"(v.z), "=r"(v.w) : "l"(p) : "memory");
    return v;
}
__device__ __forceinline__ void st_relaxed128(uint4* p, const uint4& v) {
    asm volatile("{\n.reg .b128 t;\n.reg .b64 lo, hi;\nmov.b64 lo, {%1, %2};\nmov.b64 hi, {%3, %4};\nmov.b128 t, {lo, hi};\n"
                 "st.relaxed.gpu.global.b128 [%0], t;\n}"
                 ::"l"(p), "r"(v.x), "r"(v.y), "r"(v.z), "r"(v.w) : "memory");
}
__device__ __forceinline__ void st_relaxed64(unsigned long long* p, unsigned long long v) {
    asm volatile("st.relaxed.gpu.global.u64 [%0], %1;" ::"l"(p), "l"(v) : "memory");
}
__device__ __forceinline__ void st_release8(void* p, unsigned v) {
    asm volatile("st.release.gpu.global.u8 [%0], %1;" ::"l"(p), "r"(v) : "memory");
}
__device__ __forceinline__ uint64_t policy_evict_first() {
    uint64_t pol;
    asm("createpolicy.fractional.L2::evict_first.b64 %0, 1.0;" : "=l"(pol));
    return pol;
}
__device__ __forceinline__ uint4 ldg_stream(const void* p, uint64_t pol) {
    uint4 v;
    asm volatile("ld.global.nc.L1::no_allocate.L2::cache_hint.v4.u32 {%0,%1,%2,%3}, [%4], %5;"
                 : "=r"(v.x), "=r"(v.y), "=r"(v.z), "=r"(v.w) : "l"(p), "l"(pol));
    return v;
}
template <int ID, int N> __device__ __forceinline__ void named_arrive() { asm volatile("bar.arrive %0, %1;" ::"n"(ID), "n"(N) : "memory"); }
template <int ID, int N> __device__ __forceinline__ void named_bar() { asm volatile("bar.sync %0, %1;" ::"n"(ID), "n"(N) : "memory"); }

__device__ __forceinline__ float bf_lo(uint32_t u) { return __uint_as_float(u << 16); }
__device__ __forceinline__ float bf_hi(uint32_t u) { return __uint_as_float(u & 0xffff0000u); }
__device__ __forceinline__ uint32_t pack_bf(float lo, float hi) {
    uint32_t r; asm("cvt.rn.bf16x2.f32 %0, %1, %2;" : "=r"(r) : "f"(hi), "f"(lo)); return r;
}
__device__ __forceinline__ float rbf(float v) { return __uint_as_float(pack_bf(0.f, v)); }
__device__ __forceinline__ float sqrt_f(float v) { float r; asm("sqrt.approx.f32 %0, %1;" : "=f"(r) : "f"(v)); return r; }
__device__ __forceinline__ float rcp_f(float v) { float r; asm("rcp.approx.f32 %0, %1;" : "=f"(r) : "f"(v)); return r; }
__device__ __forceinline__ float silu_f(float z) { return __fdividef(z, 1.0f + __expf(-z)); }
__device__ __forceinline__ uint32_t bsub2(uint32_t a, uint32_t b) {
    uint32_t r; asm("sub.rn.bf16x2 %0, %1, %2;" : "=r"(r) : "r"(a), "r"(b)); return r;
}
__device__ __forceinline__ uint32_t bfma2(uint32_t a, uint32_t b, uint32_t c) {
    uint32_t r; asm("fma.rn.bf16x2 %0, %1, %2, %3;" : "=r"(r) : "r"(a), "r"(b), "r"(c)); return r;
}
__device__ __forceinline__ uint32_t norm2(uint32_t xv, float m, float rinv) {
    uint32_t t = pack_bf(bf_lo(xv) - m, bf_hi(xv) - m);
    return pack_bf(bf_lo(t) * rinv, bf_hi(t) * rinv);
}
__device__ __forceinline__ float gate1(float z) {
    if (TANH) {
        float t;
        const float h = 0.5f * z;
        asm("tanh.approx.f32 %0, %1;" : "=f"(t) : "f"(h));
        return fmaf(h, t, h);
    }
    float e, r;
    asm("ex2.approx.ftz.f32 %0, %1;" : "=f"(e) : "f"(z * -1.4426950408889634f));
    asm("rcp.approx.ftz.f32 %0, %1;" : "=f"(r) : "f"(1.0f + e));
    return z * r;
}
__device__ __forceinline__ uint32_t gate2(uint32_t xv, uint32_t mean2, float r0, float r1) {
    const uint32_t t = bsub2(xv, mean2);
    return pack_bf(gate1(bf_lo(t) * r0), gate1(bf_hi(t) * r1));
}
__device__ __forceinline__ uint32_t silu2(uint32_t z) { return pack_bf(silu_f(bf_lo(z)), silu_f(bf_hi(z))); }

__device__ __forceinline__ void stmatrix4(uint32_t addr, uint32_t r0, uint32_t r1, uint32_t r2, uint32_t r3) {
    asm volatile("stmatrix.sync.aligned.m8n8.x4.shared.b16 [%0], {%1,%2,%3,%4};"
                 ::"r"(addr), "r"(r0), "r"(r1), "r"(r2), "r"(r3));
}
__device__ __forceinline__ void stmatrix4t(uint32_t addr, uint32_t r0, uint32_t r1, uint32_t r2, uint32_t r3) {
    asm volatile("stmatrix.sync.aligned.m8n8.x4.trans.shared.b16 [%0], {%1,%2,%3,%4};"
                 ::"r"(addr), "r"(r0), "r"(r1), "r"(r2), "r"(r3));
}
__device__ __forceinline__ void ldmatrix4t(uint32_t addr, uint32_t& r0, uint32_t& r1, uint32_t& r2, uint32_t& r3) {
    asm volatile("ldmatrix.sync.aligned.m8n8.x4.trans.shared.b16 {%0,%1,%2,%3}, [%4];"
                 : "=r"(r0), "=r"(r1), "=r"(r2), "=r"(r3) : "r"(addr));
}

__device__ __forceinline__ void wg_fence() { asm volatile("wgmma.fence.sync.aligned;" ::: "memory"); }
__device__ __forceinline__ void wg_commit() { asm volatile("wgmma.commit_group.sync.aligned;" ::: "memory"); }
template <int N> __device__ __forceinline__ void wg_wait() { asm volatile("wgmma.wait_group.sync.aligned %0;" ::"n"(N) : "memory"); }

__host__ __device__ constexpr uint32_t desc_lo(uint32_t addr, uint32_t lbo) { return ((addr & 0x3FFFF) >> 4) | ((lbo >> 4) << 16); }
#define DESC_HI "0x40000040"

#define R8(a, o) "+f"(a[(o) + 0]), "+f"(a[(o) + 1]), "+f"(a[(o) + 2]), "+f"(a[(o) + 3]), \
                 "+f"(a[(o) + 4]), "+f"(a[(o) + 5]), "+f"(a[(o) + 6]), "+f"(a[(o) + 7])
#define R64(a, o) R8(a, (o) + 0), R8(a, (o) + 8), R8(a, (o) + 16), R8(a, (o) + 24), \
                  R8(a, (o) + 32), R8(a, (o) + 40), R8(a, (o) + 48), R8(a, (o) + 56)

template <int O, int TA>
__device__ __forceinline__ void wgmma128(float (&a)[128], uint32_t da, uint32_t db, int scale_d) {
    asm volatile(
        "{\n.reg .pred p;\n.reg .b64 da, db;\nsetp.ne.b32 p, %66, 0;\n"
        "mov.b64 da, {%64, " DESC_HI "};\nmov.b64 db, {%65, " DESC_HI "};\n"
        "wgmma.mma_async.sync.aligned.m64n128k16.f32.bf16.bf16 "
        "{%0,%1,%2,%3,%4,%5,%6,%7,%8,%9,%10,%11,%12,%13,%14,%15,"
        "%16,%17,%18,%19,%20,%21,%22,%23,%24,%25,%26,%27,%28,%29,%30,%31,"
        "%32,%33,%34,%35,%36,%37,%38,%39,%40,%41,%42,%43,%44,%45,%46,%47,"
        "%48,%49,%50,%51,%52,%53,%54,%55,%56,%57,%58,%59,%60,%61,%62,%63},"
        "da, db, p, 1, 1, %67, 0;\n}"
        : R64(a, O)
        : "r"(da), "r"(db), "r"(scale_d), "n"(TA));
}
template <int O>
__device__ __forceinline__ void wgmma128_rs(float (&a)[128], const uint32_t* f, uint32_t db) {
    asm volatile(
        "{\n.reg .b64 db;\nmov.b64 db, {%68, 8};\n"
        "wgmma.mma_async.sync.aligned.m64n128k16.f32.bf16.bf16 "
        "{%0,%1,%2,%3,%4,%5,%6,%7,%8,%9,%10,%11,%12,%13,%14,%15,"
        "%16,%17,%18,%19,%20,%21,%22,%23,%24,%25,%26,%27,%28,%29,%30,%31,"
        "%32,%33,%34,%35,%36,%37,%38,%39,%40,%41,%42,%43,%44,%45,%46,%47,"
        "%48,%49,%50,%51,%52,%53,%54,%55,%56,%57,%58,%59,%60,%61,%62,%63},"
        "{%64, %65, %66, %67}, db, 1, 1, 1, 0;\n}"
        : R64(a, O)
        : "r"(f[0]), "r"(f[1]), "r"(f[2]), "r"(f[3]), "r"(db));
}
template <int O>
__device__ __forceinline__ void fence_regs64(float (&a)[128]) {
    asm volatile("" : R64(a, O)::"memory");
}

struct Params {
    const __nv_bfloat16* x;
    const __nv_bfloat16* dre;
    const __nv_bfloat16* dim;
    const __nv_bfloat16* wr;
    const __nv_bfloat16* wg;
    const __nv_bfloat16* wu;
    const __nv_bfloat16* wd;
    uint32_t zero;
#define AB g_ab
};

__device__ __forceinline__ float warp_sum(float v) {
#pragma unroll
    for (int o = 16; o; o >>= 1) v += __shfl_xor_sync(0xffffffffu, v, o);
    return v;
}
__device__ __forceinline__ void fma8(float* acc, const uint4& w, float s) {
    acc[0] += s * bf_lo(w.x); acc[1] += s * bf_hi(w.x); acc[2] += s * bf_lo(w.y); acc[3] += s * bf_hi(w.y);
    acc[4] += s * bf_lo(w.z); acc[5] += s * bf_hi(w.z); acc[6] += s * bf_lo(w.w); acc[7] += s * bf_hi(w.w);
}
__device__ __forceinline__ int POS(int t) { return (t & ~15) | ((t & 6) << 1) | ((t & 8) >> 2) | (t & 1); }
__host__ __device__ constexpr int PSLOT(int j) { return j < 4 ? j : (j & 1) + ((j & 2) ? 0 : 4); }
__host__ __device__ constexpr int PPAR(int j) { return j < 4 ? 0 : ((j >> 2) ^ (j >> 1) ^ 1) & 1; }
__host__ __device__ constexpr int DSLOT(int it) { return (it & 3) + 2; }
__device__ __forceinline__ int SREC(int t) { return (t & ~15) | ((t & 3) << 2) | ((t >> 2) & 3); }
__device__ __forceinline__ int KO(int cl) { return ((cl & 1) << 1) | (cl >> 1); }

__device__ __forceinline__ unsigned long long* sync_words() {
    uint32_t t;
    asm volatile("mov.u32 %0, %%smid;" : "=r"(t));
    t >>= 1;
    const uint32_t u = t - 32;
    return at(g_sync, (t < 32 ? t & 7 : t < 60 ? (SDOM ? 1 : 8) + u - 7 * ((u * 37) >> 8) : 15) * 128);
}

__global__ void __cluster_dims__(2, 1, 1) __launch_bounds__(NTHREADS, 1)
fnet_fused_kernel(const __grid_constant__ CUtensorMap tm_x, const __grid_constant__ CUtensorMap tm_dre,
                  const __grid_constant__ CUtensorMap tm_dim, const __grid_constant__ CUtensorMap tm_cre,
                  const __grid_constant__ CUtensorMap tm_cim, const __grid_constant__ CUtensorMap tm_out,
                  const Params P) {
    extern __shared__ __align__(1024) uint8_t smem[];
    const unsigned long long tstart = clock64();
    const uint32_t sb = smem_u32(smem);
    const int tid = threadIdx.x, lane = tid & 31;
    const int warp = __shfl_sync(0xffffffffu, tid >> 5, 0);
    const int pr = blockIdx.x >> 1, p7 = ((pr - 36) * 37) >> 8;
    const int c = blockIdx.x & 1;
    const int gi = pr < 4 ? 7 : pr < 36 ? 2 * ((pr - 4) & 7) + (((pr - 4) >> 2) & 1) : 2 * (pr - 36 - 7 * p7) + 1 + (pr - 36 - 7 * p7 > 2);
    const int g = gi & 7;
    const int r = (gi >> 3) * 4 + (pr < 4 ? pr : pr < 36 ? (pr - 4) >> 3 : p7);
#define BLK(n) (ORD ? (n) - ((n) <= g) : (g + (n)) & 7)
    const int grp = 2 * r + c;
    const int b = g * 16 + grp;
    const uint32_t bar0 = sb + OFF_BAR;
    const uint32_t zero = P.zero;
#define BAR(i) (bar0 + 8u * (i))
#define XBAR(i) (sb + OFF_XB + 64 + 8u * (i))
#define CLUSTER_ARRIVE() asm volatile("barrier.cluster.arrive.relaxed.aligned;" ::: "memory")
#define CLUSTER_WAIT() asm volatile("barrier.cluster.wait.aligned;" ::: "memory")
    if ((sb & 0xffffffu) != SB0) return;

#define LOAD0(it) do { \
            mbar_expect_tx(BAR(B_FS + DSLOT(it)), SLOT); tma_2d(sb + OFF_S + DSLOT(it) * SLOT, tmD, (it) * 64, r * 128, BAR(B_FS + DSLOT(it))); \
            mbar_expect_tx(BAR(B_FL + (it)), SLOT); tma_2d(sb + OFF_L + (it) * SLOT, &tm_x, (it) * 64, g * 256, BAR(B_FL + (it))); \
            mbar_expect_tx(BAR(B_FL + 4 + (it)), SLOT); tma_2d(sb + OFF_L + (4 + (it)) * SLOT, &tm_x, (it) * 64, g * 256 + 128, BAR(B_FL + 4 + (it))); \
        } while (0)
    if (warp == W0) {
        if (elect_one()) {
            const CUtensorMap* tmD = c ? &tm_dim : &tm_dre;
            if (PFX & 2) prefetch_tmap(tmD);
            if (PFX & 1) prefetch_tmap(&tm_x);
            mbar_init(BAR(B_FS + 2), 1); mbar_init(BAR(B_FL), 1); mbar_init(BAR(B_FL + 4), 1);
            asm volatile("fence.mbarrier_init.release.cluster;" ::: "memory");
            LOAD0(0);
        }
        __syncwarp();
    }
    if (warp == 12) {
        if (elect_one()) {
#pragma unroll
            for (int i = 0; i < B_COUNT; i++)
                if (i != B_FS + 2 && i != B_FL && i != B_FL + 4)
                    mbar_init(BAR(i), (i >= B_ES && i < B_FL) || i == B_GO ? 2 : i == B_STATS || i == B_LST ? 4 : 1);
#pragma unroll
            for (int i = 0; i < 12; i++) mbar_init(XBAR(i), 1);
#pragma unroll
            for (int i = 0; i < 4; i++) mbar_expect_tx(BAR(B_RECV + i), SLOT / 2);
            mbar_expect_tx(BAR(B_PEER), 1024); mbar_expect_tx(BAR(B_H), 128);
            *reinterpret_cast<volatile uint32_t*>(smem + OFF_SEL + 8) = 0;
            asm volatile("fence.mbarrier_init.release.cluster;" ::: "memory");
            fence_async_smem();
        }
        __syncwarp();
    }
    CLUSTER_ARRIVE();

    if (warp >= 12) {
        asm volatile("setmaxnreg.dec.sync.aligned.u32 %0;" ::"n"(PROD_REGS));
        CLUSTER_WAIT();
        if (warp == 12) {
            if (elect_one()) {
                const CUtensorMap* tmD = c ? &tm_dim : &tm_dre;
#define XROWS(k) do { mbar_expect_tx(XBAR(k), 8192); bulk_g2s(sb + OFF_S + (k) * 8192, at(P.x, (b * 16 + (k) * 4) * D_ * 2), 8192, XBAR(k)); } while (0)
                int k = 0;
#pragma unroll 1
                for (int it = 1; it < 16; it++) {
                    if (it < 4) { if (LDEL) sleep_until((uint32_t)tstart + LDEL + (it - 1) * LGAP); LOAD0(it); }
                    else {
                        const int s = DSLOT(it);
                        mbar_wait(BAR(B_ES + s), ((it >> 2) & 1) ^ 1);
                        TRACE(it);
                        mbar_expect_tx(BAR(B_FS + s), SLOT);
                        tma_2d(sb + OFF_S + s * SLOT, tmD, it * 64, r * 128, BAR(B_FS + s));
                    }
                    while (((XS >> (4 * k)) & 15) == it) { XROWS(k); k++; }
                }
                const unsigned ep = load_epoch(b), e8 = ep & 0xffu;
                const uint8_t* abg = at(AB, grp * 32 * SLOT);
                const unsigned long long* fl = at(g_flag, grp * 128);
                unsigned long long rdy = ld_acquire64(fl);
                mbar_wait(BAR(B_SRD), 0);
                st_release8(at(g_flag, grp * 128 + g), e8);
                PROF_T(7);
                int j = 4;
#pragma unroll 1
                for (int cl = 0; cl < 4; cl++) {
                    if (cl) rdy = ld_acquire64(fl + cl);
                    fence_async_global();
#pragma unroll 1
                    for (int n = 1; n < 8; n++, j++) {
                        const int q = BLK(n), s = (j & 1) + ((j & 2) ? 0 : 4);
                        mbar_wait(BAR(B_ES + s), ((j >> 2) ^ (j >> 1)) & 1);
                        if (j == 7) mbar_wait(BAR(B_SRD + 1), 0);
                        if (((unsigned)(rdy >> (8 * q)) & 0xffu) != e8) {
                            int m = 0;
                            do { rdy = ld_acquire64(fl + cl); } while (((unsigned)(rdy >> (8 * q)) & 0xffu) != e8 && ++m < SPIN_LIMIT);
                            fence_async_global();
                        }
                        TRACE(16 + j);
                        mbar_expect_tx(BAR(B_FS + s), SLOT);
                        bulk_g2s(sb + OFF_S + s * SLOT, at(abg, (4 * q + KO(cl)) * SLOT), SLOT, BAR(B_FS + s));
                    }
                }
                *at(g_epoch, b * 4) = ep;
            }
        } else if (warp < 15) {
            if (elect_one()) {
                const int w = warp - 13, row0 = g * 256 + w * 128;
                const CUtensorMap* tmC = c ? &tm_cim : &tm_cre;
                const uint32_t fb = BAR(B_FL + 4 * w), eb = BAR(B_EL + 4 * w), dst = sb + OFF_L + w * 4 * SLOT;
                prefetch_tmap(w ? &tm_out : tmC);
                unsigned long long* sy = sync_words();
#define ADOPT(ph, lag) do { const unsigned long long v = ld_relaxed64(sy++); \
                    if (v - (ph) - SYNCMIN < SYNCCAP) *reinterpret_cast<volatile uint32_t*>(smem + OFF_SEL + 8) = (uint32_t)v - (lag); } while (0)
                [[maybe_unused]] unsigned long long mk = 0;
                int n = 0, cl = 0;
#pragma unroll 1
                for (int it = 4; it < 48; it++) {
                    const int s = it & 3;
                    mbar_wait(eb + 8 * s, ((it >> 2) & 1) ^ 1);
                    const unsigned long long ph = clock64() - 1024u * (it - 4);
                    TRACE(64 + w * 64 + it - 4);
                    MARK(it, ph);
                    mbar_expect_tx(fb + 8 * s, SLOT);
                    tma_2d(dst + s * SLOT, it < 16 ? &tm_x : tmC, (it < 16 ? it : 4 * (n ? BLK(n) : g) + KO(cl)) * 64, row0, fb + 8 * s);
                    if (it == PFJ) tma_2d_prefetch(tmC, (4 * g + (r & 3)) * 64, row0);
                    if (it >= 16) {
                        if (it == 19) { n = 1; cl = 0; } else if (it < 19) cl++; else if (++n == 8) { n = 1; cl++; }
                    }
                    if (w == 0) {
                        if (((SYNCS << 4) >> it) & 1) red_max64(sy, ph);
                        if (((SYNCS << (4 + SYNCD)) >> it) & 1) ADOPT(ph, SYNCLAG);
                    }
                }
                {
#pragma unroll 1
                    for (int h = 0; h < 8 / OP; h++) {
                        mbar_wait(eb + 8 * h, 1);
                        fence_async_smem();
                        tma_2d_store(&tm_out, grp * 64, row0 + h * OP * 16, sb + OFF_S + (2 + w) * SLOT + h * OP * 2048);
                        bulk_commit();
                    }
                    FINISH(w);
                }
            }
        } else {
            const unsigned ep = load_epoch(b);
            uint4 f[4];
#define GATHER(ptr, cnt, valid) do { int n = 0; bool ok; do { ok = true; \
                _Pragma("unroll") for (int i = 0; i < (cnt); i++) { f[i] = ld_relaxed128((ptr) + i * 32); ok = ok && (valid); } \
                if (__all_sync(0xffffffffu, ok)) break; \
                __nanosleep(GSL); \
            } while (++n < SPIN_LIMIT); } while (0)
            {
                sleep_until((uint32_t)tstart + 6000);
                const uint4* keys = at(reinterpret_cast<const uint4*>(g_key), lane * 16);
                bool mine = false;
                int n = 0;
                do {
                    f[0] = ld_relaxed128(keys); f[1] = ld_relaxed128(keys + 32);
                    if (__all_sync(0xffffffffu, f[0].y == ep && f[0].w == ep && f[1].y == ep && f[1].w == ep)) break;
                    if (!mine) {
                        mbar_wait(BAR(B_LST), 0);
                        const uint4 k = *reinterpret_cast<const uint4*>(smem + OFF_XB);
                        if (lane == 0) st_relaxed64(at(g_key, b * 8), ((unsigned long long)ep << 32) | max(max(k.x, k.y), max(k.z, k.w)));
                        mine = true;
                    }
                    __nanosleep(GSL);
                } while (++n < SPIN_LIMIT);
                const unsigned key = __reduce_max_sync(0xffffffffu, max(max(f[0].x, f[0].z), max(f[1].x, f[1].z)));
                if (lane == 0) { *reinterpret_cast<unsigned*>(smem + OFF_SEL) = key; mbar_arrive(BAR(B_SEL)); PROF_T(8); }
            }
            if (elect_one()) {
#pragma unroll 1
                for (int cl = 0; cl < 4; cl++) {
                    uint8_t* dst = at(AB, (grp * 32 + 4 * g + KO(cl)) * SLOT);
                    const uint32_t src = sb + OFF_S + cl * SLOT, chunk = cl ? 4096 : SLOT;
                    mbar_wait(BAR(B_FS + cl), 0);
                    if (RF) fence_async_smem();
                    if (cl == 0) PROF_T(3);
                    uint32_t t0 = clock32() + (cl == 1 ? PDEL : 0);
#pragma unroll 1
                    for (uint32_t o = 0; o < SLOT; o += chunk) {
                        sleep_until(t0);
                        bulk_s2g(dst + o, src + o, chunk);
                        bulk_commit();
                        t0 += PGAP;
                    }
                    bulk_wait<0>();
                    TRACE(252 + cl);
                    if (cl < 2) mbar_arrive(BAR(B_SRD + cl));
                    else {
                        mbar_wait(BAR(B_ES + cl), 0);
                        mbar_expect_tx(BAR(B_FS + cl), SLOT);
                        tma_2d(src, &tm_x, grp * 64, g * 256 + (cl - 2) * 128, BAR(B_FS + cl));
                    }
                    if (cl) st_release8(at(g_flag, grp * 128 + cl * 8 + g), ep & 0xffu);
                    if (cl == 1) PROF_T(5);
                    if (cl == 3) PROF_T(4);
                }
            }
        }
    } else if (warp >= 8) {
        asm volatile("setmaxnreg.dec.sync.aligned.u32 %0;" ::"n"(512 - PROD_REGS - 2 * CONS_REGS));
        const int aw = warp - 8, mt = tid - 256;
        unsigned ep;
        {
            const uint8_t* rp = smem + OFF_S + aw * 2048 + lane * 16;
            const __nv_bfloat16* dp = at(c ? P.dim : P.dre, (r * 128 + g * 16 + aw * 4) * D_ * 2);
            float wf[32], sw = 0.f;
#pragma unroll
            for (int i = 0; i < 4; i++) {
                const uint4 w = __ldg(reinterpret_cast<const uint4*>(at(P.wr, lane * 16) + i * 256));
                const uint32_t wv[4] = {w.x, w.y, w.z, w.w};
#pragma unroll
                for (int e = 0; e < 4; e++) { wf[8 * i + 2 * e] = bf_lo(wv[e]); wf[8 * i + 2 * e + 1] = bf_hi(wv[e]); sw = (sw + bf_lo(wv[e])) + bf_hi(wv[e]); }
            }
            ep = load_epoch(b);
            sw = warp_sum(sw);
            CLUSTER_WAIT();
            float x0[4] = {}, s1[4] = {}, s2[4] = {}, sx[4] = {}, sd[4] = {};
#define PUSH(a, v) do { a[0] = a[1]; a[1] = a[2]; a[2] = a[3]; a[3] = v; } while (0)
#pragma unroll 1
            for (int k = 0; k < 4; k++) {
                mbar_wait(XBAR(k), 0);
                uint4 v[4];
#pragma unroll
                for (int i = 0; i < 4; i++) v[i] = *reinterpret_cast<const uint4*>(rp + k * 8192 + i * 512);
                uint32_t sh = v[0].x << 16;
                float a1s = 0.f, a2s = 0.f, axs = 0.f;
#pragma unroll
                for (int i = 0; i < 4; i++) {
                    sh = __shfl_sync(0xffffffffu, sh | (__float_as_uint(axs) & zero), 0);
                    const uint32_t xv[4] = {v[i].x, v[i].y, v[i].z, v[i].w};
#pragma unroll
                    for (int e = 0; e < 4; e++) {
                        const float a0 = bf_lo(xv[e]) - __uint_as_float(sh), a1 = bf_hi(xv[e]) - __uint_as_float(sh);
                        a1s += a0 + a1;
                        a2s = fmaf(a0, a0, fmaf(a1, a1, a2s));
                        axs = fmaf(a0, wf[8 * i + 2 * e], fmaf(a1, wf[8 * i + 2 * e + 1], axs));
                    }
                }
                PUSH(x0, __uint_as_float(sh)); PUSH(s1, a1s); PUSH(s2, a2s); PUSH(sx, axs);
                fence_async_smem();
                __syncwarp();
                if (elect_one()) {
                    const uint32_t db = XBAR(k == 3 ? 8 + aw : 4 + aw);
                    if (k == 0 || k == 3) mbar_expect_tx(db, k ? 2048 : 6144);
                    bulk_g2s(sb + OFF_S + k * 8192 + aw * 2048, dp + k * D_, 2048, db);
                }
            }
#define FOLD4(a) do { const bool u16 = lane & 16, u8 = lane & 8; \
                float p0 = (u16 ? a[2] : a[0]) + __shfl_xor_sync(0xffffffffu, u16 ? a[0] : a[2], 16); \
                float p1 = (u16 ? a[3] : a[1]) + __shfl_xor_sync(0xffffffffu, u16 ? a[1] : a[3], 16); \
                a[0] = (u8 ? p1 : p0) + __shfl_xor_sync(0xffffffffu, u8 ? p0 : p1, 8); \
                _Pragma("unroll") for (int o = 4; o; o >>= 1) a[0] += __shfl_xor_sync(0xffffffffu, a[0], o); } while (0)
#pragma unroll 1
            for (int k = 0; k < 4; k++) {
                mbar_wait(XBAR(k == 3 ? 8 + aw : 4 + aw), 0);
                float run = 0.f;
#pragma unroll
                for (int i = 0; i < 4; i++) {
                    const uint4 v = *reinterpret_cast<const uint4*>(rp + k * 8192 + i * 512);
                    const uint32_t dv[4] = {v.x, v.y, v.z, v.w};
#pragma unroll
                    for (int e = 0; e < 4; e++) run += bf_lo(dv[e]) + bf_hi(dv[e]);
                }
                PUSH(sd, run);
            }
            FOLD4(sd); FOLD4(s1); FOLD4(s2); FOLD4(sx);
            const float nb = __shfl_down_sync(0xffffffffu, sd[0], 8);
            if ((lane & 15) == 0)
                st_relaxed128(at(g_rs, (grp * 64 + g * 8 + aw * 2 + (lane >> 4)) * 16), make_uint4(__float_as_uint(sd[0]), ep, __float_as_uint(nb), ep));
            if (mt == 0) PROF_T(6);
            const int rr = lane >> 3;
            const float c0 = rr == 0 ? x0[0] : rr == 1 ? x0[1] : rr == 2 ? x0[2] : x0[3];
            const float dm = s1[0] * (1.0f / D_);
            const float mb = rbf(c0 + dm);
            const float rinv = rcp_f(rbf(sqrt_f(rbf(rbf(fmaxf(s2[0] * (1.0f / D_) - dm * dm, 0.f)) + 1e-5f))));
            if ((lane & 7) == 0) st_relaxed128(at(g_stat, (b * 16 + aw * 4 + rr) * 16), make_uint4(__float_as_uint(mb), __float_as_uint(rinv), ep, 0));
            unsigned u = __bfloat16_as_ushort(__float2bfloat16_rn((sx[0] + (c0 - mb) * sw) * rinv));
            u = (u & 0x8000u) ? (~u & 0xffffu) : (u | 0x8000u);
            u = (u << 16) | (0xffffu - (unsigned)(b * 16 + rr * 4 + aw));
            u = __reduce_max_sync(0xffffffffu, u);
            if (lane == 0) { *reinterpret_cast<unsigned*>(smem + OFF_XB + aw * 4) = u; mbar_arrive(BAR(B_LST)); }
            if (mt == 0) PROF_T(2);
            named_bar<4, 128>();
            if (mt < 12) asm volatile("mbarrier.inval.shared::cta.b64 [%0];" ::"r"(XBAR(mt)) : "memory");
            uint4 f[4];
            if (aw < 2) {
                const int t = SREC(aw * 128 + lane);
                GATHER(at(g_stat, (g * 256 + aw * 128 + lane) * 16), 4, f[i].z == ep);
#pragma unroll
                for (int i = 0; i < 4; i++) {
                    *reinterpret_cast<uint32_t*>(smem + OFF_RSTD + (POS(t) + i * 32) * 4) = f[i].y;
                    *reinterpret_cast<uint16_t*>(smem + OFF_MEAN + (POS(t) + i * 32) * 2) = (uint16_t)(f[i].x >> 16);
                }
            } else {
                const int e2 = (aw - 2) * 32 + lane;
                GATHER(at(g_rs, (grp * 64 + e2) * 16), 1, f[i].y == ep && f[i].w == ep);
#pragma unroll
                for (int i = 0; i < 2; i++) {
                    const float v = __uint_as_float(i ? f[0].z : f[0].x);
                    const float hi = rbf(v), mid = rbf(v - hi), lo = v - hi - mid;
                    *reinterpret_cast<uint4*>(smem + OFF_RS + (e2 * 2 + i) * 16) = make_uint4(pack_bf(hi, mid), pack_bf(lo, 0.f), 0, 0);
                }
            }
            fence_async_smem();
            __syncwarp();
            if (lane == 0) mbar_arrive(BAR(B_STATS));
            if (mt == 127) PROF_T(9);
        }
        const int pair = g * 7 + r;
        if (r < 7) {
            const uint64_t pol = policy_evict_first();
            const __nv_bfloat16* wp = at((aw & 1) ? P.wu : P.wg, ((c * 512 + (aw >> 1) * 256 + (lane >> 3) * 8) * F_ + pair * 64 + (lane & 7) * 8) * 2);
            uint4 b0[8], b1[8];
#define FILL(buf, str) do { _Pragma("unroll") for (int q = 0; q < 8; q++) buf[q] = ldg_stream(wp + q * (str), pol); } while (0)
            FILL(b0, F_);
            mbar_wait(BAR(B_SEL), 0);
            uint4 xn;
            {
                const int sel = 0xffff - (int)(*reinterpret_cast<volatile unsigned*>(smem + OFF_SEL) & 0xffffu);
                xn = __ldg(reinterpret_cast<const uint4*>(at(P.x, (sel * D_ + c * 512 + (aw >> 1) * 256 + (lane & 7) * 32 + (lane >> 3) * 8) * 2)));
                uint4 f[1];
                GATHER(at(g_stat, SREC(sel) * 16), 1, f[i].z == ep);
                if (PRE2) { wp += 32 * F_; FILL(b1, F_); wp -= 32 * F_; }
                if (NLATE && mbar_test(BAR(B_QUIET), 0)) mbar_wait_sleep(BAR(B_GO), 0);
                const float m = __uint_as_float(f[0].x), ri = __uint_as_float(f[0].y);
                xn = make_uint4(norm2(xn.x, m, ri), norm2(xn.y, m, ri), norm2(xn.z, m, ri), norm2(xn.w, m, ri));
            }
            float ag[8];
#pragma unroll
            for (int i = 0; i < 8; i++) ag[i] = 0.f;
            const uint32_t stag = (aw * 4 + (grp & 3)) * ESTAG;
            uint32_t te = clock32() + stag;
            bool paused = !QUIET;
#define ROUND(cur, nxt, rd) do { \
                if (!paused && mbar_test(BAR(B_QUIET), 0)) { mbar_wait_sleep(BAR(B_GO), 0); te = clock32() + stag; paused = true; } \
                sleep_until(te); \
                te = clock32() + (paused ? EGAP2 : EGAP1); \
                if (lane == 0) TRACE(192 + aw * 12 + (rd)); \
                if ((rd) == 7) wp = at(P.wd - 16 * D_, ((pair * 64 + (lane >> 4) * 8) * D_ + c * 512 + aw * 128 + (lane & 15) * 8) * 2); \
                wp = at(wp, ((rd) < 7 ? 64 * F_ : 32 * D_) + (cur[7].x & zero)); \
                if ((rd) < 7) { if ((rd) || !PRE2) FILL(nxt, F_); } else if ((rd) != 8 && (rd) < 11) FILL(nxt, D_); \
                _Pragma("unroll") for (int q = 0; q < 8; q += 2) { \
                    uint32_t xw = __shfl_sync(0xffffffffu, q == 0 ? xn.x : q == 2 ? xn.y : q == 4 ? xn.z : xn.w, (lane & 24) | ((rd) & 7)); \
                    fma8(ag, cur[q], bf_lo(xw)); \
                    if (YLD > 1) { yield(ag[7], zero); xw = __shfl_sync(0xffffffffu, xw, lane); } \
                    fma8(ag, cur[q + 1], bf_hi(xw)); \
                    if (q < 6) yield(ag[7], zero); \
                } } while (0)
#pragma unroll 1
            for (int rd = 0; rd < 12; rd += 2) {
                ROUND(b0, b1, rd);
                ROUND(b1, b0, rd + 1);
                if (rd == 6) { wp += 16 * D_; FILL(b1, D_); wp -= 16 * D_; }
                if (rd == 6 || rd == 10) {
#pragma unroll
                    for (int i = 0; i < 8; i++) ag[i] += __shfl_xor_sync(0xffffffffu, ag[i], 16);
                }
                if (rd == 6) {
#pragma unroll
                    for (int i = 0; i < 8; i++) ag[i] += __shfl_xor_sync(0xffffffffu, ag[i], 8);
                    if (lane < 8) {
                        const uint32_t dst = mapa(sb + OFF_XB + (c * 4 + aw) * 128 + (lane & 3) * 32, lane >> 2), pb = mapa(BAR(B_PEER), lane >> 2);
                        st_async4(dst, __float_as_uint(ag[0]), __float_as_uint(ag[1]), __float_as_uint(ag[2]), __float_as_uint(ag[3]), pb);
                        st_async4(dst + 16, __float_as_uint(ag[4]), __float_as_uint(ag[5]), __float_as_uint(ag[6]), __float_as_uint(ag[7]), pb);
                    }
                    if (aw == 3) {
                        mbar_wait_cluster(BAR(B_PEER), 0);
                        const float* ps = reinterpret_cast<const float*>(smem + OFF_XB) + lane;
                        const float go = (ps[0] + ps[64]) + (ps[128] + ps[192]), uo = (ps[32] + ps[96]) + (ps[160] + ps[224]);
                        const float h = rbf(silu_f(rbf(go))) * rbf(uo), ho = __shfl_xor_sync(0xffffffffu, h, 1);
                        asm volatile("st.async.weak.shared::cluster.mbarrier::complete_tx::bytes.b32 [%0], %1, [%2];"
                                     ::"r"(mapa(sb + OFF_H + c * 64 + (lane >> 1) * 4, lane & 1)), "r"((lane & 1) ? pack_bf(ho, h) : pack_bf(h, ho)),
                                       "r"(mapa(BAR(B_H), lane & 1)) : "memory");
                    }
                    mbar_wait_cluster(BAR(B_H), 0);
                    xn = *reinterpret_cast<const uint4*>(smem + OFF_H + (lane & 3) * 32 + (lane >> 4) * 16);
#pragma unroll
                    for (int i = 0; i < 8; i++) ag[i] = 0.f;
                    if (mt == 0) PROF_T(10);
                }
            }
            const int hi = lane >> 4;
            st_relaxed128(at(g_part, pair * 4096 + (c * 8 + aw * 2 + ((lane >> 3) & 1)) * 256 + hi * 128 + (lane & 7) * 16),
                          make_uint4((__float_as_uint(hi ? ag[4] : ag[0]) & ~15u) | (ep & 15u), __float_as_uint(hi ? ag[5] : ag[1]),
                                     __float_as_uint(hi ? ag[6] : ag[2]), __float_as_uint(hi ? ag[7] : ag[3])));
            if (mt == 0) PROF_T(11);
        } else {
            mbar_wait_sleep(BAR(B_SEL), 0);
        }
        const int sel = 0xffff - (int)(*reinterpret_cast<volatile unsigned*>(smem + OFF_SEL) & 0xffffu);
        if ((sel >> 8) == g) {
            const int col = (lane & 7) * 8 + ((lane >> 3) & 1) * 4;
            const uint2 xv = __ldg(reinterpret_cast<const uint2*>(at(P.x, (sel * D_ + grp * 64 + col) * 2)));
            uint4 f[1];
            GATHER(at(g_stat, SREC(sel) * 16), 1, f[i].z == ep);
            const uint4 rec = f[0];
            const uint4* src = at(g_part, (aw * 14 + (lane >> 4)) * 4096 + grp * 256 + (lane & 15) * 16);
            if (r == 7) {
                int n = 0;
                while (((ld_relaxed(src) ^ ep) & 15u) != 0 && ++n < SPIN_LIMIT) __nanosleep(500);
            }
            uint4 t[7];
            int n = 0;
            bool ok;
            do {
                ok = true;
#pragma unroll
                for (int u = 0; u < 7; u++) { t[u] = ld_relaxed128(src + u * 512); ok = ok && ((t[u].x ^ ep) & 15u) == 0; }
            } while (!__all_sync(0xffffffffu, ok) && ++n < SPIN_LIMIT);
            float4 a = make_float4(0.f, 0.f, 0.f, 0.f);
#pragma unroll
            for (int u = 0; u < 7; u++) {
                a.x += __uint_as_float(t[u].x & ~15u); a.y += __uint_as_float(t[u].y); a.z += __uint_as_float(t[u].z); a.w += __uint_as_float(t[u].w);
            }
            a.x += __shfl_xor_sync(0xffffffffu, a.x, 16); a.y += __shfl_xor_sync(0xffffffffu, a.y, 16);
            a.z += __shfl_xor_sync(0xffffffffu, a.z, 16); a.w += __shfl_xor_sync(0xffffffffu, a.w, 16);
            float4* park = reinterpret_cast<float4*>(smem + OFF_XB) + (lane & 15);
            if (lane < 16) park[aw * 16] = a;
            named_bar<4, 128>();
            if (aw == 0) {
                const float4 p1 = park[16], p2 = park[32], p3 = park[48];
                a.x = (a.x + p1.x) + (p2.x + p3.x); a.y = (a.y + p1.y) + (p2.y + p3.y);
                a.z = (a.z + p1.z) + (p2.z + p3.z); a.w = (a.w + p1.w) + (p2.w + p3.w);
                unsigned u = *reinterpret_cast<volatile unsigned*>(smem + OFF_SEL) >> 16;
                u = (u & 0x8000u) ? (u & 0x7fffu) : (~u & 0xffffu);
                const float sg = rbf(__fdividef(1.0f, 1.0f + __expf(-__uint_as_float(u << 16))));
                const float m = __uint_as_float(rec.x), ri = __uint_as_float(rec.y);
                const uint32_t n0 = norm2(xv.x, m, ri), n1 = norm2(xv.y, m, ri);
                uint2 o;
                o.x = silu2(pack_bf(bf_lo(n0) + rbf(rbf(a.x) * sg), bf_hi(n0) + rbf(rbf(a.y) * sg)));
                o.y = silu2(pack_bf(bf_lo(n1) + rbf(rbf(a.z) * sg), bf_hi(n1) + rbf(rbf(a.w) * sg)));
                if (lane < 16) *reinterpret_cast<uint2*>(smem + OFF_H + col * 2) = o;
                __syncwarp();
                if (lane == 0) { mbar_arrive(BAR(B_UPD)); PROF_T(12); }
            }
        }
    } else {
        asm volatile("setmaxnreg.inc.sync.aligned.u32 %0;" ::"n"(CONS_REGS));
        CLUSTER_WAIT();
        const int wg = warp >> 2, wq = warp & 3;
        const int wt = tid & 127;
        float acc[128];
        const uint32_t fL = BAR(B_FL + 4 * wg), eL = BAR(B_EL + 4 * wg);
        const uint32_t dL = desc_lo(SB0 + OFF_L, 16) + wg * 4096;
        constexpr uint32_t dS = desc_lo(SB0 + OFF_S, 16);
        constexpr uint32_t SL = SLOT >> 4;
#define RELEASE(ls, ss) do { if (wt == 0) { mbar_arrive(eL + 8u * (ls)); mbar_arrive(BAR(B_ES + (ss))); } } while (0)
#define WAIT_FULL(ls, lph, ss, sph) do { mbar_wait(BAR(B_FS + (ss)), sph); mbar_wait(fL + 8u * (ls), lph); } while (0)
#define TURN() do { if (wg) named_bar<6, 256>(); else named_bar<5, 256>(); } while (0)
#define PASS() do { if (wg) named_arrive<5, 256>(); else named_arrive<6, 256>(); } while (0)
#define WG_BAR() do { if (wg) named_bar<2, 128>(); else named_bar<1, 128>(); } while (0)
        uint32_t held = 0, tgt = 0;
#define PEEK() do { if (wg == 0) tgt = *reinterpret_cast<volatile uint32_t*>(smem + OFF_SEL + 8); } while (0)
#define HOLD(step) do { if (tgt != held) { held = tgt; sleep_until(tgt + 1024u * (step) - 100u); \
                int n = 0; while ((int)(clock32() - tgt - 1024u * (step)) < 0 && ++n < SPIN_LIMIT) {} } } while (0)
        if (wg == 1) PASS();

#define MMA1_P(O, s, first, pass) do { _Pragma("unroll") for (int kk = 0; kk < 4; kk++) { if (kk == PK && (pass)) PASS(); \
            wgmma128<O, 0>(acc, dL + (s) * SL + kk * 2 + (O) * 8, dS + DSLOT(s) * SL + kk * 2, !((first) && kk == 0)); } \
            if (PK == 4 && (pass)) PASS(); } while (0)
#define MMA1_H(O, s, first) MMA1_P(O, s, first, false)
#define WAIT1(s, ph) WAIT_FULL(s, ph, DSLOT(s), ph)
#define PROBE(ls, lph, ss, sph) (mbar_test(BAR(B_FS + (ss)), sph) & mbar_test(fL + 8u * (ls), lph))
#define REL1(s) RELEASE(s, DSLOT(s))
#pragma unroll 1
        for (int it = 0; it < 12; it++) {
            const int s = it & 3;
            const bool ok = PROBE(s, (it >> 2) & 1, DSLOT(s), (it >> 2) & 1);
            PEEK();
            if (it) { wg_wait<0>(); REL1((it - 1) & 3); }
            if (!ok) WAIT1(s, (it >> 2) & 1);
            HOLD(it);
            TURN();
            wg_fence(); MMA1_H(0, s, it == 0); MMA1_H(64, s, it == 0); wg_commit();
            PASS();
            if (it == QJ && tid == 0) { mbar_arrive(BAR(B_QUIET)); PROF_T(15); }
            if (it == 0 && tid == 0) PROF_T(16);
        }
        TS(12);
        float rs[4] = {};
        uint32_t nm[8] = {};
#define GET_STATS() do { mbar_wait(BAR(B_STATS), 0); \
            const int p0 = POS(wg * 128 + wq * 16 + (lane >> 2));                   \
            const uint32_t msk = (lane & 3) == 0 ? 0xffffffffu : (lane & 3) == 1 ? 0x0000ffffu : 0u; \
            _Pragma("unroll") for (int i = 0; i < 4; i++) { \
                const int p = p0 + (i & 1) * 2 + (i >> 1) * 64; \
                rs[i] = *reinterpret_cast<const float*>(smem + OFF_RSTD + p * 4); \
                const uint32_t m = *reinterpret_cast<const uint16_t*>(smem + OFF_MEAN + p * 2) ^ 0x8000u; \
                nm[i + (i & 2)] = (m | (m << 16)) & msk; \
            } } while (0)
        const bool early = wg || __all_sync(0xffffffffu, mbar_test(BAR(B_STATS), 0));
        if (early && !wg) GET_STATS();
        WAIT1(0, 1);
        TS(13);
        wg_wait<0>(); REL1(3);
        if (wg) GET_STATS();
        TS(14);
        TURN();
        wg_fence();
        MMA1_H(0, 0, false);
        if (QJ == 12 && tid == 0) { mbar_arrive(BAR(B_QUIET)); PROF_T(15); }
        WAIT1(1, 1); wg_fence(); MMA1_H(0, 1, false);
        WAIT1(2, 1); wg_fence(); MMA1_H(0, 2, false); wg_commit();
        if (!early) GET_STATS();
        asm volatile("" : "+r"(nm[0]), "+r"(nm[1]), "+r"(nm[2]), "+r"(nm[3]), "+r"(nm[4]), "+r"(nm[5]), "+r"(nm[6]), "+r"(nm[7])::"memory");
        wg_fence();
        wgmma128_rs<64>(acc, nm + 4, (SB0 + OFF_RS) >> 4);
        wgmma128_rs<0>(acc, nm, (SB0 + OFF_RS) >> 4);
        WAIT1(3, 1); wg_fence(); MMA1_P(0, 3, false, true);
        wg_commit();
        const int mrow = wq * 16 + ((lane >> 3) & 1) * 8 + (lane & 7);
#define EPI1(O, slot, FREE) do { const uint32_t dst = sb + OFF_S + (slot) * SLOT + mrow * 128; \
            uint32_t pk[32]; \
            _Pragma("unroll") for (int i = 0; i < 32; i += 4) { \
                _Pragma("unroll") for (int k = 0; k < 4; k++) \
                    pk[i + k] = pack_bf(acc[(O) + 2 * (i + k)] * rs[(O) / 32 + (k & 1)], acc[(O) + 2 * (i + k) + 1] * rs[(O) / 32 + (k & 1)]); \
                if (i == EF) { FREE; } \
                if (i >= EF) { _Pragma("unroll") for (int v = (i == EF ? 0 : i); v <= i; v += 4) \
                    stmatrix4(dst + ((v >> 4) ^ c ^ 1) * 8192 + ((((v >> 1) & 7) + (lane >> 4)) ^ (lane & 7)) * 16, pk[v], pk[v + 1], pk[v + 2], pk[v + 3]); } } \
            if (!RF) fence_async_smem(); \
            WG_BAR(); \
            if (wt == 0) mbar_arrive(BAR(B_FS + (slot))); } while (0)
        TS(15);
        wg_wait<0>();
        fence_regs64<0>(acc);
        TS(16);
        {
            constexpr int EF = 0;
            EPI1(0, wg, if (wg) mbar_wait(BAR(B_FS), 0));
        }
        TS(17);
        TURN();
        wg_fence();
        MMA1_H(64, 0, false); wg_commit();
        MMA1_H(64, 1, false); wg_commit();
        MMA1_H(64, 2, false); wg_commit();
        wg_wait<2>(); REL1(0);
        MMA1_P(64, 3, false, true); wg_commit();
        TS(18);
        wg_wait<2>(); REL1(1);
        if (RF) { mbar_wait(BAR(B_FS), 0); mbar_wait(BAR(B_FS + 1), 0); fence_async_smem(); }
        wg_wait<1>(); REL1(2);
        wg_wait<0>(); REL1(3);
        fence_regs64<64>(acc);
        TS(19);
        {
            constexpr int EF = EF2;
            EPI1(64, 2 + wg, mbar_wait(BAR(B_ES + 2 + wg), 1));
        }
        TS(20);

        float ac2[128];
#define MMA2_P(O, ls, ss, first, pass) do { _Pragma("unroll") for (int kk = 0; kk < 4; kk++) { if (kk == PK && (pass)) PASS(); \
            wgmma128<O, 1>(ac2, dS + (ss) * SL + kk * 128 + (O) * 8, dL + (ls) * SL + kk * 2, !((first) && kk == 0)); } \
            if (PK == 4 && (pass)) PASS(); } while (0)
#define MMA2_H(O, ls, ss, first) MMA2_P(O, ls, ss, first, false)
#define WAIT2(j) WAIT_FULL((j) & 3, ((j) >> 2) & 1, PSLOT(j), PPAR(j))
#define MMA2(j, pass) do { wg_fence(); MMA2_H(0, (j) & 3, PSLOT(j), (j) == 0); MMA2_P(64, (j) & 3, PSLOT(j), (j) == 0, pass); wg_commit(); } while (0)
#define REL2(j) RELEASE((j) & 3, PSLOT(j))
        if (GOJ == 0 && wt == 0) mbar_arrive(BAR(B_GO));
        WAIT2(0); TURN(); MMA2(0, false);
        WAIT2(1); MMA2(1, true);
        if (GOJ == 1 && wt == 0) mbar_arrive(BAR(B_GO));
        TS(21);
        wg_wait<1>(); REL2(0);
        if (RF) { mbar_wait(BAR(B_FS + 2), 0); mbar_wait(BAR(B_FS + 3), 0); fence_async_smem(); }
        TS(22);
        {
            uint32_t sp = 1;
#pragma unroll 1
            for (int j = 2; j < XJ; j++) {
                const uint32_t ss = PSLOT(j);
                const bool ok = PROBE(j & 3, (j >> 2) & 1, ss, PPAR(j));
                PEEK();
                wg_wait<0>(); RELEASE((j - 1) & 3, sp);
                if (!ok) WAIT_FULL(j & 3, (j >> 2) & 1, ss, PPAR(j));
                HOLD(16 + j);
                TURN();
                wg_fence(); MMA2_H(0, j & 3, ss, false); MMA2_P(64, j & 3, ss, false, true); wg_commit();
                if (j == GOJ && wt == 0) { mbar_arrive(BAR(B_GO)); if (wg == 0) PROF_T(19); }
                sp = ss;
            }
        }
        if (tid == 0) PROF_T(20);
        uint32_t gt[32];
        const uint32_t xrow = sb + OFF_S + (2 + wg) * SLOT + ((lane >> 4) * 8 + (lane & 7)) * 128 + (((2 * wq + ((lane >> 3) & 1)) ^ (lane & 7)) << 4);
        const uint32_t gsign = c ? 0x80008000u : 0u;
        mbar_wait(BAR(B_FS + 2 + wg), 1);
        mbar_wait(BAR(B_SEL), 0);
        const int sel = 0xffff - (int)(*reinterpret_cast<volatile unsigned*>(smem + OFF_SEL) & 0xffffu);
        bool own = (sel >> 7) == 2 * g + wg;
#define PATCH() do { own = false; \
            const uint32_t v0 = *reinterpret_cast<const uint16_t*>(smem + OFF_H + (wq * 16 + (lane >> 2)) * 2) ^ gsign; \
            const uint32_t v1 = *reinterpret_cast<const uint16_t*>(smem + OFF_H + (wq * 16 + (lane >> 2)) * 2 + 16) ^ gsign; \
            const uint32_t pick = (lane & 3) != ((sel >> 1) & 3) ? 0x3210u : (sel & 1) ? 0x5410u : 0x3254u; \
            _Pragma("unroll") for (int i = 0; i < 16; i++) { \
                const uint32_t m = ((sel >> 3) & 15) == i ? pick : 0x3210u; \
                gt[2 * i] = __byte_perm(gt[2 * i], v0, m); \
                gt[2 * i + 1] = __byte_perm(gt[2 * i + 1], v1, m); \
            } } while (0)
#pragma unroll
        for (int v = 0; v < 28 - XJ; v++) {
            WAIT2(XJ + v); wg_wait<0>(); REL2(XJ + v - 1); TURN(); MMA2(XJ + v, true);
            constexpr int NS = 8 / (28 - XJ);
#pragma unroll
            for (int u = v * NS; u < (v + 1) * NS; u++) {
                uint32_t* o = &gt[4 * u];
                ldmatrix4t(xrow + u * 2048, o[0], o[1], o[2], o[3]);
                const float4 r4 = *reinterpret_cast<const float4*>(smem + OFF_RSTD + (wg * 128 + u * 16 + (lane & 3) * 4) * 4);
                const uint2 m2 = *reinterpret_cast<const uint2*>(smem + OFF_MEAN + (wg * 128 + u * 16 + (lane & 3) * 4) * 2);
                o[0] = gate2(o[0], m2.x, r4.x, r4.y) ^ gsign;
                o[1] = gate2(o[1], m2.x, r4.x, r4.y) ^ gsign;
                o[2] = gate2(o[2], m2.y, r4.z, r4.w) ^ gsign;
                o[3] = gate2(o[3], m2.y, r4.z, r4.w) ^ gsign;
                asm volatile("st.shared.v2.u32 [%0], {%1,%2};" ::"r"(sb + OFF_SEL + 16), "r"(o[0] ^ o[1]), "r"(o[2] ^ o[3]) : "memory");
            }
        }
        if (tid == 0) PROF_T(21);
        WAIT2(28);
        wg_wait<0>(); REL2(27);
        if (own) {
            const uint32_t t0 = clock32();
            bool ok;
            while (!(ok = mbar_test(BAR(B_UPD), 0)) && clock32() - t0 < wg * 1400u) __nanosleep(50);
            if (__all_sync(0xffffffffu, ok)) PATCH();
        }
        TS(0);
        TURN();
        wg_fence(); MMA2_H(0, 0, PSLOT(28), false); wg_commit();
        if (wg == 0 || !ASYM) { wg_fence(); MMA2_H(64, 0, PSLOT(28), false); wg_commit(); }
        WAIT2(29); wg_fence(); MMA2_H(0, 1, PSLOT(29), false); wg_commit();
        WAIT2(30); wg_fence(); MMA2_H(0, 2, PSLOT(30), false); wg_commit();
        wg_wait<2>();
        if (tid == 0) mbar_arrive_cluster(mapa(BAR(B_RDY), c ^ 1));
        WAIT2(31); wg_fence(); MMA2_H(0, 3, PSLOT(31), false); wg_commit();
        TS(1);
#define KEEP(i) wgmma128<64, 1>(ac2, dS + PSLOT(29 + ((i) >> 2)) * SL + ((i) & 3) * 128 + 512, dL + (1 + ((i) >> 2)) * SL + ((i) & 3) * 2, 1)
        wg_fence();
#pragma unroll
        for (int i = 0; i < KQ; i++) KEEP(i);
        wg_commit();
        mbar_wait(BAR(B_RDY + wg), 0);
        wg_wait<1>();
        fence_regs64<0>(ac2);
        TS(2);
        wg_fence();
        {
            const uint32_t dst = mapa(sb + OFF_L + wg * SLOT + wt * 16, c ^ 1), rb = mapa(BAR(B_RECV + 2 * wg), c ^ 1);
#pragma unroll
            for (int v = 0; v < 8; v++) {
                if (KQ + v < 12) KEEP(KQ + v);
                if (KQ + v == 11) { wg_commit(); if (wg == 0) PASS(); }
                st_async4(dst + v * 2048, pack_bf(ac2[8 * v + 0], ac2[8 * v + 1]), pack_bf(ac2[8 * v + 2], ac2[8 * v + 3]),
                          pack_bf(ac2[8 * v + 4], ac2[8 * v + 5]), pack_bf(ac2[8 * v + 6], ac2[8 * v + 7]), rb + (v >> 2) * 8);
            }
        }
        if (wg == 1 && ASYM) { wg_fence(); MMA2_H(64, 0, PSLOT(28), false); wg_commit(); }
        TS(3);
        uint32_t xr[32];
#define LDX(v) ldmatrix4t(xrow + (v) * 2048, xr[4 * (v)], xr[4 * (v) + 1], xr[4 * (v) + 2], xr[4 * (v) + 3])
#pragma unroll
        for (int v = 0; v < XE; v++) LDX(v);
        if (wg == 0) {
            wg_wait<0>();
            if (wt == 0) mbar_arrive_cluster(mapa(BAR(B_RDY + 1), c ^ 1));
        }
        TS(4);
        if (own) { mbar_wait(BAR(B_UPD), 0); PATCH(); }
        TS(5);
        uint4 rv[8];
#define FETCH(v0) do { if ((v0) == 0 || (v0) == 4) mbar_wait_cluster(BAR(B_RECV + 2 * wg + (v0) / 4), 0); \
            _Pragma("unroll") for (int v = (v0); v < (v0) + OP; v++) { \
                asm volatile("ld.shared.v4.u32 {%0,%1,%2,%3}, [%4];" : "=r"(rv[v].x), "=r"(rv[v].y), "=r"(rv[v].z), "=r"(rv[v].w) \
                             : "r"(sb + OFF_L + wg * SLOT + v * 2048 + wt * 16) : "memory"); \
                if (v >= XE) LDX(v); } } while (0)
        FETCH(0);
        TS(6);
        wg_wait<0>();
        fence_regs64<64>(ac2);
        TS(7);
#pragma unroll
        for (int v0 = 0; v0 < 8; v0 += OP) {
#pragma unroll
            for (int v = v0; v < v0 + OP; v++) {
                const float* a = &ac2[64 + 8 * v];
                stmatrix4t(xrow + v * 2048,
                           bfma2(bsub2(pack_bf(a[0], a[1]), rv[v].x), gt[4 * v + 0], xr[4 * v + 0]),
                           bfma2(bsub2(pack_bf(a[2], a[3]), rv[v].y), gt[4 * v + 1], xr[4 * v + 1]),
                           bfma2(bsub2(pack_bf(a[4], a[5]), rv[v].z), gt[4 * v + 2], xr[4 * v + 2]),
                           bfma2(bsub2(pack_bf(a[6], a[7]), rv[v].w), gt[4 * v + 3], xr[4 * v + 3]));
            }
            WG_BAR();
            if (wt == 0) mbar_arrive(eL + 8 * (v0 / OP));
            if (v0 + OP < 8) FETCH(v0 + OP);
            if (v0 == 0) TS(8);
        }
        TS(9);
    }
}

typedef CUresult (*EncodeFn)(CUtensorMap*, CUtensorMapDataType, cuuint32_t, void*, const cuuint64_t*, const cuuint64_t*,
                             const cuuint32_t*, const cuuint32_t*, CUtensorMapInterleave, CUtensorMapSwizzle,
                             CUtensorMapL2promotion, CUtensorMapFloatOOBfill);

void make_map(EncodeFn fn, CUtensorMap* tm, const void* p, uint64_t rows, uint64_t cols, uint32_t box_rows,
              CUtensorMapL2promotion promo = CU_TENSOR_MAP_L2_PROMOTION_L2_128B) {
    cuuint64_t dims[2] = {cols, rows};
    cuuint64_t strides[1] = {cols * 2};
    cuuint32_t box[2] = {64, box_rows};
    cuuint32_t es[2] = {1, 1};
    fn(tm, CU_TENSOR_MAP_DATA_TYPE_BFLOAT16, 2, const_cast<void*>(p), dims, strides, box, es, CU_TENSOR_MAP_INTERLEAVE_NONE,
       CU_TENSOR_MAP_SWIZZLE_128B, promo, CU_TENSOR_MAP_FLOAT_OOB_FILL_NONE);
}

}

extern "C" void kernel_launch(void* const* d_in, const int* in_sizes, int n_in, void* d_out, int out_size) {
    (void)in_sizes; (void)n_in; (void)out_size;
    static EncodeFn fn = nullptr;
    if (!fn) {
        void* p = nullptr;
        cudaDriverEntryPointQueryResult q;
        cudaGetDriverEntryPoint("cuTensorMapEncodeTiled", &p, cudaEnableDefault, &q);
        fn = (EncodeFn)p;
        cudaFuncSetAttribute(fnet_fused_kernel, cudaFuncAttributeMaxDynamicSharedMemorySize, SMEM_BYTES);
    }
    CUtensorMap tx, tdre, tdim, tcre, tcim, tout;
    make_map(fn, &tx, d_in[0], S_, D_, 128, PRX);
    make_map(fn, &tcre, d_in[1], S_, S_, 128, PRC);
    make_map(fn, &tcim, d_in[2], S_, S_, 128, PRC);
    make_map(fn, &tdre, d_in[3], D_, D_, 128, PRD);
    make_map(fn, &tdim, d_in[4], D_, D_, 128, PRD);
    make_map(fn, &tout, d_out, S_, D_, 16 * OP);
    Params P;
    P.x = (const __nv_bfloat16*)d_in[0];
    P.dre = (const __nv_bfloat16*)d_in[3];
    P.dim = (const __nv_bfloat16*)d_in[4];
    P.wr = (const __nv_bfloat16*)d_in[6];
    P.wg = (const __nv_bfloat16*)d_in[7];
    P.wu = (const __nv_bfloat16*)d_in[8];
    P.wd = (const __nv_bfloat16*)d_in[9];
    P.zero = 0;
    fnet_fused_kernel<<<NCTA, NTHREADS, SMEM_BYTES, cudaStreamPerThread>>>(tx, tdre, tdim, tcre, tcim, tout, P);
}
```

```cpp
#include <cuda_runtime.h>
#include <cuda_bf16.h>
#include <cuda.h>
#include <stdint.h>

#define LDEL 0
#define LGAP 0
#define XS 0x5432
#define GSL 200
#define YNS 0u
#define YLD 1
#define PDEL 1000
#define PDEL3 0
#define PCH 1024
#define PGAP2 800
#define PGAP3 960
#define PGAP 800
#define PK 4
#define ASYM 1
#define RF 1
#define EF2 16
#define NLATE 1
#define XE 2
#define W0 12
#define PFX 1
#define PFJ 0
#define MAPD 1
#define ORD 1
#define PRE2 1
#define CHK 1
#define MID 1
#define PSM 3
#define PSTAG 0
#define KQ 5
#define OP 2
#define XJ0 20
#define EGAP1 0
#define EGAP2 0
#define ESTAG 0
#define QJ 12
#define GOJ 2
#define TANH 1
#define QUIET 1
#define PRX CU_TENSOR_MAP_L2_PROMOTION_L2_128B
#define PRD CU_TENSOR_MAP_L2_PROMOTION_L2_128B
#define PRC CU_TENSOR_MAP_L2_PROMOTION_L2_128B
#define SLEEP_NS 200
#define PROD_REGS 32
#define CONS_REGS 184

namespace {

constexpr int S_ = 2048, D_ = 1024, F_ = 3584;
constexpr int NCTA = 128;
constexpr int XJ = XJ0;
constexpr uint32_t SLOT = 16384;
constexpr uint32_t OFF_L = 0;
constexpr uint32_t OFF_S = 8 * SLOT;
constexpr uint32_t OFF_RS = OFF_S + SLOT;
constexpr uint32_t OFF_BAR = 14 * SLOT;
constexpr uint32_t OFF_SEL = OFF_BAR + 360;
constexpr uint32_t OFF_RSTD = OFF_BAR + 384;
constexpr uint32_t OFF_MEAN = OFF_RSTD + 1024;
constexpr uint32_t OFF_XB = OFF_MEAN + 512;
constexpr uint32_t OFF_H = OFF_XB + 1024;
constexpr uint32_t SMEM_BYTES = OFF_H + 128;
constexpr uint32_t OFF_TS = OFF_XB + 512;
constexpr uint32_t SB0 = 1024;
constexpr int NTHREADS = 512;
static_assert(SMEM_BYTES <= 232448, "smem");

enum { B_FS = 0, B_ES = 6, B_FL = 12, B_EL = 20, B_SRD = 28, B_RECV = 30  , B_RDY = 34, B_STATS = 36, B_LST = 37, B_UPD = 38,
       B_QUIET = 39, B_GO = 40, B_PEER = 41, B_SEL = 42, B_H = 43, B_CHK = 44, B_COUNT = 45 };
static_assert(B_COUNT * 8 <= 360, "barriers");

__device__ __align__(1024) uint8_t g_ab[16u * 32u * SLOT];
__device__ __align__(128) uint4 g_part[56 * (D_ / 4)];
__device__ __align__(128) uint4 g_stat[S_];
__device__ __align__(128) uint4 g_rs[D_];
__device__ __align__(128) unsigned long long g_key[NCTA];
__device__ __align__(128) unsigned long long g_flag[16 * 16];
__device__ __align__(128) unsigned g_epoch[NCTA];
#define PROF_T(i) do {} while (0)
#define TRACE(i) do {} while (0)
#define PROF_G(i) do {} while (0)
#define TS(i) do {} while (0)
#define FINISH(wg) bulk_wait_read<0>()

#define MARK(it) do {} while (0)

__device__ __forceinline__ uint32_t smem_u32(const void* p) { return (uint32_t)__cvta_generic_to_shared(p); }
__device__ __forceinline__ void mbar_init(uint32_t bar, uint32_t cnt) {
    asm volatile("mbarrier.init.shared::cta.b64 [%0], %1;" ::"r"(bar), "r"(cnt) : "memory");
}
__device__ __forceinline__ bool mbar_try(uint32_t bar, uint32_t parity) {
    uint32_t ok;
    asm volatile("{\n.reg .pred p;\nmbarrier.try_wait.parity.shared::cta.b64 p, [%1], %2;\nselp.u32 %0, 1, 0, p;\n}"
                 : "=r"(ok) : "r"(bar), "r"(parity) : "memory");
    return ok;
}
__device__ __forceinline__ bool mbar_test(uint32_t bar, uint32_t parity) {
    uint32_t ok;
    asm volatile("{\n.reg .pred p;\nmbarrier.test_wait.parity.shared::cta.b64 p, [%1], %2;\nselp.u32 %0, 1, 0, p;\n}"
                 : "=r"(ok) : "r"(bar), "r"(parity) : "memory");
    return ok;
}
__device__ __forceinline__ bool mbar_try_cluster(uint32_t bar, uint32_t parity) {
    uint32_t ok;
    asm volatile("{\n.reg .pred p;\nmbarrier.try_wait.parity.acquire.cluster.shared::cta.b64 p, [%1], %2;\nselp.u32 %0, 1, 0, p;\n}"
                 : "=r"(ok) : "r"(bar), "r"(parity) : "memory");
    return ok;
}
constexpr int SPIN_LIMIT = 1 << 20;
__device__ __forceinline__ void mbar_wait(uint32_t bar, uint32_t parity) {
    if (mbar_try(bar, parity)) return;
    int n = 0;
    while (!mbar_try(bar, parity) && ++n < SPIN_LIMIT) {}
}
__device__ __forceinline__ void mbar_wait_cluster(uint32_t bar, uint32_t parity) {
    int n = 0;
    while (!mbar_try_cluster(bar, parity) && ++n < SPIN_LIMIT) {}
}
__device__ __forceinline__ void mbar_wait_sleep(uint32_t bar, uint32_t parity) {
    int n = 0;
    while (!mbar_try(bar, parity) && ++n < SPIN_LIMIT) __nanosleep(SLEEP_NS);
}
__device__ __forceinline__ void mbar_arrive(uint32_t bar) {
    asm volatile("mbarrier.arrive.shared::cta.b64 _, [%0];" ::"r"(bar) : "memory");
}
__device__ __forceinline__ void mbar_arrive_cluster(uint32_t cluster_bar) {
    asm volatile("mbarrier.arrive.shared::cluster.b64 _, [%0];" ::"r"(cluster_bar) : "memory");
}
__device__ __forceinline__ void mbar_expect_tx(uint32_t bar, uint32_t bytes) {
    asm volatile("mbarrier.arrive.expect_tx.shared::cta.b64 _, [%0], %1;" ::"r"(bar), "r"(bytes) : "memory");
}
__device__ __forceinline__ bool elect_one() {
    uint32_t p;
    asm volatile("{\n.reg .pred p;\nelect.sync _|p, 0xffffffff;\nselp.u32 %0, 1, 0, p;\n}" : "=r"(p));
    return p;
}
__device__ __forceinline__ uint32_t mapa(uint32_t addr, uint32_t rank) {
    uint32_t r;
    asm("mapa.shared::cluster.u32 %0, %1, %2;" : "=r"(r) : "r"(addr), "r"(rank));
    return r;
}
__device__ __forceinline__ uint32_t clock32() { uint32_t t; asm volatile("mov.u32 %0, %%clock;" : "=r"(t)); return t; }
__device__ __forceinline__ void sleep_until(uint32_t t) {
    int n = 0;
    while ((int)(clock32() - t) < 0 && ++n < SPIN_LIMIT) __nanosleep(20);
}
__device__ __forceinline__ void yield(float last, uint32_t zero) {
    if (YLD) asm volatile("nanosleep.u32 %0;" ::"r"((__float_as_uint(last) & zero) | YNS));
}
template <typename T> __device__ __forceinline__ T* at(T* p, uint32_t bytes) {
    asm("" : "+r"(bytes));
    return reinterpret_cast<T*>(reinterpret_cast<uintptr_t>(p) + bytes);
}
__device__ __forceinline__ void tma_2d(uint32_t dst, const CUtensorMap* tm, int c0, int c1, uint32_t bar) {
    asm volatile("cp.async.bulk.tensor.2d.shared::cluster.global.mbarrier::complete_tx::bytes [%0], [%1, {%3, %4}], [%2];"
                 ::"r"(dst), "l"(tm), "r"(bar), "r"(c0), "r"(c1) : "memory");
}
__device__ __forceinline__ void tma_2d_prefetch(const CUtensorMap* tm, int c0, int c1) {
    asm volatile("cp.async.bulk.prefetch.tensor.2d.L2.global [%0, {%1, %2}];" ::"l"(tm), "r"(c0), "r"(c1) : "memory");
}
__device__ __forceinline__ void tma_2d_store(const CUtensorMap* tm, int c0, int c1, uint32_t src) {
    asm volatile("cp.async.bulk.tensor.2d.global.shared::cta.bulk_group [%0, {%2, %3}], [%1];"
                 ::"l"(tm), "r"(src), "r"(c0), "r"(c1) : "memory");
}
__device__ __forceinline__ void bulk_g2s(uint32_t dst, const void* src, uint32_t bytes, uint32_t bar) {
    asm volatile("cp.async.bulk.shared::cluster.global.mbarrier::complete_tx::bytes [%0], [%1], %2, [%3];"
                 ::"r"(dst), "l"(src), "r"(bytes), "r"(bar) : "memory");
}
__device__ __forceinline__ void bulk_s2g(void* dst, uint32_t src, uint32_t bytes) {
    asm volatile("cp.async.bulk.global.shared::cta.bulk_group [%0], [%1], %2;" ::"l"(dst), "r"(src), "r"(bytes) : "memory");
}
__device__ __forceinline__ void st_async4(uint32_t dst, uint32_t a, uint32_t b, uint32_t c, uint32_t d, uint32_t bar) {
    asm volatile("st.async.weak.shared::cluster.mbarrier::complete_tx::bytes.v4.b32 [%0], {%1,%2,%3,%4}, [%5];"
                 ::"r"(dst), "r"(a), "r"(b), "r"(c), "r"(d), "r"(bar) : "memory");
}
__device__ __forceinline__ void bulk_commit() { asm volatile("cp.async.bulk.commit_group;" ::: "memory"); }
template <int N> __device__ __forceinline__ void bulk_wait_read() { asm volatile("cp.async.bulk.wait_group.read %0;" ::"n"(N) : "memory"); }
template <int N> __device__ __forceinline__ void bulk_wait() { asm volatile("cp.async.bulk.wait_group %0;" ::"n"(N) : "memory"); }
__device__ __forceinline__ void fence_async_smem() { asm volatile("fence.proxy.async.shared::cta;" ::: "memory"); }
__device__ __forceinline__ void fence_async_global() { asm volatile("fence.proxy.async.global;" ::: "memory"); }
__device__ __forceinline__ void prefetch_tmap(const CUtensorMap* tm) {
    asm volatile("prefetch.tensormap [%0];" ::"l"(tm) : "memory");
}
__device__ __forceinline__ unsigned long long ld_acquire64(const unsigned long long* p) {
    unsigned long long v; asm volatile("ld.acquire.gpu.global.u64 %0, [%1];" : "=l"(v) : "l"(p) : "memory"); return v;
}
__device__ __forceinline__ unsigned load_epoch(int b) {
    unsigned v; asm volatile("ld.global.u32 %0, [%1];" : "=r"(v) : "l"(at(g_epoch, b * 4)) : "memory"); return v + 1;
}
__device__ __forceinline__ unsigned ld_relaxed(const void* p) {
    unsigned v; asm volatile("ld.relaxed.gpu.global.u32 %0, [%1];" : "=r"(v) : "l"(p) : "memory"); return v;
}
__device__ __forceinline__ uint4 ld_relaxed128(const uint4* p) {
    uint4 v;
    asm volatile("{\n.reg .b128 t;\n.reg .b64 lo, hi;\nld.relaxed.gpu.global.b128 t, [%4];\nmov.b128 {lo, hi}, t;\n"
                 "mov.b64 {%0, %1}, lo;\nmov.b64 {%2, %3}, hi;\n}"
                 : "=r"(v.x), "=r"(v.y), "=r"(v.z), "=r"(v.w) : "l"(p) : "memory");
    return v;
}
__device__ __forceinline__ void st_relaxed128(uint4* p, const uint4& v) {
    asm volatile("{\n.reg .b128 t;\n.reg .b64 lo, hi;\nmov.b64 lo, {%1, %2};\nmov.b64 hi, {%3, %4};\nmov.b128 t, {lo, hi};\n"
                 "st.relaxed.gpu.global.b128 [%0], t;\n}"
                 ::"l"(p), "r"(v.x), "r"(v.y), "r"(v.z), "r"(v.w) : "memory");
}
__device__ __forceinline__ void st_relaxed64(unsigned long long* p, unsigned long long v) {
    asm volatile("st.relaxed.gpu.global.u64 [%0], %1;" ::"l"(p), "l"(v) : "memory");
}
__device__ __forceinline__ void st_release8(void* p, unsigned v) {
    asm volatile("st.release.gpu.global.u8 [%0], %1;" ::"l"(p), "r"(v) : "memory");
}
__device__ __forceinline__ uint64_t policy_evict_first() {
    uint64_t pol;
    asm("createpolicy.fractional.L2::evict_first.b64 %0, 1.0;" : "=l"(pol));
    return pol;
}
__device__ __forceinline__ uint4 ldg_stream(const void* p, uint64_t pol) {
    uint4 v;
    asm volatile("ld.global.nc.L1::no_allocate.L2::cache_hint.v4.u32 {%0,%1,%2,%3}, [%4], %5;"
                 : "=r"(v.x), "=r"(v.y), "=r"(v.z), "=r"(v.w) : "l"(p), "l"(pol));
    return v;
}
template <int ID, int N> __device__ __forceinline__ void named_arrive() { asm volatile("bar.arrive %0, %1;" ::"n"(ID), "n"(N) : "memory"); }
template <int ID, int N> __device__ __forceinline__ void named_bar() { asm volatile("bar.sync %0, %1;" ::"n"(ID), "n"(N) : "memory"); }

__device__ __forceinline__ float bf_lo(uint32_t u) { return __uint_as_float(u << 16); }
__device__ __forceinline__ float bf_hi(uint32_t u) { return __uint_as_float(u & 0xffff0000u); }
__device__ __forceinline__ uint32_t pack_bf(float lo, float hi) {
    uint32_t r; asm("cvt.rn.bf16x2.f32 %0, %1, %2;" : "=r"(r) : "f"(hi), "f"(lo)); return r;
}
__device__ __forceinline__ float rbf(float v) { return __uint_as_float(pack_bf(0.f, v)); }
__device__ __forceinline__ float sqrt_f(float v) { float r; asm("sqrt.approx.f32 %0, %1;" : "=f"(r) : "f"(v)); return r; }
__device__ __forceinline__ float rcp_f(float v) { float r; asm("rcp.approx.f32 %0, %1;" : "=f"(r) : "f"(v)); return r; }
__device__ __forceinline__ float silu_f(float z) { return __fdividef(z, 1.0f + __expf(-z)); }
__device__ __forceinline__ uint32_t bsub2(uint32_t a, uint32_t b) {
    uint32_t r; asm("sub.rn.bf16x2 %0, %1, %2;" : "=r"(r) : "r"(a), "r"(b)); return r;
}
__device__ __forceinline__ uint32_t bfma2(uint32_t a, uint32_t b, uint32_t c) {
    uint32_t r; asm("fma.rn.bf16x2 %0, %1, %2, %3;" : "=r"(r) : "r"(a), "r"(b), "r"(c)); return r;
}
__device__ __forceinline__ uint32_t norm2(uint32_t xv, float m, float rinv) {
    uint32_t t = pack_bf(bf_lo(xv) - m, bf_hi(xv) - m);
    return pack_bf(bf_lo(t) * rinv, bf_hi(t) * rinv);
}
__device__ __forceinline__ float gate1(float z) {
    if (TANH) {
        float t;
        const float h = 0.5f * z;
        asm("tanh.approx.f32 %0, %1;" : "=f"(t) : "f"(h));
        return fmaf(h, t, h);
    }
    float e, r;
    asm("ex2.approx.ftz.f32 %0, %1;" : "=f"(e) : "f"(z * -1.4426950408889634f));
    asm("rcp.approx.ftz.f32 %0, %1;" : "=f"(r) : "f"(1.0f + e));
    return z * r;
}
__device__ __forceinline__ uint32_t gate2(uint32_t xv, uint32_t mean2, float r0, float r1) {
    const uint32_t t = bsub2(xv, mean2);
    return pack_bf(gate1(bf_lo(t) * r0), gate1(bf_hi(t) * r1));
}
__device__ __forceinline__ uint32_t silu2(uint32_t z) { return pack_bf(silu_f(bf_lo(z)), silu_f(bf_hi(z))); }

__device__ __forceinline__ void stmatrix4(uint32_t addr, uint32_t r0, uint32_t r1, uint32_t r2, uint32_t r3) {
    asm volatile("stmatrix.sync.aligned.m8n8.x4.shared.b16 [%0], {%1,%2,%3,%4};"
                 ::"r"(addr), "r"(r0), "r"(r1), "r"(r2), "r"(r3));
}
__device__ __forceinline__ void stmatrix4t(uint32_t addr, uint32_t r0, uint32_t r1, uint32_t r2, uint32_t r3) {
    asm volatile("stmatrix.sync.aligned.m8n8.x4.trans.shared.b16 [%0], {%1,%2,%3,%4};"
                 ::"r"(addr), "r"(r0), "r"(r1), "r"(r2), "r"(r3));
}
__device__ __forceinline__ void ldmatrix4t(uint32_t addr, uint32_t& r0, uint32_t& r1, uint32_t& r2, uint32_t& r3) {
    asm volatile("ldmatrix.sync.aligned.m8n8.x4.trans.shared.b16 {%0,%1,%2,%3}, [%4];"
                 : "=r"(r0), "=r"(r1), "=r"(r2), "=r"(r3) : "r"(addr));
}

__device__ __forceinline__ void wg_fence() { asm volatile("wgmma.fence.sync.aligned;" ::: "memory"); }
__device__ __forceinline__ void wg_commit() { asm volatile("wgmma.commit_group.sync.aligned;" ::: "memory"); }
template <int N> __device__ __forceinline__ void wg_wait() { asm volatile("wgmma.wait_group.sync.aligned %0;" ::"n"(N) : "memory"); }

__host__ __device__ constexpr uint32_t desc_lo(uint32_t addr, uint32_t lbo) { return ((addr & 0x3FFFF) >> 4) | ((lbo >> 4) << 16); }
#define DESC_HI "0x40000040"

#define R8(a, o) "+f"(a[(o) + 0]), "+f"(a[(o) + 1]), "+f"(a[(o) + 2]), "+f"(a[(o) + 3]), \
                 "+f"(a[(o) + 4]), "+f"(a[(o) + 5]), "+f"(a[(o) + 6]), "+f"(a[(o) + 7])
#define R64(a, o) R8(a, (o) + 0), R8(a, (o) + 8), R8(a, (o) + 16), R8(a, (o) + 24), \
                  R8(a, (o) + 32), R8(a, (o) + 40), R8(a, (o) + 48), R8(a, (o) + 56)

template <int O, int TA>
__device__ __forceinline__ void wgmma128(float (&a)[128], uint32_t da, uint32_t db, int scale_d) {
    asm volatile(
        "{\n.reg .pred p;\n.reg .b64 da, db;\nsetp.ne.b32 p, %66, 0;\n"
        "mov.b64 da, {%64, " DESC_HI "};\nmov.b64 db, {%65, " DESC_HI "};\n"
        "wgmma.mma_async.sync.aligned.m64n128k16.f32.bf16.bf16 "
        "{%0,%1,%2,%3,%4,%5,%6,%7,%8,%9,%10,%11,%12,%13,%14,%15,"
        "%16,%17,%18,%19,%20,%21,%22,%23,%24,%25,%26,%27,%28,%29,%30,%31,"
        "%32,%33,%34,%35,%36,%37,%38,%39,%40,%41,%42,%43,%44,%45,%46,%47,"
        "%48,%49,%50,%51,%52,%53,%54,%55,%56,%57,%58,%59,%60,%61,%62,%63},"
        "da, db, p, 1, 1, %67, 0;\n}"
        : R64(a, O)
        : "r"(da), "r"(db), "r"(scale_d), "n"(TA));
}
template <int O>
__device__ __forceinline__ void wgmma128_rs(float (&a)[128], const uint32_t* f, uint32_t db) {
    asm volatile(
        "{\n.reg .b64 db;\nmov.b64 db, {%68, 8};\n"
        "wgmma.mma_async.sync.aligned.m64n128k16.f32.bf16.bf16 "
        "{%0,%1,%2,%3,%4,%5,%6,%7,%8,%9,%10,%11,%12,%13,%14,%15,"
        "%16,%17,%18,%19,%20,%21,%22,%23,%24,%25,%26,%27,%28,%29,%30,%31,"
        "%32,%33,%34,%35,%36,%37,%38,%39,%40,%41,%42,%43,%44,%45,%46,%47,"
        "%48,%49,%50,%51,%52,%53,%54,%55,%56,%57,%58,%59,%60,%61,%62,%63},"
        "{%64, %65, %66, %67}, db, 1, 1, 1, 0;\n}"
        : R64(a, O)
        : "r"(f[0]), "r"(f[1]), "r"(f[2]), "r"(f[3]), "r"(db));
}
template <int O>
__device__ __forceinline__ void fence_regs64(float (&a)[128]) {
    asm volatile("" : R64(a, O)::"memory");
}

struct Params {
    const __nv_bfloat16* x;
    const __nv_bfloat16* dre;
    const __nv_bfloat16* dim;
    const __nv_bfloat16* wr;
    const __nv_bfloat16* wg;
    const __nv_bfloat16* wu;
    const __nv_bfloat16* wd;
    uint32_t zero;
#define AB g_ab
};

__device__ __forceinline__ float warp_sum(float v) {
#pragma unroll
    for (int o = 16; o; o >>= 1) v += __shfl_xor_sync(0xffffffffu, v, o);
    return v;
}
__device__ __forceinline__ void fma8(float* acc, const uint4& w, float s) {
    acc[0] += s * bf_lo(w.x); acc[1] += s * bf_hi(w.x); acc[2] += s * bf_lo(w.y); acc[3] += s * bf_hi(w.y);
    acc[4] += s * bf_lo(w.z); acc[5] += s * bf_hi(w.z); acc[6] += s * bf_lo(w.w); acc[7] += s * bf_hi(w.w);
}
__device__ __forceinline__ int POS(int t) { return (t & ~15) | ((t & 6) << 1) | ((t & 8) >> 2) | (t & 1); }
__host__ __device__ constexpr int PSLOT(int j) { return j < 4 ? j : (j & 1) + ((j & 2) ? 0 : 4); }
__host__ __device__ constexpr int PPAR(int j) { return j < 4 ? 0 : ((j >> 2) ^ (j >> 1) ^ 1) & 1; }
__host__ __device__ constexpr int DSLOT(int it) { return (it & 3) + 2; }
__device__ __forceinline__ int SREC(int t) { return (t & ~15) | ((t & 3) << 2) | ((t >> 2) & 3); }
__device__ __forceinline__ int KO(int cl) { return ((cl & 1) << 1) | (cl >> 1); }

__global__ void __cluster_dims__(2, 1, 1) __launch_bounds__(NTHREADS, 1)
fnet_fused_kernel(const __grid_constant__ CUtensorMap tm_x, const __grid_constant__ CUtensorMap tm_dre,
                  const __grid_constant__ CUtensorMap tm_dim, const __grid_constant__ CUtensorMap tm_cre,
                  const __grid_constant__ CUtensorMap tm_cim, const __grid_constant__ CUtensorMap tm_out,
                  const __grid_constant__ CUtensorMap tm_x64,
                  const Params P) {
    extern __shared__ __align__(1024) uint8_t smem[];
    const unsigned long long tstart = clock64();
    const uint32_t sb = smem_u32(smem);
    const int tid = threadIdx.x, lane = tid & 31;
    const int warp = __shfl_sync(0xffffffffu, tid >> 5, 0);
    const int pr = blockIdx.x >> 1, p7 = ((pr - 36) * 37) >> 8;
    const int c = blockIdx.x & 1;
    const int gi = pr < 4 ? 7 : pr < 36 ? 2 * ((pr - 4) & 7) + (((pr - 4) >> 2) & 1) : 2 * (pr - 36 - 7 * p7) + 1 + (pr - 36 - 7 * p7 > 2);
    const int g = gi & 7;
    const int r = (gi >> 3) * 4 + (pr < 4 ? pr : pr < 36 ? (pr - 4) >> 3 : p7);
#define BLK(n) (ORD ? (n) - ((n) <= g) : (g + (n)) & 7)
    const int grp = 2 * r + c;
    const int b = g * 16 + grp;
    const uint32_t bar0 = sb + OFF_BAR;
    const uint32_t zero = P.zero;
#define BAR(i) (bar0 + 8u * (i))
#define XBAR(i) (sb + OFF_XB + 64 + 8u * (i))
#define CLUSTER_ARRIVE() asm volatile("barrier.cluster.arrive.relaxed.aligned;" ::: "memory")
#define CLUSTER_WAIT() asm volatile("barrier.cluster.wait.aligned;" ::: "memory")
    if ((sb & 0xffffffu) != SB0) return;

#define LOAD0(it) do { \
            mbar_expect_tx(BAR(B_FS + DSLOT(it)), SLOT); tma_2d(sb + OFF_S + DSLOT(it) * SLOT, tmD, (it) * 64, r * 128, BAR(B_FS + DSLOT(it))); \
            mbar_expect_tx(BAR(B_FL + (it)), SLOT); tma_2d(sb + OFF_L + (it) * SLOT, &tm_x, (it) * 64, g * 256, BAR(B_FL + (it))); \
            mbar_expect_tx(BAR(B_FL + 4 + (it)), SLOT); tma_2d(sb + OFF_L + (4 + (it)) * SLOT, &tm_x, (it) * 64, g * 256 + 128, BAR(B_FL + 4 + (it))); \
        } while (0)
    if (warp == W0) {
        if (elect_one()) {
            const CUtensorMap* tmD = c ? &tm_dim : &tm_dre;
            if (PFX & 2) prefetch_tmap(tmD);
            if (PFX & 1) prefetch_tmap(&tm_x);
            mbar_init(BAR(B_FS + 2), 1); mbar_init(BAR(B_FL), 1); mbar_init(BAR(B_FL + 4), 1);
            asm volatile("fence.mbarrier_init.release.cluster;" ::: "memory");
            LOAD0(0);
        }
        __syncwarp();
    }
    if (warp == 12) {
        if (elect_one()) {
#pragma unroll
            for (int i = 0; i < B_COUNT; i++)
                if (i != B_FS + 2 && i != B_FL && i != B_FL + 4)
                    mbar_init(BAR(i), (i >= B_ES && i < B_FL) || i == B_GO ? 2 : i == B_STATS || i == B_LST ? 4 : 1);
#pragma unroll
            for (int i = 0; i < 12; i++) mbar_init(XBAR(i), 1);
#pragma unroll
            for (int i = 0; i < 4; i++) mbar_expect_tx(BAR(B_RECV + i), SLOT / 2);
            mbar_expect_tx(BAR(B_PEER), 1024); mbar_expect_tx(BAR(B_H), 128);
            asm volatile("fence.mbarrier_init.release.cluster;" ::: "memory");
            fence_async_smem();
        }
        __syncwarp();
    }
    CLUSTER_ARRIVE();

    if (warp >= 12) {
        asm volatile("setmaxnreg.dec.sync.aligned.u32 %0;" ::"n"(PROD_REGS));
        CLUSTER_WAIT();
        if (warp == 12) {
            if (elect_one()) {
                const CUtensorMap* tmD = c ? &tm_dim : &tm_dre;
#define XROWS(k) do { mbar_expect_tx(XBAR(k), 8192); bulk_g2s(sb + OFF_S + (k) * 8192, at(P.x, (b * 16 + (k) * 4) * D_ * 2), 8192, XBAR(k)); } while (0)
                int k = 0;
#pragma unroll 1
                for (int it = 1; it < 16; it++) {
                    if (it < 4) { if (LDEL) sleep_until((uint32_t)tstart + LDEL + (it - 1) * LGAP); LOAD0(it); }
                    else {
                        const int s = DSLOT(it);
                        mbar_wait(BAR(B_ES + s), ((it >> 2) & 1) ^ 1);
                        TRACE(it);
                        mbar_expect_tx(BAR(B_FS + s), SLOT);
                        tma_2d(sb + OFF_S + s * SLOT, tmD, it * 64, r * 128, BAR(B_FS + s));
                    }
                    while (((XS >> (4 * k)) & 15) == it) { XROWS(k); k++; }
                }
                const unsigned ep = load_epoch(b), e8 = ep & 0xffu;
                const uint8_t* abg = at(AB, grp * 32 * SLOT);
                const unsigned long long* fl = at(g_flag, grp * 128);
                unsigned long long rdy = ld_acquire64(fl);
                mbar_wait(BAR(B_SRD), 0);
                st_release8(at(g_flag, grp * 128 + g), e8);
                PROF_T(7);
                int j = 4;
#pragma unroll 1
                for (int cl = 0; cl < 4; cl++) {
                    if (cl) {
                        int m = 0;
                        fl++;
                        do { rdy = ld_acquire64(fl); } while (CHK && ((unsigned)rdy != e8 * 0x01010101u || (unsigned)(rdy >> 32) != e8 * 0x01010101u) && ++m < SPIN_LIMIT);
                        if (CHK && cl < 3) mbar_arrive(BAR(B_CHK));
                    }
                    fence_async_global();
#pragma unroll 1
                    for (int n = 1; n < 8; n++, j++) {
                        const int q = BLK(n), s = (j & 1) + ((j & 2) ? 0 : 4);
                        mbar_wait(BAR(B_ES + s), ((j >> 2) ^ (j >> 1)) & 1);
                        if (j == 7) mbar_wait(BAR(B_SRD + 1), 0);
                        if (((unsigned)(rdy >> (8 * q)) & 0xffu) != e8) {
                            int m = 0;
                            do { rdy = ld_acquire64(fl); } while (((unsigned)(rdy >> (8 * q)) & 0xffu) != e8 && ++m < SPIN_LIMIT);
                            fence_async_global();
                        }
                        TRACE(16 + j);
                        mbar_expect_tx(BAR(B_FS + s), SLOT);
                        bulk_g2s(sb + OFF_S + s * SLOT, at(abg, (4 * q + KO(cl)) * SLOT), SLOT, BAR(B_FS + s));
                    }
                }
                *at(g_epoch, b * 4) = ep;
            }
        } else if (warp < 15) {
            if (elect_one()) {
                const int w = warp - 13, row0 = g * 256 + w * 128;
                const CUtensorMap* tmC = c ? &tm_cim : &tm_cre;
                const uint32_t fb = BAR(B_FL + 4 * w), eb = BAR(B_EL + 4 * w), dst = sb + OFF_L + w * 4 * SLOT;
                prefetch_tmap(w ? &tm_out : tmC);
                [[maybe_unused]] unsigned long long mk = 0;
                int n = 0, cl = 0;
#pragma unroll 1
                for (int it = 4; it < 48; it++) {
                    const int s = it & 3;
                    mbar_wait(eb + 8 * s, ((it >> 2) & 1) ^ 1);
                    TRACE(64 + w * 64 + it - 4);
                    MARK(it);
                    mbar_expect_tx(fb + 8 * s, SLOT);
                    tma_2d(dst + s * SLOT, it < 16 ? &tm_x : tmC, (it < 16 ? it : 4 * (n ? BLK(n) : g) + KO(cl)) * 64, row0, fb + 8 * s);
                    if (it == PFJ) tma_2d_prefetch(tmC, (4 * g + (r & 3)) * 64, row0);
                    if (it >= 16) {
                        if (it == 19) { n = 1; cl = 0; } else if (it < 19) cl++; else if (++n == 8) { n = 1; cl++; }
                    }
                }
                {
#pragma unroll 1
                    for (int h = 0; h < 8 / OP; h++) {
                        mbar_wait(eb + 8 * h, 1);
                        fence_async_smem();
                        tma_2d_store(&tm_out, grp * 64, row0 + h * OP * 16, sb + OFF_S + (2 + (h * OP >> 2)) * SLOT + w * 8192 + (h * OP & 3) * 2048);
                        bulk_commit();
                    }
                    FINISH(w);
                }
            }
        } else {
            const unsigned ep = load_epoch(b);
            uint4 f[4];
#define GATHER(ptr, cnt, valid) do { int n = 0; bool ok; do { ok = true; \
                _Pragma("unroll") for (int i = 0; i < (cnt); i++) { f[i] = ld_relaxed128((ptr) + i * 32); ok = ok && (valid); } \
                if (__all_sync(0xffffffffu, ok)) break; \
                __nanosleep(GSL); \
            } while (++n < SPIN_LIMIT); } while (0)
            {
                sleep_until((uint32_t)tstart + 6000);
                const uint4* keys = at(reinterpret_cast<const uint4*>(g_key), lane * 16);
                bool mine = false;
                int n = 0;
                do {
                    f[0] = ld_relaxed128(keys); f[1] = ld_relaxed128(keys + 32);
                    if (__all_sync(0xffffffffu, f[0].y == ep && f[0].w == ep && f[1].y == ep && f[1].w == ep)) break;
                    if (!mine) {
                        mbar_wait(BAR(B_LST), 0);
                        const uint4 k = *reinterpret_cast<const uint4*>(smem + OFF_XB);
                        if (lane == 0) st_relaxed64(at(g_key, b * 8), ((unsigned long long)ep << 32) | max(max(k.x, k.y), max(k.z, k.w)));
                        mine = true;
                    }
                    __nanosleep(GSL);
                } while (++n < SPIN_LIMIT);
                const unsigned key = __reduce_max_sync(0xffffffffu, max(max(f[0].x, f[0].z), max(f[1].x, f[1].z)));
                if (lane == 0) { *reinterpret_cast<unsigned*>(smem + OFF_SEL) = key; mbar_arrive(BAR(B_SEL)); PROF_T(8); }
            }
            if (elect_one()) {
#pragma unroll 1
                for (int cl = 0; cl < 4; cl++) {
                    uint8_t* dst = at(AB, (grp * 32 + 4 * g + KO(cl)) * SLOT);
                    const uint32_t src = sb + OFF_S + cl * SLOT, chunk = cl ? PCH : SLOT;
                    mbar_wait(BAR(B_FS + cl), 0);
                    if (RF) fence_async_smem();
                    if (cl == 0) PROF_T(3);
                    uint32_t t0 = clock32() + (cl == 1 ? PDEL : cl == 3 ? PDEL3 : 0);
#pragma unroll 1
                    for (uint32_t o = 0; o < SLOT; o += chunk) {
                        sleep_until(t0);
                        bulk_s2g(dst + o, src + o, chunk);
                        bulk_commit();
                        t0 += (cl == 1 ? PGAP : cl == 2 ? PGAP2 : PGAP3) / (4096 / PCH);
                    }
                    bulk_wait<0>();
                    TRACE(252 + cl);
                    if (cl < 2) mbar_arrive(BAR(B_SRD + cl));
                    else {
                        mbar_wait(BAR(B_ES + cl), 0);
                        mbar_expect_tx(BAR(B_FS + cl), SLOT);
                        tma_2d(src, &tm_x64, grp * 64, g * 256 + (cl - 2) * 64, BAR(B_FS + cl));
                        tma_2d(src + 8192, &tm_x64, grp * 64, g * 256 + (cl - 2) * 64 + 128, BAR(B_FS + cl));
                    }
                    if (CHK && cl > 1) mbar_wait(BAR(B_CHK), cl & 1);
                    if (cl) st_release8(at(g_flag, grp * 128 + cl * 8 + g), ep & 0xffu);
                    if (cl == 1) PROF_T(5);
                    if (cl == 3) PROF_T(4);
                }
            }
        }
    } else if (warp >= 8) {
        asm volatile("setmaxnreg.dec.sync.aligned.u32 %0;" ::"n"(512 - PROD_REGS - 2 * CONS_REGS));
        const int aw = warp - 8, mt = tid - 256;
        unsigned ep;
        {
            const uint8_t* rp = smem + OFF_S + aw * 2048 + lane * 16;
            const __nv_bfloat16* dp = at(c ? P.dim : P.dre, (r * 128 + g * 16 + aw * 4) * D_ * 2);
            float wf[32], sw = 0.f;
#pragma unroll
            for (int i = 0; i < 4; i++) {
                const uint4 w = __ldg(reinterpret_cast<const uint4*>(at(P.wr, lane * 16) + i * 256));
                const uint32_t wv[4] = {w.x, w.y, w.z, w.w};
#pragma unroll
                for (int e = 0; e < 4; e++) { wf[8 * i + 2 * e] = bf_lo(wv[e]); wf[8 * i + 2 * e + 1] = bf_hi(wv[e]); sw = (sw + bf_lo(wv[e])) + bf_hi(wv[e]); }
            }
            ep = load_epoch(b);
            sw = warp_sum(sw);
            CLUSTER_WAIT();
            float x0[4] = {}, s1[4] = {}, s2[4] = {}, sx[4] = {}, sd[4] = {};
#define PUSH(a, v) do { a[0] = a[1]; a[1] = a[2]; a[2] = a[3]; a[3] = v; } while (0)
#pragma unroll 1
            for (int k = 0; k < 4; k++) {
                mbar_wait(XBAR(k), 0);
                uint4 v[4];
#pragma unroll
                for (int i = 0; i < 4; i++) v[i] = *reinterpret_cast<const uint4*>(rp + k * 8192 + i * 512);
                uint32_t sh = v[0].x << 16;
                float a1s = 0.f, a2s = 0.f, axs = 0.f;
#pragma unroll
                for (int i = 0; i < 4; i++) {
                    sh = __shfl_sync(0xffffffffu, sh | (__float_as_uint(axs) & zero), 0);
                    const uint32_t xv[4] = {v[i].x, v[i].y, v[i].z, v[i].w};
#pragma unroll
                    for (int e = 0; e < 4; e++) {
                        const float a0 = bf_lo(xv[e]) - __uint_as_float(sh), a1 = bf_hi(xv[e]) - __uint_as_float(sh);
                        a1s += a0 + a1;
                        a2s = fmaf(a0, a0, fmaf(a1, a1, a2s));
                        axs = fmaf(a0, wf[8 * i + 2 * e], fmaf(a1, wf[8 * i + 2 * e + 1], axs));
                    }
                }
                PUSH(x0, __uint_as_float(sh)); PUSH(s1, a1s); PUSH(s2, a2s); PUSH(sx, axs);
                fence_async_smem();
                __syncwarp();
                if (elect_one()) {
                    const uint32_t db = XBAR(k == 3 ? 8 + aw : 4 + aw);
                    if (k == 0 || k == 3) mbar_expect_tx(db, k ? 2048 : 6144);
                    bulk_g2s(sb + OFF_S + k * 8192 + aw * 2048, dp + k * D_, 2048, db);
                }
            }
#define FOLD4(a) do { const bool u16 = lane & 16, u8 = lane & 8; \
                float p0 = (u16 ? a[2] : a[0]) + __shfl_xor_sync(0xffffffffu, u16 ? a[0] : a[2], 16); \
                float p1 = (u16 ? a[3] : a[1]) + __shfl_xor_sync(0xffffffffu, u16 ? a[1] : a[3], 16); \
                a[0] = (u8 ? p1 : p0) + __shfl_xor_sync(0xffffffffu, u8 ? p0 : p1, 8); \
                _Pragma("unroll") for (int o = 4; o; o >>= 1) a[0] += __shfl_xor_sync(0xffffffffu, a[0], o); } while (0)
#pragma unroll 1
            for (int k = 0; k < 4; k++) {
                mbar_wait(XBAR(k == 3 ? 8 + aw : 4 + aw), 0);
                float run = 0.f;
#pragma unroll
                for (int i = 0; i < 4; i++) {
                    const uint4 v = *reinterpret_cast<const uint4*>(rp + k * 8192 + i * 512);
                    const uint32_t dv[4] = {v.x, v.y, v.z, v.w};
#pragma unroll
                    for (int e = 0; e < 4; e++) run += bf_lo(dv[e]) + bf_hi(dv[e]);
                }
                PUSH(sd, run);
            }
            FOLD4(sd); FOLD4(s1); FOLD4(s2); FOLD4(sx);
            const float nb = __shfl_down_sync(0xffffffffu, sd[0], 8);
            if ((lane & 15) == 0)
                st_relaxed128(at(g_rs, (grp * 64 + g * 8 + aw * 2 + (lane >> 4)) * 16), make_uint4(__float_as_uint(sd[0]), ep, __float_as_uint(nb), ep));
            if (mt == 0) PROF_T(6);
            const int rr = lane >> 3;
            const float c0 = rr == 0 ? x0[0] : rr == 1 ? x0[1] : rr == 2 ? x0[2] : x0[3];
            const float dm = s1[0] * (1.0f / D_);
            const float mb = rbf(c0 + dm);
            const float rinv = rcp_f(rbf(sqrt_f(rbf(rbf(fmaxf(s2[0] * (1.0f / D_) - dm * dm, 0.f)) + 1e-5f))));
            if ((lane & 7) == 0) st_relaxed128(at(g_stat, (b * 16 + aw * 4 + rr) * 16), make_uint4(__float_as_uint(mb), __float_as_uint(rinv), ep, 0));
            unsigned u = __bfloat16_as_ushort(__float2bfloat16_rn((sx[0] + (c0 - mb) * sw) * rinv));
            u = (u & 0x8000u) ? (~u & 0xffffu) : (u | 0x8000u);
            u = (u << 16) | (0xffffu - (unsigned)(b * 16 + rr * 4 + aw));
            u = __reduce_max_sync(0xffffffffu, u);
            if (lane == 0) { *reinterpret_cast<unsigned*>(smem + OFF_XB + aw * 4) = u; mbar_arrive(BAR(B_LST)); }
            if (mt == 0) PROF_T(2);
            named_bar<4, 128>();
            if (mt < 12) asm volatile("mbarrier.inval.shared::cta.b64 [%0];" ::"r"(XBAR(mt)) : "memory");
            uint4 f[4];
            if (aw < 2) {
                const int t = SREC(aw * 128 + lane);
                GATHER(at(g_stat, (g * 256 + aw * 128 + lane) * 16), 4, f[i].z == ep);
#pragma unroll
                for (int i = 0; i < 4; i++) {
                    *reinterpret_cast<uint32_t*>(smem + OFF_RSTD + (POS(t) + i * 32) * 4) = f[i].y;
                    *reinterpret_cast<uint16_t*>(smem + OFF_MEAN + (POS(t) + i * 32) * 2) = (uint16_t)(f[i].x >> 16);
                }
            } else {
                const int e2 = (aw - 2) * 32 + lane;
                GATHER(at(g_rs, (grp * 64 + e2) * 16), 1, f[i].y == ep && f[i].w == ep);
#pragma unroll
                for (int i = 0; i < 2; i++) {
                    const float v = __uint_as_float(i ? f[0].z : f[0].x);
                    const float hi = rbf(v), mid = rbf(v - hi), lo = v - hi - mid;
                    *reinterpret_cast<uint4*>(smem + OFF_RS + (e2 * 2 + i) * 16) = make_uint4(pack_bf(hi, mid), pack_bf(lo, 0.f), 0, 0);
                }
            }
            fence_async_smem();
            __syncwarp();
            if (lane == 0) mbar_arrive(BAR(B_STATS));
            if (mt == 127) PROF_T(9);
        }
        const int pair = g * 7 + r;
        if (r < 7) {
            const uint64_t pol = policy_evict_first();
            const __nv_bfloat16* wp = at((aw & 1) ? P.wu : P.wg, ((c * 512 + (aw >> 1) * 256 + (lane >> 3) * 8) * F_ + pair * 64 + (lane & 7) * 8) * 2);
            uint4 b0[8], b1[8];
#define FILL(buf, str) do { _Pragma("unroll") for (int q = 0; q < 8; q++) buf[q] = ldg_stream(wp + q * (str), pol); } while (0)
            FILL(b0, F_);
            mbar_wait(BAR(B_SEL), 0);
            uint4 xn;
            {
                const int sel = 0xffff - (int)(*reinterpret_cast<volatile unsigned*>(smem + OFF_SEL) & 0xffffu);
                xn = __ldg(reinterpret_cast<const uint4*>(at(P.x, (sel * D_ + c * 512 + (aw >> 1) * 256 + (lane & 7) * 32 + (lane >> 3) * 8) * 2)));
                uint4 f[1];
                GATHER(at(g_stat, SREC(sel) * 16), 1, f[i].z == ep);
                if (PRE2) { wp += 32 * F_; FILL(b1, F_); wp -= 32 * F_; }
                if (NLATE && mbar_test(BAR(B_QUIET), 0)) mbar_wait_sleep(BAR(B_GO), 0);
                const float m = __uint_as_float(f[0].x), ri = __uint_as_float(f[0].y);
                xn = make_uint4(norm2(xn.x, m, ri), norm2(xn.y, m, ri), norm2(xn.z, m, ri), norm2(xn.w, m, ri));
            }
            float ag[8];
#pragma unroll
            for (int i = 0; i < 8; i++) ag[i] = 0.f;
            const uint32_t stag = (pair & PSM) * PSTAG + aw * ESTAG;
            uint32_t te = clock32() + stag;
            bool paused = !QUIET;
#define ROUND(cur, nxt, rd) do { \
                if (!paused && mbar_test(BAR(B_QUIET), 0)) { mbar_wait_sleep(BAR(B_GO), 0); te = clock32() + stag; paused = true; } \
                sleep_until(te); \
                te = clock32() + (paused ? EGAP2 : EGAP1); \
                if (lane == 0) TRACE(192 + aw * 12 + (rd)); \
                if ((rd) == 7) wp = at(P.wd - 16 * D_, ((pair * 64 + (lane >> 4) * 8) * D_ + c * 512 + aw * 128 + (lane & 15) * 8) * 2); \
                wp = at(wp, ((rd) < 7 ? 64 * F_ : 32 * D_) + (cur[7].x & zero)); \
                if ((rd) < 7) { if ((rd) || !PRE2) FILL(nxt, F_); } else if (((rd) != 8 || MID == 2) && (rd) < 11) FILL(nxt, D_); \
                _Pragma("unroll") for (int q = 0; q < 8; q += 2) { \
                    uint32_t xw = __shfl_sync(0xffffffffu, q == 0 ? xn.x : q == 2 ? xn.y : q == 4 ? xn.z : xn.w, (lane & 24) | ((rd) & 7)); \
                    fma8(ag, cur[q], bf_lo(xw)); \
                    if (YLD > 1) { yield(ag[7], zero); xw = __shfl_sync(0xffffffffu, xw, lane); } \
                    fma8(ag, cur[q + 1], bf_hi(xw)); \
                    if (q < 6) yield(ag[7], zero); \
                } } while (0)
#pragma unroll 1
            for (int rd = 0; rd < 12; rd += 2) {
                ROUND(b0, b1, rd);
                ROUND(b1, b0, rd + 1);
                if (rd == 6 && MID == 0) { wp += 16 * D_; FILL(b1, D_); wp -= 16 * D_; }
                if (rd == 6 || rd == 10) {
#pragma unroll
                    for (int i = 0; i < 8; i++) ag[i] += __shfl_xor_sync(0xffffffffu, ag[i], 16);
                }
                if (rd == 6) {
#pragma unroll
                    for (int i = 0; i < 8; i++) ag[i] += __shfl_xor_sync(0xffffffffu, ag[i], 8);
                    if (lane < 8) {
                        const uint32_t dst = mapa(sb + OFF_XB + (c * 4 + aw) * 128 + (lane & 3) * 32, lane >> 2), pb = mapa(BAR(B_PEER), lane >> 2);
                        st_async4(dst, __float_as_uint(ag[0]), __float_as_uint(ag[1]), __float_as_uint(ag[2]), __float_as_uint(ag[3]), pb);
                        st_async4(dst + 16, __float_as_uint(ag[4]), __float_as_uint(ag[5]), __float_as_uint(ag[6]), __float_as_uint(ag[7]), pb);
                    }
                    if (MID == 1) { __syncwarp(); wp += 16 * D_; FILL(b1, D_); wp -= 16 * D_; }
                    if (aw == 3) {
                        mbar_wait_cluster(BAR(B_PEER), 0);
                        const float* ps = reinterpret_cast<const float*>(smem + OFF_XB) + lane;
                        const float go = (ps[0] + ps[64]) + (ps[128] + ps[192]), uo = (ps[32] + ps[96]) + (ps[160] + ps[224]);
                        const float h = rbf(silu_f(rbf(go))) * rbf(uo), ho = __shfl_xor_sync(0xffffffffu, h, 1);
                        asm volatile("st.async.weak.shared::cluster.mbarrier::complete_tx::bytes.b32 [%0], %1, [%2];"
                                     ::"r"(mapa(sb + OFF_H + c * 64 + (lane >> 1) * 4, lane & 1)), "r"((lane & 1) ? pack_bf(ho, h) : pack_bf(h, ho)),
                                       "r"(mapa(BAR(B_H), lane & 1)) : "memory");
                    }
                    mbar_wait_cluster(BAR(B_H), 0);
                    xn = *reinterpret_cast<const uint4*>(smem + OFF_H + (lane & 3) * 32 + (lane >> 4) * 16);
#pragma unroll
                    for (int i = 0; i < 8; i++) ag[i] = 0.f;
                    if (mt == 0) PROF_T(10);
                }
            }
            const int hi = lane >> 4;
            st_relaxed128(at(g_part, pair * 4096 + (c * 8 + aw * 2 + ((lane >> 3) & 1)) * 256 + hi * 128 + (lane & 7) * 16),
                          make_uint4((__float_as_uint(hi ? ag[4] : ag[0]) & ~15u) | (ep & 15u), __float_as_uint(hi ? ag[5] : ag[1]),
                                     __float_as_uint(hi ? ag[6] : ag[2]), __float_as_uint(hi ? ag[7] : ag[3])));
            if (mt == 0) PROF_T(11);
        } else {
            mbar_wait_sleep(BAR(B_SEL), 0);
        }
        const int sel = 0xffff - (int)(*reinterpret_cast<volatile unsigned*>(smem + OFF_SEL) & 0xffffu);
        if ((sel >> 8) == g) {
            const int col = (lane & 7) * 8 + ((lane >> 3) & 1) * 4;
            const uint2 xv = __ldg(reinterpret_cast<const uint2*>(at(P.x, (sel * D_ + grp * 64 + col) * 2)));
            uint4 f[1];
            GATHER(at(g_stat, SREC(sel) * 16), 1, f[i].z == ep);
            const uint4 rec = f[0];
            const uint4* src = at(g_part, (aw * 14 + (lane >> 4)) * 4096 + grp * 256 + (lane & 15) * 16);
            if (r == 7) {
                int n = 0;
                while (((ld_relaxed(src) ^ ep) & 15u) != 0 && ++n < SPIN_LIMIT) __nanosleep(500);
            }
            uint4 t[7];
            int n = 0;
            bool ok;
            do {
                ok = true;
#pragma unroll
                for (int u = 0; u < 7; u++) { t[u] = ld_relaxed128(src + u * 512); ok = ok && ((t[u].x ^ ep) & 15u) == 0; }
            } while (!__all_sync(0xffffffffu, ok) && ++n < SPIN_LIMIT);
            float4 a = make_float4(0.f, 0.f, 0.f, 0.f);
#pragma unroll
            for (int u = 0; u < 7; u++) {
                a.x += __uint_as_float(t[u].x & ~15u); a.y += __uint_as_float(t[u].y); a.z += __uint_as_float(t[u].z); a.w += __uint_as_float(t[u].w);
            }
            a.x += __shfl_xor_sync(0xffffffffu, a.x, 16); a.y += __shfl_xor_sync(0xffffffffu, a.y, 16);
            a.z += __shfl_xor_sync(0xffffffffu, a.z, 16); a.w += __shfl_xor_sync(0xffffffffu, a.w, 16);
            float4* park = reinterpret_cast<float4*>(smem + OFF_XB) + (lane & 15);
            if (lane < 16) park[aw * 16] = a;
            named_bar<4, 128>();
            if (aw == 0) {
                const float4 p1 = park[16], p2 = park[32], p3 = park[48];
                a.x = (a.x + p1.x) + (p2.x + p3.x); a.y = (a.y + p1.y) + (p2.y + p3.y);
                a.z = (a.z + p1.z) + (p2.z + p3.z); a.w = (a.w + p1.w) + (p2.w + p3.w);
                unsigned u = *reinterpret_cast<volatile unsigned*>(smem + OFF_SEL) >> 16;
                u = (u & 0x8000u) ? (u & 0x7fffu) : (~u & 0xffffu);
                const float sg = rbf(__fdividef(1.0f, 1.0f + __expf(-__uint_as_float(u << 16))));
                const float m = __uint_as_float(rec.x), ri = __uint_as_float(rec.y);
                const uint32_t n0 = norm2(xv.x, m, ri), n1 = norm2(xv.y, m, ri);
                uint2 o;
                o.x = silu2(pack_bf(bf_lo(n0) + rbf(rbf(a.x) * sg), bf_hi(n0) + rbf(rbf(a.y) * sg)));
                o.y = silu2(pack_bf(bf_lo(n1) + rbf(rbf(a.z) * sg), bf_hi(n1) + rbf(rbf(a.w) * sg)));
                if (lane < 16) *reinterpret_cast<uint2*>(smem + OFF_H + col * 2) = o;
                __syncwarp();
                if (lane == 0) { mbar_arrive(BAR(B_UPD)); PROF_T(12); }
            }
        }
    } else {
        asm volatile("setmaxnreg.inc.sync.aligned.u32 %0;" ::"n"(CONS_REGS));
        CLUSTER_WAIT();
        const int wg = warp >> 2, wq = warp & 3;
        const int wt = tid & 127;
        float acc[128];
        const uint32_t fL = BAR(B_FL + 4 * wg), eL = BAR(B_EL + 4 * wg);
        const uint32_t dL = desc_lo(SB0 + OFF_L, 16) + wg * 4096;
        constexpr uint32_t dS = desc_lo(SB0 + OFF_S, 16);
        constexpr uint32_t SL = SLOT >> 4;
#define RELEASE(ls, ss) do { if (wt == 0) { mbar_arrive(eL + 8u * (ls)); mbar_arrive(BAR(B_ES + (ss))); } } while (0)
#define WAIT_FULL(ls, lph, ss, sph) do { mbar_wait(BAR(B_FS + (ss)), sph); mbar_wait(fL + 8u * (ls), lph); } while (0)
#define TURN() do { if (wg) named_bar<6, 256>(); else named_bar<5, 256>(); } while (0)
#define PASS() do { if (wg) named_arrive<5, 256>(); else named_arrive<6, 256>(); } while (0)
#define WG_BAR() do { if (wg) named_bar<2, 128>(); else named_bar<1, 128>(); } while (0)
        if (wg == 1) PASS();

#define MMA1_P(O, s, first, pass) do { _Pragma("unroll") for (int kk = 0; kk < 4; kk++) { if (kk == PK && (pass)) PASS(); \
            wgmma128<O, 0>(acc, dL + (s) * SL + kk * 2 + (O) * 8, dS + DSLOT(s) * SL + kk * 2, !((first) && kk == 0)); } \
            if (PK == 4 && (pass)) PASS(); } while (0)
#define MMA1_H(O, s, first) MMA1_P(O, s, first, false)
#define WAIT1(s, ph) WAIT_FULL(s, ph, DSLOT(s), ph)
#define PROBE(ls, lph, ss, sph) (mbar_test(BAR(B_FS + (ss)), sph) & mbar_test(fL + 8u * (ls), lph))
#define REL1(s) RELEASE(s, DSLOT(s))
#pragma unroll 1
        for (int it = 0; it < 12; it++) {
            const int s = it & 3;
            const bool ok = PROBE(s, (it >> 2) & 1, DSLOT(s), (it >> 2) & 1);
            if (it) { wg_wait<0>(); REL1((it - 1) & 3); }
            if (!ok) WAIT1(s, (it >> 2) & 1);
            TURN();
            wg_fence(); MMA1_H(0, s, it == 0); MMA1_H(64, s, it == 0); wg_commit();
            PASS();
            if (it == QJ && tid == 0) { mbar_arrive(BAR(B_QUIET)); PROF_T(15); }
            if (it == 0 && tid == 0) PROF_T(16);
        }
        TS(12);
        float rs[4] = {};
        uint32_t nm[8] = {};
#define GET_STATS() do { mbar_wait(BAR(B_STATS), 0); \
            const int p0 = POS(wg * 128 + wq * 16 + (lane >> 2));                   \
            const uint32_t msk = (lane & 3) == 0 ? 0xffffffffu : (lane & 3) == 1 ? 0x0000ffffu : 0u; \
            _Pragma("unroll") for (int i = 0; i < 4; i++) { \
                const int p = p0 + (i & 1) * 2 + (i >> 1) * 64; \
                rs[i] = *reinterpret_cast<const float*>(smem + OFF_RSTD + p * 4); \
                const uint32_t m = *reinterpret_cast<const uint16_t*>(smem + OFF_MEAN + p * 2) ^ 0x8000u; \
                nm[i + (i & 2)] = (m | (m << 16)) & msk; \
            } } while (0)
        const bool early = wg || __all_sync(0xffffffffu, mbar_test(BAR(B_STATS), 0));
        if (early && !wg) GET_STATS();
        WAIT1(0, 1);
        TS(13);
        wg_wait<0>(); REL1(3);
        if (wg) GET_STATS();
        TS(14);
        TURN();
        wg_fence();
        MMA1_H(0, 0, false);
        if (QJ == 12 && tid == 0) { mbar_arrive(BAR(B_QUIET)); PROF_T(15); }
        WAIT1(1, 1); wg_fence(); MMA1_H(0, 1, false);
        WAIT1(2, 1); wg_fence(); MMA1_H(0, 2, false); wg_commit();
        if (!early) GET_STATS();
        asm volatile("" : "+r"(nm[0]), "+r"(nm[1]), "+r"(nm[2]), "+r"(nm[3]), "+r"(nm[4]), "+r"(nm[5]), "+r"(nm[6]), "+r"(nm[7])::"memory");
        wg_fence();
        wgmma128_rs<64>(acc, nm + 4, (SB0 + OFF_RS) >> 4);
        wgmma128_rs<0>(acc, nm, (SB0 + OFF_RS) >> 4);
        WAIT1(3, 1); wg_fence(); MMA1_P(0, 3, false, true);
        wg_commit();
        const int mrow = wq * 16 + ((lane >> 3) & 1) * 8 + (lane & 7);
#define EPI1(O, slot, FREE) do { const uint32_t dst = sb + OFF_S + (slot) * SLOT + mrow * 128; \
            uint32_t pk[32]; \
            _Pragma("unroll") for (int i = 0; i < 32; i += 4) { \
                _Pragma("unroll") for (int k = 0; k < 4; k++) \
                    pk[i + k] = pack_bf(acc[(O) + 2 * (i + k)] * rs[(O) / 32 + (k & 1)], acc[(O) + 2 * (i + k) + 1] * rs[(O) / 32 + (k & 1)]); \
                if (i == EF) { FREE; } \
                if (i >= EF) { _Pragma("unroll") for (int v = (i == EF ? 0 : i); v <= i; v += 4) \
                    stmatrix4(dst + ((v >> 4) ^ c ^ 1) * 8192 + ((((v >> 1) & 7) + (lane >> 4)) ^ (lane & 7)) * 16, pk[v], pk[v + 1], pk[v + 2], pk[v + 3]); } } \
            if (!RF) fence_async_smem(); \
            WG_BAR(); \
            if (wt == 0) mbar_arrive(BAR(B_FS + (slot))); } while (0)
        TS(15);
        wg_wait<0>();
        fence_regs64<0>(acc);
        TS(16);
        {
            constexpr int EF = 0;
            EPI1(0, wg, if (wg) mbar_wait(BAR(B_FS), 0));
        }
        TS(17);
        TURN();
        wg_fence();
        MMA1_H(64, 0, false); wg_commit();
        MMA1_H(64, 1, false); wg_commit();
        MMA1_H(64, 2, false); wg_commit();
        wg_wait<2>(); REL1(0);
        MMA1_P(64, 3, false, true); wg_commit();
        TS(18);
        wg_wait<2>(); REL1(1);
        if (RF) { mbar_wait(BAR(B_FS), 0); mbar_wait(BAR(B_FS + 1), 0); fence_async_smem(); }
        wg_wait<1>(); REL1(2);
        wg_wait<0>(); REL1(3);
        fence_regs64<64>(acc);
        TS(19);
        {
            constexpr int EF = EF2;
            EPI1(64, 2 + wg, mbar_wait(BAR(B_ES + 2 + wg), 1));
        }
        TS(20);

        float ac2[128];
#define MMA2_P(O, ls, ss, first, pass) do { _Pragma("unroll") for (int kk = 0; kk < 4; kk++) { if (kk == PK && (pass)) PASS(); \
            wgmma128<O, 1>(ac2, dS + (ss) * SL + kk * 128 + (O) * 8, dL + (ls) * SL + kk * 2, !((first) && kk == 0)); } \
            if (PK == 4 && (pass)) PASS(); } while (0)
#define MMA2_H(O, ls, ss, first) MMA2_P(O, ls, ss, first, false)
#define WAIT2(j) WAIT_FULL((j) & 3, ((j) >> 2) & 1, PSLOT(j), PPAR(j))
#define MMA2(j, pass) do { wg_fence(); MMA2_H(0, (j) & 3, PSLOT(j), (j) == 0); MMA2_P(64, (j) & 3, PSLOT(j), (j) == 0, pass); wg_commit(); } while (0)
#define REL2(j) RELEASE((j) & 3, PSLOT(j))
        if (GOJ == 0 && wt == 0) mbar_arrive(BAR(B_GO));
        WAIT2(0); TURN(); MMA2(0, false);
        WAIT2(1); MMA2(1, true);
        if (GOJ == 1 && wt == 0) mbar_arrive(BAR(B_GO));
        TS(21);
        wg_wait<1>(); REL2(0);
        if (RF) { mbar_wait(BAR(B_FS + 2), 0); mbar_wait(BAR(B_FS + 3), 0); fence_async_smem(); }
        TS(22);
        {
            uint32_t sp = 1;
#pragma unroll 1
            for (int j = 2; j < XJ; j++) {
                const uint32_t ss = PSLOT(j);
                const bool ok = PROBE(j & 3, (j >> 2) & 1, ss, PPAR(j));
                wg_wait<0>(); RELEASE((j - 1) & 3, sp);
                if (!ok) WAIT_FULL(j & 3, (j >> 2) & 1, ss, PPAR(j));
                TURN();
                wg_fence(); MMA2_H(0, j & 3, ss, false); MMA2_P(64, j & 3, ss, false, true); wg_commit();
                if (j == GOJ && wt == 0) { mbar_arrive(BAR(B_GO)); if (wg == 0) PROF_T(19); }
                sp = ss;
            }
        }
        if (tid == 0) PROF_T(20);
        uint32_t gt[32];
        const uint32_t xrow = sb + OFF_S + 2 * SLOT + wg * 8192 + ((lane >> 4) * 8 + (lane & 7)) * 128 + (((2 * wq + ((lane >> 3) & 1)) ^ (lane & 7)) << 4);
        const uint32_t gsign = c ? 0x80008000u : 0u;
#define XOFF(v) (((v) >> 2) * SLOT + ((v) & 3) * 2048)
        mbar_wait(BAR(B_SEL), 0);
        const int sel = 0xffff - (int)(*reinterpret_cast<volatile unsigned*>(smem + OFF_SEL) & 0xffffu);
        bool own = (sel >> 7) == 2 * g + wg;
#define PATCH() do { own = false; \
            const uint32_t v0 = *reinterpret_cast<const uint16_t*>(smem + OFF_H + (wq * 16 + (lane >> 2)) * 2) ^ gsign; \
            const uint32_t v1 = *reinterpret_cast<const uint16_t*>(smem + OFF_H + (wq * 16 + (lane >> 2)) * 2 + 16) ^ gsign; \
            const uint32_t pick = (lane & 3) != ((sel >> 1) & 3) ? 0x3210u : (sel & 1) ? 0x5410u : 0x3254u; \
            _Pragma("unroll") for (int i = 0; i < 16; i++) { \
                const uint32_t m = ((sel >> 3) & 15) == i ? pick : 0x3210u; \
                gt[2 * i] = __byte_perm(gt[2 * i], v0, m); \
                gt[2 * i + 1] = __byte_perm(gt[2 * i + 1], v1, m); \
            } } while (0)
#pragma unroll
        for (int v = 0; v < 28 - XJ; v++) {
            WAIT2(XJ + v); wg_wait<0>(); REL2(XJ + v - 1); TURN(); MMA2(XJ + v, true);
            constexpr int NS = 8 / (28 - XJ);
#pragma unroll
            for (int u = v * NS; u < (v + 1) * NS; u++) {
                uint32_t* o = &gt[4 * u];
                if (!(u & 3)) mbar_wait(BAR(B_FS + 2 + (u >> 2)), 1);
                ldmatrix4t(xrow + XOFF(u), o[0], o[1], o[2], o[3]);
                const float4 r4 = *reinterpret_cast<const float4*>(smem + OFF_RSTD + (wg * 128 + u * 16 + (lane & 3) * 4) * 4);
                const uint2 m2 = *reinterpret_cast<const uint2*>(smem + OFF_MEAN + (wg * 128 + u * 16 + (lane & 3) * 4) * 2);
                o[0] = gate2(o[0], m2.x, r4.x, r4.y) ^ gsign;
                o[1] = gate2(o[1], m2.x, r4.x, r4.y) ^ gsign;
                o[2] = gate2(o[2], m2.y, r4.z, r4.w) ^ gsign;
                o[3] = gate2(o[3], m2.y, r4.z, r4.w) ^ gsign;
                asm volatile("st.shared.v2.u32 [%0], {%1,%2};" ::"r"(sb + OFF_SEL + 16), "r"(o[0] ^ o[1]), "r"(o[2] ^ o[3]) : "memory");
            }
        }
        if (tid == 0) PROF_T(21);
        WAIT2(28);
        wg_wait<0>(); REL2(27);
        if (own) {
            const uint32_t t0 = clock32();
            bool ok;
            while (!(ok = mbar_test(BAR(B_UPD), 0)) && clock32() - t0 < wg * 1400u) __nanosleep(50);
            if (__all_sync(0xffffffffu, ok)) PATCH();
        }
        TS(0);
        TURN();
        wg_fence(); MMA2_H(0, 0, PSLOT(28), false); wg_commit();
        if (wg == 0 || !ASYM) { wg_fence(); MMA2_H(64, 0, PSLOT(28), false); wg_commit(); }
        WAIT2(29); wg_fence(); MMA2_H(0, 1, PSLOT(29), false); wg_commit();
        WAIT2(30); wg_fence(); MMA2_H(0, 2, PSLOT(30), false); wg_commit();
        wg_wait<2>();
        if (tid == 0) mbar_arrive_cluster(mapa(BAR(B_RDY), c ^ 1));
        WAIT2(31); wg_fence(); MMA2_H(0, 3, PSLOT(31), false); wg_commit();
        TS(1);
#define KEEP(i) wgmma128<64, 1>(ac2, dS + PSLOT(29 + ((i) >> 2)) * SL + ((i) & 3) * 128 + 512, dL + (1 + ((i) >> 2)) * SL + ((i) & 3) * 2, 1)
        wg_fence();
#pragma unroll
        for (int i = 0; i < KQ; i++) KEEP(i);
        wg_commit();
        mbar_wait(BAR(B_RDY + wg), 0);
        wg_wait<1>();
        fence_regs64<0>(ac2);
        TS(2);
        wg_fence();
        {
            const uint32_t dst = mapa(sb + OFF_L + wg * SLOT + wt * 16, c ^ 1), rb = mapa(BAR(B_RECV + 2 * wg), c ^ 1);
#pragma unroll
            for (int v = 0; v < 8; v++) {
                if (KQ + v < 12) KEEP(KQ + v);
                if (KQ + v == 11) { wg_commit(); if (wg == 0) PASS(); }
                st_async4(dst + v * 2048, pack_bf(ac2[8 * v + 0], ac2[8 * v + 1]), pack_bf(ac2[8 * v + 2], ac2[8 * v + 3]),
                          pack_bf(ac2[8 * v + 4], ac2[8 * v + 5]), pack_bf(ac2[8 * v + 6], ac2[8 * v + 7]), rb + (v >> 2) * 8);
            }
        }
        if (wg == 1 && ASYM) { wg_fence(); MMA2_H(64, 0, PSLOT(28), false); wg_commit(); }
        TS(3);
        uint32_t xr[32];
#define LDX(v) ldmatrix4t(xrow + XOFF(v), xr[4 * (v)], xr[4 * (v) + 1], xr[4 * (v) + 2], xr[4 * (v) + 3])
#pragma unroll
        for (int v = 0; v < XE; v++) LDX(v);
        if (wg == 0) {
            wg_wait<0>();
            if (wt == 0) mbar_arrive_cluster(mapa(BAR(B_RDY + 1), c ^ 1));
        }
        TS(4);
        if (own) { mbar_wait(BAR(B_UPD), 0); PATCH(); }
        TS(5);
        uint4 rv[8];
#define FETCH(v0) do { if ((v0) == 0 || (v0) == 4) mbar_wait_cluster(BAR(B_RECV + 2 * wg + (v0) / 4), 0); \
            _Pragma("unroll") for (int v = (v0); v < (v0) + OP; v++) { \
                asm volatile("ld.shared.v4.u32 {%0,%1,%2,%3}, [%4];" : "=r"(rv[v].x), "=r"(rv[v].y), "=r"(rv[v].z), "=r"(rv[v].w) \
                             : "r"(sb + OFF_L + wg * SLOT + v * 2048 + wt * 16) : "memory"); \
                if (v >= XE) LDX(v); } } while (0)
        FETCH(0);
        TS(6);
        wg_wait<0>();
        fence_regs64<64>(ac2);
        TS(7);
#pragma unroll
        for (int v0 = 0; v0 < 8; v0 += OP) {
#pragma unroll
            for (int v = v0; v < v0 + OP; v++) {
                const float* a = &ac2[64 + 8 * v];
                stmatrix4t(xrow + XOFF(v),
                           bfma2(bsub2(pack_bf(a[0], a[1]), rv[v].x), gt[4 * v + 0], xr[4 * v + 0]),
                           bfma2(bsub2(pack_bf(a[2], a[3]), rv[v].y), gt[4 * v + 1], xr[4 * v + 1]),
                           bfma2(bsub2(pack_bf(a[4], a[5]), rv[v].z), gt[4 * v + 2], xr[4 * v + 2]),
                           bfma2(bsub2(pack_bf(a[6], a[7]), rv[v].w), gt[4 * v + 3], xr[4 * v + 3]));
            }
            WG_BAR();
            if (wt == 0) mbar_arrive(eL + 8 * (v0 / OP));
            if (v0 + OP < 8) FETCH(v0 + OP);
            if (v0 == 0) TS(8);
        }
        TS(9);
    }
}

typedef CUresult (*EncodeFn)(CUtensorMap*, CUtensorMapDataType, cuuint32_t, void*, const cuuint64_t*, const cuuint64_t*,
                             const cuuint32_t*, const cuuint32_t*, CUtensorMapInterleave, CUtensorMapSwizzle,
                             CUtensorMapL2promotion, CUtensorMapFloatOOBfill);

void make_map(EncodeFn fn, CUtensorMap* tm, const void* p, uint64_t rows, uint64_t cols, uint32_t box_rows,
              CUtensorMapL2promotion promo = CU_TENSOR_MAP_L2_PROMOTION_L2_128B) {
    cuuint64_t dims[2] = {cols, rows};
    cuuint64_t strides[1] = {cols * 2};
    cuuint32_t box[2] = {64, box_rows};
    cuuint32_t es[2] = {1, 1};
    fn(tm, CU_TENSOR_MAP_DATA_TYPE_BFLOAT16, 2, const_cast<void*>(p), dims, strides, box, es, CU_TENSOR_MAP_INTERLEAVE_NONE,
       CU_TENSOR_MAP_SWIZZLE_128B, promo, CU_TENSOR_MAP_FLOAT_OOB_FILL_NONE);
}

}

extern "C" void kernel_launch(void* const* d_in, const int* in_sizes, int n_in, void* d_out, int out_size) {
    (void)in_sizes; (void)n_in; (void)out_size;
    static EncodeFn fn = nullptr;
    if (!fn) {
        void* p = nullptr;
        cudaDriverEntryPointQueryResult q;
        cudaGetDriverEntryPoint("cuTensorMapEncodeTiled", &p, cudaEnableDefault, &q);
        fn = (EncodeFn)p;
        cudaFuncSetAttribute(fnet_fused_kernel, cudaFuncAttributeMaxDynamicSharedMemorySize, SMEM_BYTES);
    }
    CUtensorMap tx, tdre, tdim, tcre, tcim, tout, tx64;
    make_map(fn, &tx, d_in[0], S_, D_, 128, PRX);
    make_map(fn, &tcre, d_in[1], S_, S_, 128, PRC);
    make_map(fn, &tcim, d_in[2], S_, S_, 128, PRC);
    make_map(fn, &tdre, d_in[3], D_, D_, 128, PRD);
    make_map(fn, &tdim, d_in[4], D_, D_, 128, PRD);
    make_map(fn, &tx64, d_in[0], S_, D_, 64, PRX);
    make_map(fn, &tout, d_out, S_, D_, 16 * OP);
    Params P;
    P.x = (const __nv_bfloat16*)d_in[0];
    P.dre = (const __nv_bfloat16*)d_in[3];
    P.dim = (const __nv_bfloat16*)d_in[4];
    P.wr = (const __nv_bfloat16*)d_in[6];
    P.wg = (const __nv_bfloat16*)d_in[7];
    P.wu = (const __nv_bfloat16*)d_in[8];
    P.wd = (const __nv_bfloat16*)d_in[9];
    P.zero = 0;
    fnet_fused_kernel<<<NCTA, NTHREADS, SMEM_BYTES, cudaStreamPerThread>>>(tx, tdre, tdim, tcre, tcim, tout, tx64, P);
}
```

```cpp
#include <cuda_runtime.h>
#include <cuda_bf16.h>
#include <cuda.h>
#include <stdint.h>

#define XS 0x5432
#define GSL 200
#define SLEEP_NS 200
#define PDEL 1000
#define PGAP1 200
#define PGAP2 200
#define PGAP3 240
#define GOJ 2
#define KQ 5
#define XE 2
#define PROD_REGS 32
#define CONS_REGS 184

namespace {

constexpr int S_ = 2048, D_ = 1024, F_ = 3584;
constexpr int NCTA = 128;
constexpr int XJ = 20;
constexpr uint32_t SLOT = 16384;
constexpr uint32_t OFF_L = 0;
constexpr uint32_t OFF_S = 8 * SLOT;
constexpr uint32_t OFF_RS = OFF_S + SLOT;
constexpr uint32_t OFF_BAR = 14 * SLOT;
constexpr uint32_t OFF_SEL = OFF_BAR + 360;
constexpr uint32_t OFF_RSTD = OFF_BAR + 384;
constexpr uint32_t OFF_MEAN = OFF_RSTD + 1024;
constexpr uint32_t OFF_XB = OFF_MEAN + 512;
constexpr uint32_t OFF_H = OFF_XB + 1024;
constexpr uint32_t SMEM_BYTES = OFF_H + 128;
constexpr uint32_t SB0 = 1024;
constexpr int NTHREADS = 512;
static_assert(SMEM_BYTES <= 232448, "smem");

enum { B_FS = 0, B_ES = 6, B_FL = 12, B_EL = 20, B_SRD = 28, B_RECV = 30  , B_RDY = 34, B_STATS = 36, B_LST = 37, B_UPD = 38,
       B_QUIET = 39, B_GO = 40, B_PEER = 41, B_SEL = 42, B_H = 43, B_COUNT = 44 };
static_assert(B_COUNT * 8 <= 360, "barriers");

__device__ __align__(1024) uint8_t g_ab[16u * 32u * SLOT];
__device__ __align__(128) uint4 g_part[56 * (D_ / 4)];
__device__ __align__(128) uint4 g_stat[S_];
__device__ __align__(128) uint4 g_rs[D_];
__device__ __align__(128) unsigned long long g_key[NCTA];
__device__ __align__(128) unsigned long long g_flag[16 * 16];
__device__ __align__(128) unsigned g_epoch[NCTA];
#define PROF_T(i) do {} while (0)
#define TRACE(i) do {} while (0)
#define PROF_G(i) do {} while (0)
#define TS(i) do {} while (0)
#define FINISH(wg) bulk_wait_read<0>()

#define MARK(it) do {} while (0)

__device__ __forceinline__ uint32_t smem_u32(const void* p) { return (uint32_t)__cvta_generic_to_shared(p); }
__device__ __forceinline__ void mbar_init(uint32_t bar, uint32_t cnt) {
    asm volatile("mbarrier.init.shared::cta.b64 [%0], %1;" ::"r"(bar), "r"(cnt) : "memory");
}
__device__ __forceinline__ bool mbar_try(uint32_t bar, uint32_t parity) {
    uint32_t ok;
    asm volatile("{\n.reg .pred p;\nmbarrier.try_wait.parity.shared::cta.b64 p, [%1], %2;\nselp.u32 %0, 1, 0, p;\n}"
                 : "=r"(ok) : "r"(bar), "r"(parity) : "memory");
    return ok;
}
__device__ __forceinline__ bool mbar_test(uint32_t bar, uint32_t parity) {
    uint32_t ok;
    asm volatile("{\n.reg .pred p;\nmbarrier.test_wait.parity.shared::cta.b64 p, [%1], %2;\nselp.u32 %0, 1, 0, p;\n}"
                 : "=r"(ok) : "r"(bar), "r"(parity) : "memory");
    return ok;
}
__device__ __forceinline__ bool mbar_try_cluster(uint32_t bar, uint32_t parity) {
    uint32_t ok;
    asm volatile("{\n.reg .pred p;\nmbarrier.try_wait.parity.acquire.cluster.shared::cta.b64 p, [%1], %2;\nselp.u32 %0, 1, 0, p;\n}"
                 : "=r"(ok) : "r"(bar), "r"(parity) : "memory");
    return ok;
}
constexpr int SPIN_LIMIT = 1 << 20;
__device__ __forceinline__ void mbar_wait(uint32_t bar, uint32_t parity) {
    if (mbar_try(bar, parity)) return;
    int n = 0;
    while (!mbar_try(bar, parity) && ++n < SPIN_LIMIT) {}
}
__device__ __forceinline__ void mbar_wait_cluster(uint32_t bar, uint32_t parity) {
    int n = 0;
    while (!mbar_try_cluster(bar, parity) && ++n < SPIN_LIMIT) {}
}
__device__ __forceinline__ void mbar_wait_sleep(uint32_t bar, uint32_t parity) {
    int n = 0;
    while (!mbar_try(bar, parity) && ++n < SPIN_LIMIT) __nanosleep(SLEEP_NS);
}
__device__ __forceinline__ void mbar_arrive(uint32_t bar) {
    asm volatile("mbarrier.arrive.shared::cta.b64 _, [%0];" ::"r"(bar) : "memory");
}
__device__ __forceinline__ void mbar_arrive_cluster(uint32_t cluster_bar) {
    asm volatile("mbarrier.arrive.shared::cluster.b64 _, [%0];" ::"r"(cluster_bar) : "memory");
}
__device__ __forceinline__ void mbar_expect_tx(uint32_t bar, uint32_t bytes) {
    asm volatile("mbarrier.arrive.expect_tx.shared::cta.b64 _, [%0], %1;" ::"r"(bar), "r"(bytes) : "memory");
}
__device__ __forceinline__ bool elect_one() {
    uint32_t p;
    asm volatile("{\n.reg .pred p;\nelect.sync _|p, 0xffffffff;\nselp.u32 %0, 1, 0, p;\n}" : "=r"(p));
    return p;
}
__device__ __forceinline__ uint32_t mapa(uint32_t addr, uint32_t rank) {
    uint32_t r;
    asm("mapa.shared::cluster.u32 %0, %1, %2;" : "=r"(r) : "r"(addr), "r"(rank));
    return r;
}
__device__ __forceinline__ uint32_t clock32() { uint32_t t; asm volatile("mov.u32 %0, %%clock;" : "=r"(t)); return t; }
__device__ __forceinline__ void sleep_until(uint32_t t) {
    int n = 0;
    while ((int)(clock32() - t) < 0 && ++n < SPIN_LIMIT) __nanosleep(20);
}
__device__ __forceinline__ void yield(float last, uint32_t zero) {
    asm volatile("nanosleep.u32 %0;" ::"r"(__float_as_uint(last) & zero));
}
template <typename T> __device__ __forceinline__ T* at(T* p, uint32_t bytes) {
    asm("" : "+r"(bytes));
    return reinterpret_cast<T*>(reinterpret_cast<uintptr_t>(p) + bytes);
}
__device__ __forceinline__ void tma_2d(uint32_t dst, const CUtensorMap* tm, int c0, int c1, uint32_t bar) {
    asm volatile("cp.async.bulk.tensor.2d.shared::cluster.global.mbarrier::complete_tx::bytes [%0], [%1, {%3, %4}], [%2];"
                 ::"r"(dst), "l"(tm), "r"(bar), "r"(c0), "r"(c1) : "memory");
}
__device__ __forceinline__ void tma_2d_store(const CUtensorMap* tm, int c0, int c1, uint32_t src) {
    asm volatile("cp.async.bulk.tensor.2d.global.shared::cta.bulk_group [%0, {%2, %3}], [%1];"
                 ::"l"(tm), "r"(src), "r"(c0), "r"(c1) : "memory");
}
__device__ __forceinline__ void bulk_g2s(uint32_t dst, const void* src, uint32_t bytes, uint32_t bar) {
    asm volatile("cp.async.bulk.shared::cluster.global.mbarrier::complete_tx::bytes [%0], [%1], %2, [%3];"
                 ::"r"(dst), "l"(src), "r"(bytes), "r"(bar) : "memory");
}
__device__ __forceinline__ void bulk_s2g(void* dst, uint32_t src, uint32_t bytes) {
    asm volatile("cp.async.bulk.global.shared::cta.bulk_group [%0], [%1], %2;" ::"l"(dst), "r"(src), "r"(bytes) : "memory");
}
__device__ __forceinline__ void st_async4(uint32_t dst, uint32_t a, uint32_t b, uint32_t c, uint32_t d, uint32_t bar) {
    asm volatile("st.async.weak.shared::cluster.mbarrier::complete_tx::bytes.v4.b32 [%0], {%1,%2,%3,%4}, [%5];"
                 ::"r"(dst), "r"(a), "r"(b), "r"(c), "r"(d), "r"(bar) : "memory");
}
__device__ __forceinline__ void bulk_commit() { asm volatile("cp.async.bulk.commit_group;" ::: "memory"); }
template <int N> __device__ __forceinline__ void bulk_wait_read() { asm volatile("cp.async.bulk.wait_group.read %0;" ::"n"(N) : "memory"); }
template <int N> __device__ __forceinline__ void bulk_wait() { asm volatile("cp.async.bulk.wait_group %0;" ::"n"(N) : "memory"); }
__device__ __forceinline__ void fence_async_smem() { asm volatile("fence.proxy.async.shared::cta;" ::: "memory"); }
__device__ __forceinline__ void fence_async_global() { asm volatile("fence.proxy.async.global;" ::: "memory"); }
__device__ __forceinline__ void prefetch_tmap(const CUtensorMap* tm) {
    asm volatile("prefetch.tensormap [%0];" ::"l"(tm) : "memory");
}
__device__ __forceinline__ unsigned long long ld_acquire64(const unsigned long long* p) {
    unsigned long long v; asm volatile("ld.acquire.gpu.global.u64 %0, [%1];" : "=l"(v) : "l"(p) : "memory"); return v;
}
__device__ __forceinline__ unsigned load_epoch(int b) {
    unsigned v; asm volatile("ld.global.u32 %0, [%1];" : "=r"(v) : "l"(at(g_epoch, b * 4)) : "memory"); return v + 1;
}
__device__ __forceinline__ unsigned ld_relaxed(const void* p) {
    unsigned v; asm volatile("ld.relaxed.gpu.global.u32 %0, [%1];" : "=r"(v) : "l"(p) : "memory"); return v;
}
__device__ __forceinline__ uint4 ld_relaxed128(const uint4* p) {
    uint4 v;
    asm volatile("{\n.reg .b128 t;\n.reg .b64 lo, hi;\nld.relaxed.gpu.global.b128 t, [%4];\nmov.b128 {lo, hi}, t;\n"
                 "mov.b64 {%0, %1}, lo;\nmov.b64 {%2, %3}, hi;\n}"
                 : "=r"(v.x), "=r"(v.y), "=r"(v.z), "=r"(v.w) : "l"(p) : "memory");
    return v;
}
__device__ __forceinline__ void st_relaxed128(uint4* p, const uint4& v) {
    asm volatile("{\n.reg .b128 t;\n.reg .b64 lo, hi;\nmov.b64 lo, {%1, %2};\nmov.b64 hi, {%3, %4};\nmov.b128 t, {lo, hi};\n"
                 "st.relaxed.gpu.global.b128 [%0], t;\n}"
                 ::"l"(p), "r"(v.x), "r"(v.y), "r"(v.z), "r"(v.w) : "memory");
}
__device__ __forceinline__ void st_relaxed64(unsigned long long* p, unsigned long long v) {
    asm volatile("st.relaxed.gpu.global.u64 [%0], %1;" ::"l"(p), "l"(v) : "memory");
}
__device__ __forceinline__ void st_release8(void* p, unsigned v) {
    asm volatile("st.release.gpu.global.u8 [%0], %1;" ::"l"(p), "r"(v) : "memory");
}
__device__ __forceinline__ uint64_t policy_evict_first() {
    uint64_t pol;
    asm("createpolicy.fractional.L2::evict_first.b64 %0, 1.0;" : "=l"(pol));
    return pol;
}
__device__ __forceinline__ uint4 ldg_stream(const void* p, uint64_t pol) {
    uint4 v;
    asm volatile("ld.global.nc.L1::no_allocate.L2::cache_hint.v4.u32 {%0,%1,%2,%3}, [%4], %5;"
                 : "=r"(v.x), "=r"(v.y), "=r"(v.z), "=r"(v.w) : "l"(p), "l"(pol));
    return v;
}
template <int ID, int N> __device__ __forceinline__ void named_arrive() { asm volatile("bar.arrive %0, %1;" ::"n"(ID), "n"(N) : "memory"); }
template <int ID, int N> __device__ __forceinline__ void named_bar() { asm volatile("bar.sync %0, %1;" ::"n"(ID), "n"(N) : "memory"); }

__device__ __forceinline__ float bf_lo(uint32_t u) { return __uint_as_float(u << 16); }
__device__ __forceinline__ float bf_hi(uint32_t u) { return __uint_as_float(u & 0xffff0000u); }
__device__ __forceinline__ uint32_t pack_bf(float lo, float hi) {
    uint32_t r; asm("cvt.rn.bf16x2.f32 %0, %1, %2;" : "=r"(r) : "f"(hi), "f"(lo)); return r;
}
__device__ __forceinline__ float rbf(float v) { return __uint_as_float(pack_bf(0.f, v)); }
__device__ __forceinline__ float sqrt_f(float v) { float r; asm("sqrt.approx.f32 %0, %1;" : "=f"(r) : "f"(v)); return r; }
__device__ __forceinline__ float rcp_f(float v) { float r; asm("rcp.approx.f32 %0, %1;" : "=f"(r) : "f"(v)); return r; }
__device__ __forceinline__ float silu_f(float z) { return __fdividef(z, 1.0f + __expf(-z)); }
__device__ __forceinline__ uint32_t bsub2(uint32_t a, uint32_t b) {
    uint32_t r; asm("sub.rn.bf16x2 %0, %1, %2;" : "=r"(r) : "r"(a), "r"(b)); return r;
}
__device__ __forceinline__ uint32_t bfma2(uint32_t a, uint32_t b, uint32_t c) {
    uint32_t r; asm("fma.rn.bf16x2 %0, %1, %2, %3;" : "=r"(r) : "r"(a), "r"(b), "r"(c)); return r;
}
__device__ __forceinline__ uint32_t norm2(uint32_t xv, float m, float rinv) {
    uint32_t t = pack_bf(bf_lo(xv) - m, bf_hi(xv) - m);
    return pack_bf(bf_lo(t) * rinv, bf_hi(t) * rinv);
}
__device__ __forceinline__ float gate1(float z) {
    float t;
    const float h = 0.5f * z;
    asm("tanh.approx.f32 %0, %1;" : "=f"(t) : "f"(h));
    return fmaf(h, t, h);
}
__device__ __forceinline__ uint32_t gate2(uint32_t xv, uint32_t mean2, float r0, float r1) {
    const uint32_t t = bsub2(xv, mean2);
    return pack_bf(gate1(bf_lo(t) * r0), gate1(bf_hi(t) * r1));
}
__device__ __forceinline__ uint32_t silu2(uint32_t z) { return pack_bf(silu_f(bf_lo(z)), silu_f(bf_hi(z))); }

__device__ __forceinline__ void stmatrix4(uint32_t addr, uint32_t r0, uint32_t r1, uint32_t r2, uint32_t r3) {
    asm volatile("stmatrix.sync.aligned.m8n8.x4.shared.b16 [%0], {%1,%2,%3,%4};"
                 ::"r"(addr), "r"(r0), "r"(r1), "r"(r2), "r"(r3));
}
__device__ __forceinline__ void stmatrix4t(uint32_t addr, uint32_t r0, uint32_t r1, uint32_t r2, uint32_t r3) {
    asm volatile("stmatrix.sync.aligned.m8n8.x4.trans.shared.b16 [%0], {%1,%2,%3,%4};"
                 ::"r"(addr), "r"(r0), "r"(r1), "r"(r2), "r"(r3));
}
__device__ __forceinline__ void ldmatrix4t(uint32_t addr, uint32_t& r0, uint32_t& r1, uint32_t& r2, uint32_t& r3) {
    asm volatile("ldmatrix.sync.aligned.m8n8.x4.trans.shared.b16 {%0,%1,%2,%3}, [%4];"
                 : "=r"(r0), "=r"(r1), "=r"(r2), "=r"(r3) : "r"(addr));
}

__device__ __forceinline__ void wg_fence() { asm volatile("wgmma.fence.sync.aligned;" ::: "memory"); }
__device__ __forceinline__ void wg_commit() { asm volatile("wgmma.commit_group.sync.aligned;" ::: "memory"); }
template <int N> __device__ __forceinline__ void wg_wait() { asm volatile("wgmma.wait_group.sync.aligned %0;" ::"n"(N) : "memory"); }

__host__ __device__ constexpr uint32_t desc_lo(uint32_t addr, uint32_t lbo) { return ((addr & 0x3FFFF) >> 4) | ((lbo >> 4) << 16); }
#define DESC_HI "0x40000040"

#define R8(a, o) "+f"(a[(o) + 0]), "+f"(a[(o) + 1]), "+f"(a[(o) + 2]), "+f"(a[(o) + 3]), \
                 "+f"(a[(o) + 4]), "+f"(a[(o) + 5]), "+f"(a[(o) + 6]), "+f"(a[(o) + 7])
#define R64(a, o) R8(a, (o) + 0), R8(a, (o) + 8), R8(a, (o) + 16), R8(a, (o) + 24), \
                  R8(a, (o) + 32), R8(a, (o) + 40), R8(a, (o) + 48), R8(a, (o) + 56)

template <int O, int TA>
__device__ __forceinline__ void wgmma128(float (&a)[128], uint32_t da, uint32_t db, int scale_d) {
    asm volatile(
        "{\n.reg .pred p;\n.reg .b64 da, db;\nsetp.ne.b32 p, %66, 0;\n"
        "mov.b64 da, {%64, " DESC_HI "};\nmov.b64 db, {%65, " DESC_HI "};\n"
        "wgmma.mma_async.sync.aligned.m64n128k16.f32.bf16.bf16 "
        "{%0,%1,%2,%3,%4,%5,%6,%7,%8,%9,%10,%11,%12,%13,%14,%15,"
        "%16,%17,%18,%19,%20,%21,%22,%23,%24,%25,%26,%27,%28,%29,%30,%31,"
        "%32,%33,%34,%35,%36,%37,%38,%39,%40,%41,%42,%43,%44,%45,%46,%47,"
        "%48,%49,%50,%51,%52,%53,%54,%55,%56,%57,%58,%59,%60,%61,%62,%63},"
        "da, db, p, 1, 1, %67, 0;\n}"
        : R64(a, O)
        : "r"(da), "r"(db), "r"(scale_d), "n"(TA));
}
template <int O>
__device__ __forceinline__ void wgmma128_rs(float (&a)[128], const uint32_t* f, uint32_t db) {
    asm volatile(
        "{\n.reg .b64 db;\nmov.b64 db, {%68, 8};\n"
        "wgmma.mma_async.sync.aligned.m64n128k16.f32.bf16.bf16 "
        "{%0,%1,%2,%3,%4,%5,%6,%7,%8,%9,%10,%11,%12,%13,%14,%15,"
        "%16,%17,%18,%19,%20,%21,%22,%23,%24,%25,%26,%27,%28,%29,%30,%31,"
        "%32,%33,%34,%35,%36,%37,%38,%39,%40,%41,%42,%43,%44,%45,%46,%47,"
        "%48,%49,%50,%51,%52,%53,%54,%55,%56,%57,%58,%59,%60,%61,%62,%63},"
        "{%64, %65, %66, %67}, db, 1, 1, 1, 0;\n}"
        : R64(a, O)
        : "r"(f[0]), "r"(f[1]), "r"(f[2]), "r"(f[3]), "r"(db));
}
template <int O>
__device__ __forceinline__ void fence_regs64(float (&a)[128]) {
    asm volatile("" : R64(a, O)::"memory");
}

struct Params {
    const __nv_bfloat16* x;
    const __nv_bfloat16* dre;
    const __nv_bfloat16* dim;
    const __nv_bfloat16* wr;
    const __nv_bfloat16* wg;
    const __nv_bfloat16* wu;
    const __nv_bfloat16* wd;
    uint32_t zero;
#define AB g_ab
};

__device__ __forceinline__ float warp_sum(float v) {
#pragma unroll
    for (int o = 16; o; o >>= 1) v += __shfl_xor_sync(0xffffffffu, v, o);
    return v;
}
__device__ __forceinline__ void fma8(float* acc, const uint4& w, float s) {
    acc[0] += s * bf_lo(w.x); acc[1] += s * bf_hi(w.x); acc[2] += s * bf_lo(w.y); acc[3] += s * bf_hi(w.y);
    acc[4] += s * bf_lo(w.z); acc[5] += s * bf_hi(w.z); acc[6] += s * bf_lo(w.w); acc[7] += s * bf_hi(w.w);
}
__device__ __forceinline__ int POS(int t) { return (t & ~15) | ((t & 6) << 1) | ((t & 8) >> 2) | (t & 1); }
__host__ __device__ constexpr int PSLOT(int j) { return j < 4 ? j : (j & 1) + ((j & 2) ? 0 : 4); }
__host__ __device__ constexpr int PPAR(int j) { return j < 4 ? 0 : ((j >> 2) ^ (j >> 1) ^ 1) & 1; }
__host__ __device__ constexpr int DSLOT(int it) { return (it & 3) + 2; }
__device__ __forceinline__ int SREC(int t) { return (t & ~15) | ((t & 3) << 2) | ((t >> 2) & 3); }
__device__ __forceinline__ int KO(int cl) { return ((cl & 1) << 1) | (cl >> 1); }

__global__ void __cluster_dims__(2, 1, 1) __launch_bounds__(NTHREADS, 1)
fnet_fused_kernel(const __grid_constant__ CUtensorMap tm_x, const __grid_constant__ CUtensorMap tm_dre,
                  const __grid_constant__ CUtensorMap tm_dim, const __grid_constant__ CUtensorMap tm_cre,
                  const __grid_constant__ CUtensorMap tm_cim, const __grid_constant__ CUtensorMap tm_out,
                  const __grid_constant__ CUtensorMap tm_x64,
                  const Params P) {
    extern __shared__ __align__(1024) uint8_t smem[];
    const unsigned long long tstart = clock64();
    const uint32_t sb = smem_u32(smem);
    const int tid = threadIdx.x, lane = tid & 31;
    const int warp = __shfl_sync(0xffffffffu, tid >> 5, 0);
    const int pr = blockIdx.x >> 1, p7 = ((pr - 36) * 37) >> 8;
    const int c = blockIdx.x & 1;
    const int gi = pr < 4 ? 7 : pr < 36 ? 2 * ((pr - 4) & 7) + (((pr - 4) >> 2) & 1) : 2 * (pr - 36 - 7 * p7) + 1 + (pr - 36 - 7 * p7 > 2);
    const int g = gi & 7;
    const int r = (gi >> 3) * 4 + (pr < 4 ? pr : pr < 36 ? (pr - 4) >> 3 : p7);
#define BLK(n) ((n) - ((n) <= g))
    const int grp = 2 * r + c;
    const int b = g * 16 + grp;
    const uint32_t bar0 = sb + OFF_BAR;
    const uint32_t zero = P.zero;
#define BAR(i) (bar0 + 8u * (i))
#define XBAR(i) (sb + OFF_XB + 64 + 8u * (i))
#define CLUSTER_ARRIVE() asm volatile("barrier.cluster.arrive.relaxed.aligned;" ::: "memory")
#define CLUSTER_WAIT() asm volatile("barrier.cluster.wait.aligned;" ::: "memory")
    if ((sb & 0xffffffu) != SB0) return;

#define LOAD0(it) do { \
            mbar_expect_tx(BAR(B_FS + DSLOT(it)), SLOT); tma_2d(sb + OFF_S + DSLOT(it) * SLOT, tmD, (it) * 64, r * 128, BAR(B_FS + DSLOT(it))); \
            mbar_expect_tx(BAR(B_FL + (it)), SLOT); tma_2d(sb + OFF_L + (it) * SLOT, &tm_x, (it) * 64, g * 256, BAR(B_FL + (it))); \
            mbar_expect_tx(BAR(B_FL + 4 + (it)), SLOT); tma_2d(sb + OFF_L + (4 + (it)) * SLOT, &tm_x, (it) * 64, g * 256 + 128, BAR(B_FL + 4 + (it))); \
        } while (0)
    if (warp == 12) {
        if (elect_one()) {
            const CUtensorMap* tmD = c ? &tm_dim : &tm_dre;
            prefetch_tmap(&tm_x);
            mbar_init(BAR(B_FS + 2), 1); mbar_init(BAR(B_FL), 1); mbar_init(BAR(B_FL + 4), 1);
            asm volatile("fence.mbarrier_init.release.cluster;" ::: "memory");
            LOAD0(0);
#pragma unroll
            for (int i = 0; i < B_COUNT; i++)
                if (i != B_FS + 2 && i != B_FL && i != B_FL + 4)
                    mbar_init(BAR(i), (i >= B_ES && i < B_FL) || i == B_GO ? 2 : i == B_STATS || i == B_LST ? 4 : 1);
#pragma unroll
            for (int i = 0; i < 12; i++) mbar_init(XBAR(i), 1);
#pragma unroll
            for (int i = 0; i < 4; i++) mbar_expect_tx(BAR(B_RECV + i), SLOT / 2);
            mbar_expect_tx(BAR(B_PEER), 1024); mbar_expect_tx(BAR(B_H), 128);
            asm volatile("fence.mbarrier_init.release.cluster;" ::: "memory");
            fence_async_smem();
        }
        __syncwarp();
    }
    CLUSTER_ARRIVE();

    if (warp >= 12) {
        asm volatile("setmaxnreg.dec.sync.aligned.u32 %0;" ::"n"(PROD_REGS));
        CLUSTER_WAIT();
        if (warp == 12) {
            if (elect_one()) {
                const CUtensorMap* tmD = c ? &tm_dim : &tm_dre;
#define XROWS(k) do { mbar_expect_tx(XBAR(k), 8192); bulk_g2s(sb + OFF_S + (k) * 8192, at(P.x, (b * 16 + (k) * 4) * D_ * 2), 8192, XBAR(k)); } while (0)
                int k = 0;
#pragma unroll 1
                for (int it = 1; it < 16; it++) {
                    if (it < 4) LOAD0(it);
                    else {
                        const int s = DSLOT(it);
                        mbar_wait(BAR(B_ES + s), ((it >> 2) & 1) ^ 1);
                        TRACE(it);
                        mbar_expect_tx(BAR(B_FS + s), SLOT);
                        tma_2d(sb + OFF_S + s * SLOT, tmD, it * 64, r * 128, BAR(B_FS + s));
                    }
                    while (((XS >> (4 * k)) & 15) == it) { XROWS(k); k++; }
                }
                const unsigned ep = load_epoch(b), e8 = ep & 0xffu;
                const uint8_t* abg = at(AB, grp * 32 * SLOT);
                const unsigned long long* fl = at(g_flag, grp * 128);
                unsigned long long rdy = ld_acquire64(fl);
                mbar_wait(BAR(B_SRD), 0);
                st_release8(at(g_flag, grp * 128 + g), e8);
                PROF_T(7);
                int j = 4;
#pragma unroll 1
                for (int cl = 0; cl < 4; cl++) {
                    if (cl) rdy = ld_acquire64(++fl);
                    fence_async_global();
#pragma unroll 1
                    for (int n = 1; n < 8; n++, j++) {
                        const int q = BLK(n), s = (j & 1) + ((j & 2) ? 0 : 4);
                        mbar_wait(BAR(B_ES + s), ((j >> 2) ^ (j >> 1)) & 1);
                        if (j == 7) mbar_wait(BAR(B_SRD + 1), 0);
                        if (((unsigned)(rdy >> (8 * q)) & 0xffu) != e8) {
                            int m = 0;
                            do { rdy = ld_acquire64(fl); } while (((unsigned)(rdy >> (8 * q)) & 0xffu) != e8 && ++m < SPIN_LIMIT);
                            fence_async_global();
                        }
                        TRACE(16 + j);
                        mbar_expect_tx(BAR(B_FS + s), SLOT);
                        bulk_g2s(sb + OFF_S + s * SLOT, at(abg, (4 * q + KO(cl)) * SLOT), SLOT, BAR(B_FS + s));
                    }
                }
                *at(g_epoch, b * 4) = ep;
            }
        } else if (warp < 15) {
            if (elect_one()) {
                const int w = warp - 13, row0 = g * 256 + w * 128;
                const CUtensorMap* tmC = c ? &tm_cim : &tm_cre;
                const uint32_t fb = BAR(B_FL + 4 * w), eb = BAR(B_EL + 4 * w), dst = sb + OFF_L + w * 4 * SLOT;
                prefetch_tmap(w ? &tm_out : tmC);
                [[maybe_unused]] unsigned long long mk = 0, mg = 0;
                int n = 0, cl = 0;
#pragma unroll 1
                for (int it = 4; it < 48; it++) {
                    const int s = it & 3;
                    mbar_wait(eb + 8 * s, ((it >> 2) & 1) ^ 1);
                    TRACE(64 + w * 64 + it - 4);
                    MARK(it);
                    mbar_expect_tx(fb + 8 * s, SLOT);
                    tma_2d(dst + s * SLOT, it < 16 ? &tm_x : tmC, (it < 16 ? it : 4 * (n ? BLK(n) : g) + KO(cl)) * 64, row0, fb + 8 * s);
                    if (it >= 16) {
                        if (it == 19) { n = 1; cl = 0; } else if (it < 19) cl++; else if (++n == 8) { n = 1; cl++; }
                    }
                }
#pragma unroll 1
                for (int h = 0; h < 4; h++) {
                    mbar_wait(eb + 8 * h, 1);
                    fence_async_smem();
                    tma_2d_store(&tm_out, grp * 64, row0 + h * 32, sb + OFF_S + (2 + (h >> 1)) * SLOT + w * 8192 + (h & 1) * 4096);
                    bulk_commit();
                }
                FINISH(w);
            }
        } else {
            const unsigned ep = load_epoch(b);
            uint4 f[4];
#define GATHER(ptr, cnt, valid) do { int n = 0; bool ok; do { ok = true; \
                _Pragma("unroll") for (int i = 0; i < (cnt); i++) { f[i] = ld_relaxed128((ptr) + i * 32); ok = ok && (valid); } \
                if (__all_sync(0xffffffffu, ok)) break; \
                __nanosleep(GSL); \
            } while (++n < SPIN_LIMIT); } while (0)
            {
                sleep_until((uint32_t)tstart + 6000);
                const uint4* keys = at(reinterpret_cast<const uint4*>(g_key), lane * 16);
                bool mine = false;
                int n = 0;
                do {
                    f[0] = ld_relaxed128(keys); f[1] = ld_relaxed128(keys + 32);
                    if (__all_sync(0xffffffffu, f[0].y == ep && f[0].w == ep && f[1].y == ep && f[1].w == ep)) break;
                    if (!mine) {
                        mbar_wait(BAR(B_LST), 0);
                        const uint4 k = *reinterpret_cast<const uint4*>(smem + OFF_XB);
                        if (lane == 0) st_relaxed64(at(g_key, b * 8), ((unsigned long long)ep << 32) | max(max(k.x, k.y), max(k.z, k.w)));
                        mine = true;
                    }
                    __nanosleep(GSL);
                } while (++n < SPIN_LIMIT);
                const unsigned key = __reduce_max_sync(0xffffffffu, max(max(f[0].x, f[0].z), max(f[1].x, f[1].z)));
                if (lane == 0) { *reinterpret_cast<unsigned*>(smem + OFF_SEL) = key; mbar_arrive(BAR(B_SEL)); PROF_T(8); }
            }
            if (elect_one()) {
#pragma unroll 1
                for (int cl = 0; cl < 4; cl++) {
                    uint8_t* dst = at(AB, (grp * 32 + 4 * g + KO(cl)) * SLOT);
                    const uint32_t src = sb + OFF_S + cl * SLOT, chunk = cl ? 1024 : SLOT;
                    mbar_wait(BAR(B_FS + cl), 0);
                    fence_async_smem();
                    if (cl == 0) PROF_T(3);
                    uint32_t t0 = clock32() + (cl == 1 ? PDEL : 0);
#pragma unroll 1
                    for (uint32_t o = 0; o < SLOT; o += chunk) {
                        sleep_until(t0);
                        bulk_s2g(dst + o, src + o, chunk);
                        bulk_commit();
                        t0 += cl == 1 ? PGAP1 : cl == 2 ? PGAP2 : PGAP3;
                    }
                    bulk_wait<0>();
                    TRACE(252 + cl);
                    if (cl < 2) mbar_arrive(BAR(B_SRD + cl));
                    else {
                        mbar_wait(BAR(B_ES + cl), 0);
                        mbar_expect_tx(BAR(B_FS + cl), SLOT);
                        tma_2d(src, &tm_x64, grp * 64, g * 256 + (cl - 2) * 64, BAR(B_FS + cl));
                        tma_2d(src + 8192, &tm_x64, grp * 64, g * 256 + (cl - 2) * 64 + 128, BAR(B_FS + cl));
                    }
                    if (cl) st_release8(at(g_flag, grp * 128 + cl * 8 + g), ep & 0xffu);
                    if (cl == 1) PROF_T(5);
                    if (cl == 3) PROF_T(4);
                }
            }
        }
    } else if (warp >= 8) {
        asm volatile("setmaxnreg.dec.sync.aligned.u32 %0;" ::"n"(512 - PROD_REGS - 2 * CONS_REGS));
        const int aw = warp - 8, mt = tid - 256;
        unsigned ep;
        {
            const uint8_t* rp = smem + OFF_S + aw * 2048 + lane * 16;
            const __nv_bfloat16* dp = at(c ? P.dim : P.dre, (r * 128 + g * 16 + aw * 4) * D_ * 2);
            float wf[32], sw = 0.f;
#pragma unroll
            for (int i = 0; i < 4; i++) {
                const uint4 w = __ldg(reinterpret_cast<const uint4*>(at(P.wr, lane * 16) + i * 256));
                const uint32_t wv[4] = {w.x, w.y, w.z, w.w};
#pragma unroll
                for (int e = 0; e < 4; e++) { wf[8 * i + 2 * e] = bf_lo(wv[e]); wf[8 * i + 2 * e + 1] = bf_hi(wv[e]); sw = (sw + bf_lo(wv[e])) + bf_hi(wv[e]); }
            }
            ep = load_epoch(b);
            sw = warp_sum(sw);
            CLUSTER_WAIT();
            float x0[4] = {}, s1[4] = {}, s2[4] = {}, sx[4] = {}, sd[4] = {};
#define PUSH(a, v) do { a[0] = a[1]; a[1] = a[2]; a[2] = a[3]; a[3] = v; } while (0)
#pragma unroll 1
            for (int k = 0; k < 4; k++) {
                mbar_wait(XBAR(k), 0);
                uint4 v[4];
#pragma unroll
                for (int i = 0; i < 4; i++) v[i] = *reinterpret_cast<const uint4*>(rp + k * 8192 + i * 512);
                uint32_t sh = v[0].x << 16;
                float a1s = 0.f, a2s = 0.f, axs = 0.f;
#pragma unroll
                for (int i = 0; i < 4; i++) {
                    sh = __shfl_sync(0xffffffffu, sh | (__float_as_uint(axs) & zero), 0);
                    const uint32_t xv[4] = {v[i].x, v[i].y, v[i].z, v[i].w};
#pragma unroll
                    for (int e = 0; e < 4; e++) {
                        const float a0 = bf_lo(xv[e]) - __uint_as_float(sh), a1 = bf_hi(xv[e]) - __uint_as_float(sh);
                        a1s += a0 + a1;
                        a2s = fmaf(a0, a0, fmaf(a1, a1, a2s));
                        axs = fmaf(a0, wf[8 * i + 2 * e], fmaf(a1, wf[8 * i + 2 * e + 1], axs));
                    }
                }
                PUSH(x0, __uint_as_float(sh)); PUSH(s1, a1s); PUSH(s2, a2s); PUSH(sx, axs);
                fence_async_smem();
                __syncwarp();
                if (elect_one()) {
                    const uint32_t db = XBAR(k == 3 ? 8 + aw : 4 + aw);
                    if (k == 0 || k == 3) mbar_expect_tx(db, k ? 2048 : 6144);
                    bulk_g2s(sb + OFF_S + k * 8192 + aw * 2048, dp + k * D_, 2048, db);
                }
            }
#define FOLD4(a) do { const bool u16 = lane & 16, u8 = lane & 8; \
                float p0 = (u16 ? a[2] : a[0]) + __shfl_xor_sync(0xffffffffu, u16 ? a[0] : a[2], 16); \
                float p1 = (u16 ? a[3] : a[1]) + __shfl_xor_sync(0xffffffffu, u16 ? a[1] : a[3], 16); \
                a[0] = (u8 ? p1 : p0) + __shfl_xor_sync(0xffffffffu, u8 ? p0 : p1, 8); \
                _Pragma("unroll") for (int o = 4; o; o >>= 1) a[0] += __shfl_xor_sync(0xffffffffu, a[0], o); } while (0)
#pragma unroll 1
            for (int k = 0; k < 4; k++) {
                mbar_wait(XBAR(k == 3 ? 8 + aw : 4 + aw), 0);
                float run = 0.f;
#pragma unroll
                for (int i = 0; i < 4; i++) {
                    const uint4 v = *reinterpret_cast<const uint4*>(rp + k * 8192 + i * 512);
                    const uint32_t dv[4] = {v.x, v.y, v.z, v.w};
#pragma unroll
                    for (int e = 0; e < 4; e++) run += bf_lo(dv[e]) + bf_hi(dv[e]);
                }
                PUSH(sd, run);
            }
            named_bar<4, 128>();
            if (mt < 12) asm volatile("mbarrier.inval.shared::cta.b64 [%0];" ::"r"(XBAR(mt)) : "memory");
            FOLD4(sd); FOLD4(s1); FOLD4(s2); FOLD4(sx);
            const float nb = __shfl_down_sync(0xffffffffu, sd[0], 8);
            if ((lane & 15) == 0)
                st_relaxed128(at(g_rs, (grp * 64 + g * 8 + aw * 2 + (lane >> 4)) * 16), make_uint4(__float_as_uint(sd[0]), ep, __float_as_uint(nb), ep));
            if (mt == 0) PROF_T(6);
            const int rr = lane >> 3;
            const float c0 = rr == 0 ? x0[0] : rr == 1 ? x0[1] : rr == 2 ? x0[2] : x0[3];
            const float dm = s1[0] * (1.0f / D_);
            const float mb = rbf(c0 + dm);
            const float rinv = rcp_f(rbf(sqrt_f(rbf(rbf(fmaxf(s2[0] * (1.0f / D_) - dm * dm, 0.f)) + 1e-5f))));
            if ((lane & 7) == 0) st_relaxed128(at(g_stat, (b * 16 + aw * 4 + rr) * 16), make_uint4(__float_as_uint(mb), __float_as_uint(rinv), ep, 0));
            unsigned u = __bfloat16_as_ushort(__float2bfloat16_rn((sx[0] + (c0 - mb) * sw) * rinv));
            u = (u & 0x8000u) ? (~u & 0xffffu) : (u | 0x8000u);
            u = (u << 16) | (0xffffu - (unsigned)(b * 16 + rr * 4 + aw));
            u = __reduce_max_sync(0xffffffffu, u);
            if (lane == 0) { *reinterpret_cast<unsigned*>(smem + OFF_XB + aw * 4) = u; mbar_arrive(BAR(B_LST)); }
            if (mt == 0) PROF_T(2);
            uint4 f[4];
            if (aw < 2) {
                const int t = SREC(aw * 128 + lane);
                GATHER(at(g_stat, (g * 256 + aw * 128 + lane) * 16), 4, f[i].z == ep);
#pragma unroll
                for (int i = 0; i < 4; i++) {
                    *reinterpret_cast<uint32_t*>(smem + OFF_RSTD + (POS(t) + i * 32) * 4) = f[i].y;
                    *reinterpret_cast<uint16_t*>(smem + OFF_MEAN + (POS(t) + i * 32) * 2) = (uint16_t)(f[i].x >> 16);
                }
            } else {
                const int e2 = (aw - 2) * 32 + lane;
                GATHER(at(g_rs, (grp * 64 + e2) * 16), 1, f[i].y == ep && f[i].w == ep);
#pragma unroll
                for (int i = 0; i < 2; i++) {
                    const float v = __uint_as_float(i ? f[0].z : f[0].x);
                    const float hi = rbf(v), mid = rbf(v - hi), lo = v - hi - mid;
                    *reinterpret_cast<uint4*>(smem + OFF_RS + (e2 * 2 + i) * 16) = make_uint4(pack_bf(hi, mid), pack_bf(lo, 0.f), 0, 0);
                }
            }
            fence_async_smem();
            __syncwarp();
            if (lane == 0) mbar_arrive(BAR(B_STATS));
            if (mt == 127) PROF_T(9);
        }
        const int pair = g * 7 + r;
        if (r < 7) {
            const uint64_t pol = policy_evict_first();
            const __nv_bfloat16* wp = at((aw & 1) ? P.wu : P.wg, ((c * 512 + (aw >> 1) * 256 + (lane >> 3) * 8) * F_ + pair * 64 + (lane & 7) * 8) * 2);
            uint4 b0[8], b1[8];
#define FILL(buf, str) do { _Pragma("unroll") for (int q = 0; q < 8; q++) buf[q] = ldg_stream(wp + q * (str), pol); } while (0)
#define PAUSE() do { if (mbar_test(BAR(B_QUIET), 0)) mbar_wait_sleep(BAR(B_GO), 0); } while (0)
            FILL(b0, F_);
            mbar_wait(BAR(B_SEL), 0);
            uint4 xn;
            {
                const int sel = ~*reinterpret_cast<volatile unsigned*>(smem + OFF_SEL) & (S_ - 1);
                xn = __ldg(reinterpret_cast<const uint4*>(at(P.x, (sel * D_ + c * 512 + (aw >> 1) * 256 + (lane & 7) * 32 + (lane >> 3) * 8) * 2)));
                uint4 f[1];
                GATHER(at(g_stat, SREC(sel) * 16), 1, f[i].z == ep);
                wp += 32 * F_; FILL(b1, F_); wp -= 32 * F_;
                PAUSE();
                const float m = __uint_as_float(f[0].x), ri = __uint_as_float(f[0].y);
                xn = make_uint4(norm2(xn.x, m, ri), norm2(xn.y, m, ri), norm2(xn.z, m, ri), norm2(xn.w, m, ri));
            }
            float ag[8];
#pragma unroll
            for (int i = 0; i < 8; i++) ag[i] = 0.f;
#define ROUND(cur, nxt, rd) do { \
                PAUSE(); \
                if (lane == 0) TRACE(192 + aw * 12 + (rd)); \
                if ((rd) == 7) wp = at(P.wd - 16 * D_, ((pair * 64 + (lane >> 4) * 8) * D_ + c * 512 + aw * 128 + (lane & 15) * 8) * 2); \
                wp = at(wp, ((rd) < 7 ? 64 * F_ : 32 * D_) + (cur[7].x & zero)); \
                if ((rd) & 7) { if ((rd) < 7) FILL(nxt, F_); else if ((rd) < 11) FILL(nxt, D_); } \
                _Pragma("unroll") for (int q = 0; q < 8; q += 2) { \
                    const uint32_t xw = __shfl_sync(0xffffffffu, q == 0 ? xn.x : q == 2 ? xn.y : q == 4 ? xn.z : xn.w, (lane & 24) | ((rd) & 7)); \
                    fma8(ag, cur[q], bf_lo(xw)); \
                    fma8(ag, cur[q + 1], bf_hi(xw)); \
                    if (q < 6) yield(ag[7], zero); \
                } } while (0)
#pragma unroll 1
            for (int rd = 0; rd < 12; rd += 2) {
                ROUND(b0, b1, rd);
                ROUND(b1, b0, rd + 1);
                if (rd == 6 || rd == 10) {
#pragma unroll
                    for (int i = 0; i < 8; i++) ag[i] += __shfl_xor_sync(0xffffffffu, ag[i], 16);
                }
                if (rd == 6) {
#pragma unroll
                    for (int i = 0; i < 8; i++) ag[i] += __shfl_xor_sync(0xffffffffu, ag[i], 8);
                    if (lane < 8) {
                        const uint32_t dst = mapa(sb + OFF_XB + (c * 4 + aw) * 128 + (lane & 3) * 32, lane >> 2), pb = mapa(BAR(B_PEER), lane >> 2);
                        st_async4(dst, __float_as_uint(ag[0]), __float_as_uint(ag[1]), __float_as_uint(ag[2]), __float_as_uint(ag[3]), pb);
                        st_async4(dst + 16, __float_as_uint(ag[4]), __float_as_uint(ag[5]), __float_as_uint(ag[6]), __float_as_uint(ag[7]), pb);
                    }
                    __syncwarp();
                    wp += 16 * D_; FILL(b1, D_); wp -= 16 * D_;
                    if (aw == 3) {
                        mbar_wait_cluster(BAR(B_PEER), 0);
                        const float* ps = reinterpret_cast<const float*>(smem + OFF_XB) + lane;
                        const float go = (ps[0] + ps[64]) + (ps[128] + ps[192]), uo = (ps[32] + ps[96]) + (ps[160] + ps[224]);
                        const float h = rbf(silu_f(rbf(go))) * rbf(uo), ho = __shfl_xor_sync(0xffffffffu, h, 1);
                        asm volatile("st.async.weak.shared::cluster.mbarrier::complete_tx::bytes.b32 [%0], %1, [%2];"
                                     ::"r"(mapa(sb + OFF_H + c * 64 + (lane >> 1) * 4, lane & 1)), "r"((lane & 1) ? pack_bf(ho, h) : pack_bf(h, ho)),
                                       "r"(mapa(BAR(B_H), lane & 1)) : "memory");
                    }
                    mbar_wait_cluster(BAR(B_H), 0);
                    xn = *reinterpret_cast<const uint4*>(smem + OFF_H + (lane & 3) * 32 + (lane >> 4) * 16);
#pragma unroll
                    for (int i = 0; i < 8; i++) ag[i] = 0.f;
                    if (mt == 0) PROF_T(10);
                }
            }
            const int hi = lane >> 4;
            st_relaxed128(at(g_part, pair * 4096 + (c * 8 + aw * 2 + ((lane >> 3) & 1)) * 256 + hi * 128 + (lane & 7) * 16),
                          make_uint4((__float_as_uint(hi ? ag[4] : ag[0]) & ~15u) | (ep & 15u), __float_as_uint(hi ? ag[5] : ag[1]),
                                     __float_as_uint(hi ? ag[6] : ag[2]), __float_as_uint(hi ? ag[7] : ag[3])));
            if (mt == 0) PROF_T(11);
        } else {
            mbar_wait_sleep(BAR(B_SEL), 0);
        }
        const int sel = ~*reinterpret_cast<volatile unsigned*>(smem + OFF_SEL) & (S_ - 1);
        if ((sel >> 8) == g) {
            const int col = (lane & 7) * 8 + ((lane >> 3) & 1) * 4;
            const uint2 xv = __ldg(reinterpret_cast<const uint2*>(at(P.x, (sel * D_ + grp * 64 + col) * 2)));
            uint4 f[1];
            GATHER(at(g_stat, SREC(sel) * 16), 1, f[i].z == ep);
            const uint4 rec = f[0];
            const uint4* src = at(g_part, (aw * 14 + (lane >> 4)) * 4096 + grp * 256 + (lane & 15) * 16);
            if (r == 7) {
                int n = 0;
                while (((ld_relaxed(src) ^ ep) & 15u) != 0 && ++n < SPIN_LIMIT) __nanosleep(500);
            }
            uint4 t[7];
            int n = 0;
            bool ok;
            do {
                ok = true;
#pragma unroll
                for (int u = 0; u < 7; u++) { t[u] = ld_relaxed128(src + u * 512); ok = ok && ((t[u].x ^ ep) & 15u) == 0; }
            } while (!__all_sync(0xffffffffu, ok) && ++n < SPIN_LIMIT);
            float4 a = make_float4(0.f, 0.f, 0.f, 0.f);
#pragma unroll
            for (int u = 0; u < 7; u++) {
                a.x += __uint_as_float(t[u].x & ~15u); a.y += __uint_as_float(t[u].y); a.z += __uint_as_float(t[u].z); a.w += __uint_as_float(t[u].w);
            }
            a.x += __shfl_xor_sync(0xffffffffu, a.x, 16); a.y += __shfl_xor_sync(0xffffffffu, a.y, 16);
            a.z += __shfl_xor_sync(0xffffffffu, a.z, 16); a.w += __shfl_xor_sync(0xffffffffu, a.w, 16);
            float4* park = reinterpret_cast<float4*>(smem + OFF_XB) + (lane & 15);
            if (lane < 16) park[aw * 16] = a;
            named_bar<4, 128>();
            if (aw == 0) {
                const float4 p1 = park[16], p2 = park[32], p3 = park[48];
                a.x = (a.x + p1.x) + (p2.x + p3.x); a.y = (a.y + p1.y) + (p2.y + p3.y);
                a.z = (a.z + p1.z) + (p2.z + p3.z); a.w = (a.w + p1.w) + (p2.w + p3.w);
                unsigned u = *reinterpret_cast<volatile unsigned*>(smem + OFF_SEL) >> 16;
                u = (u & 0x8000u) ? (u & 0x7fffu) : (~u & 0xffffu);
                const float sg = rbf(__fdividef(1.0f, 1.0f + __expf(-__uint_as_float(u << 16))));
                const float m = __uint_as_float(rec.x), ri = __uint_as_float(rec.y);
                const uint32_t n0 = norm2(xv.x, m, ri), n1 = norm2(xv.y, m, ri);
                uint2 o;
                o.x = silu2(pack_bf(bf_lo(n0) + rbf(rbf(a.x) * sg), bf_hi(n0) + rbf(rbf(a.y) * sg)));
                o.y = silu2(pack_bf(bf_lo(n1) + rbf(rbf(a.z) * sg), bf_hi(n1) + rbf(rbf(a.w) * sg)));
                if (lane < 16) *reinterpret_cast<uint2*>(smem + OFF_H + col * 2) = o;
                __syncwarp();
                if (lane == 0) { mbar_arrive(BAR(B_UPD)); PROF_T(12); }
            }
        }
    } else {
        asm volatile("setmaxnreg.inc.sync.aligned.u32 %0;" ::"n"(CONS_REGS));
        CLUSTER_WAIT();
        const int wg = warp >> 2, wq = warp & 3;
        const int wt = tid & 127;
        float acc[128];
        const uint32_t fL = BAR(B_FL + 4 * wg), eL = BAR(B_EL + 4 * wg);
        const uint32_t dL = desc_lo(SB0 + OFF_L, 16) + wg * 4096;
        constexpr uint32_t dS = desc_lo(SB0 + OFF_S, 16);
        constexpr uint32_t SL = SLOT >> 4;
#define RELEASE(ls, ss) do { if (wt == 0) { mbar_arrive(eL + 8u * (ls)); mbar_arrive(BAR(B_ES + (ss))); } } while (0)
#define WAIT_FULL(ls, lph, ss, sph) do { mbar_wait(BAR(B_FS + (ss)), sph); mbar_wait(fL + 8u * (ls), lph); } while (0)
#define TURN() do { if (wg) named_bar<6, 256>(); else named_bar<5, 256>(); } while (0)
#define PASS() do { if (wg) named_arrive<5, 256>(); else named_arrive<6, 256>(); } while (0)
#define WG_BAR() do { if (wg) named_bar<2, 128>(); else named_bar<1, 128>(); } while (0)
        if (wg == 1) PASS();

#define MMA1_H(O, s, first) do { _Pragma("unroll") for (int kk = 0; kk < 4; kk++) \
            wgmma128<O, 0>(acc, dL + (s) * SL + kk * 2 + (O) * 8, dS + DSLOT(s) * SL + kk * 2, !((first) && kk == 0)); } while (0)
#define WAIT1(s, ph) WAIT_FULL(s, ph, DSLOT(s), ph)
#define PROBE(ls, lph, ss, sph) (mbar_test(BAR(B_FS + (ss)), sph) & mbar_test(fL + 8u * (ls), lph))
#define REL1(s) RELEASE(s, DSLOT(s))
#pragma unroll 1
        for (int it = 0; it < 12; it++) {
            const int s = it & 3;
            const bool ok = PROBE(s, (it >> 2) & 1, DSLOT(s), (it >> 2) & 1);
            if (it) { wg_wait<0>(); REL1((it - 1) & 3); }
            if (!ok) WAIT1(s, (it >> 2) & 1);
            TURN();
            wg_fence(); MMA1_H(0, s, it == 0); MMA1_H(64, s, it == 0); wg_commit();
            PASS();
            if (it == 0 && tid == 0) PROF_T(16);
        }
        TS(12);
        float rs[4] = {};
        uint32_t nm[8] = {};
#define GET_STATS() do { mbar_wait(BAR(B_STATS), 0); \
            const int p0 = POS(wg * 128 + wq * 16 + (lane >> 2));                   \
            const uint32_t msk = (lane & 3) == 0 ? 0xffffffffu : (lane & 3) == 1 ? 0x0000ffffu : 0u; \
            _Pragma("unroll") for (int i = 0; i < 4; i++) { \
                const int p = p0 + (i & 1) * 2 + (i >> 1) * 64; \
                rs[i] = *reinterpret_cast<const float*>(smem + OFF_RSTD + p * 4); \
                const uint32_t m = *reinterpret_cast<const uint16_t*>(smem + OFF_MEAN + p * 2) ^ 0x8000u; \
                nm[i + (i & 2)] = (m | (m << 16)) & msk; \
            } } while (0)
        const bool early = wg || __all_sync(0xffffffffu, mbar_test(BAR(B_STATS), 0));
        if (early && !wg) GET_STATS();
        WAIT1(0, 1);
        TS(13);
        wg_wait<0>(); REL1(3);
        if (wg) GET_STATS();
        TS(14);
        TURN();
        wg_fence();
        MMA1_H(0, 0, false);
        if (tid == 0) { mbar_arrive(BAR(B_QUIET)); PROF_T(15); }
        WAIT1(1, 1); wg_fence(); MMA1_H(0, 1, false);
        WAIT1(2, 1); wg_fence(); MMA1_H(0, 2, false); wg_commit();
        if (!early) GET_STATS();
        asm volatile("" : "+r"(nm[0]), "+r"(nm[1]), "+r"(nm[2]), "+r"(nm[3]), "+r"(nm[4]), "+r"(nm[5]), "+r"(nm[6]), "+r"(nm[7])::"memory");
        wg_fence();
        wgmma128_rs<64>(acc, nm + 4, (SB0 + OFF_RS) >> 4);
        wgmma128_rs<0>(acc, nm, (SB0 + OFF_RS) >> 4);
        WAIT1(3, 1); wg_fence(); MMA1_H(0, 3, false); wg_commit();
        PASS();
        const int mrow = wq * 16 + ((lane >> 3) & 1) * 8 + (lane & 7);
#define EPI1(O, slot, FREE) do { const uint32_t dst = sb + OFF_S + (slot) * SLOT + mrow * 128; \
            uint32_t pk[32]; \
            _Pragma("unroll") for (int i = 0; i < 32; i += 4) { \
                _Pragma("unroll") for (int k = 0; k < 4; k++) \
                    pk[i + k] = pack_bf(acc[(O) + 2 * (i + k)] * rs[(O) / 32 + (k & 1)], acc[(O) + 2 * (i + k) + 1] * rs[(O) / 32 + (k & 1)]); \
                if (i == EF) { FREE; } \
                if (i >= EF) { _Pragma("unroll") for (int v = (i == EF ? 0 : i); v <= i; v += 4) \
                    stmatrix4(dst + ((v >> 4) ^ c ^ 1) * 8192 + ((((v >> 1) & 7) + (lane >> 4)) ^ (lane & 7)) * 16, pk[v], pk[v + 1], pk[v + 2], pk[v + 3]); } } \
            WG_BAR(); \
            if (wt == 0) mbar_arrive(BAR(B_FS + (slot))); } while (0)
        TS(15);
        wg_wait<0>();
        fence_regs64<0>(acc);
        TS(16);
        {
            constexpr int EF = 0;
            EPI1(0, wg, if (wg) mbar_wait(BAR(B_FS), 0));
        }
        TS(17);
        TURN();
        wg_fence();
        MMA1_H(64, 0, false); wg_commit();
        MMA1_H(64, 1, false); wg_commit();
        MMA1_H(64, 2, false); wg_commit();
        wg_wait<2>(); REL1(0);
        MMA1_H(64, 3, false); wg_commit();
        PASS();
        TS(18);
        wg_wait<2>(); REL1(1);
        mbar_wait(BAR(B_FS), 0); mbar_wait(BAR(B_FS + 1), 0); fence_async_smem();
        wg_wait<1>(); REL1(2);
        wg_wait<0>(); REL1(3);
        fence_regs64<64>(acc);
        TS(19);
        {
            constexpr int EF = 16;
            EPI1(64, 2 + wg, mbar_wait(BAR(B_ES + 2 + wg), 1));
        }
        TS(20);

        float ac2[128];
#define MMA2_H(O, ls, ss, first) do { _Pragma("unroll") for (int kk = 0; kk < 4; kk++) \
            wgmma128<O, 1>(ac2, dS + (ss) * SL + kk * 128 + (O) * 8, dL + (ls) * SL + kk * 2, !((first) && kk == 0)); } while (0)
#define WAIT2(j) WAIT_FULL((j) & 3, ((j) >> 2) & 1, PSLOT(j), PPAR(j))
#define MMA2(j) do { wg_fence(); MMA2_H(0, (j) & 3, PSLOT(j), (j) == 0); MMA2_H(64, (j) & 3, PSLOT(j), (j) == 0); wg_commit(); } while (0)
#define REL2(j) RELEASE((j) & 3, PSLOT(j))
        WAIT2(0); TURN(); MMA2(0);
        WAIT2(1); MMA2(1); PASS();
        TS(21);
        wg_wait<1>(); REL2(0);
        mbar_wait(BAR(B_FS + 2), 0); mbar_wait(BAR(B_FS + 3), 0); fence_async_smem();
        TS(22);
        {
            uint32_t sp = 1;
#pragma unroll 1
            for (int j = 2; j < XJ; j++) {
                const uint32_t ss = PSLOT(j);
                const bool ok = PROBE(j & 3, (j >> 2) & 1, ss, PPAR(j));
                wg_wait<0>(); RELEASE((j - 1) & 3, sp);
                if (!ok) WAIT_FULL(j & 3, (j >> 2) & 1, ss, PPAR(j));
                TURN();
                wg_fence(); MMA2_H(0, j & 3, ss, false); MMA2_H(64, j & 3, ss, false); wg_commit();
                PASS();
                if (j == GOJ && wt == 0) { mbar_arrive(BAR(B_GO)); if (wg == 0) PROF_T(19); }
                sp = ss;
            }
        }
        if (tid == 0) PROF_T(20);
        uint32_t gt[32];
        const uint32_t xrow = sb + OFF_S + 2 * SLOT + wg * 8192 + ((lane >> 4) * 8 + (lane & 7)) * 128 + (((2 * wq + ((lane >> 3) & 1)) ^ (lane & 7)) << 4);
        const uint32_t gsign = c ? 0x80008000u : 0u;
#define XOFF(v) (((v) >> 2) * SLOT + ((v) & 3) * 2048)
        mbar_wait(BAR(B_SEL), 0);
        const int sel = ~*reinterpret_cast<volatile unsigned*>(smem + OFF_SEL) & (S_ - 1);
        bool own = (sel >> 7) == 2 * g + wg;
#define PATCH() do { own = false; \
            const uint32_t v0 = *reinterpret_cast<const uint16_t*>(smem + OFF_H + (wq * 16 + (lane >> 2)) * 2) ^ gsign; \
            const uint32_t v1 = *reinterpret_cast<const uint16_t*>(smem + OFF_H + (wq * 16 + (lane >> 2)) * 2 + 16) ^ gsign; \
            const uint32_t pick = (lane & 3) != ((sel >> 1) & 3) ? 0x3210u : (sel & 1) ? 0x5410u : 0x3254u; \
            _Pragma("unroll") for (int i = 0; i < 16; i++) { \
                const uint32_t m = ((sel >> 3) & 15) == i ? pick : 0x3210u; \
                gt[2 * i] = __byte_perm(gt[2 * i], v0, m); \
                gt[2 * i + 1] = __byte_perm(gt[2 * i + 1], v1, m); \
            } } while (0)
#pragma unroll
        for (int u = 0; u < 8; u++) {
            WAIT2(XJ + u); wg_wait<0>(); REL2(XJ + u - 1); TURN(); MMA2(XJ + u); PASS();
            uint32_t* o = &gt[4 * u];
            if (!(u & 3)) mbar_wait(BAR(B_FS + 2 + (u >> 2)), 1);
            ldmatrix4t(xrow + XOFF(u), o[0], o[1], o[2], o[3]);
            const float4 r4 = *reinterpret_cast<const float4*>(smem + OFF_RSTD + (wg * 128 + u * 16 + (lane & 3) * 4) * 4);
            const uint2 m2 = *reinterpret_cast<const uint2*>(smem + OFF_MEAN + (wg * 128 + u * 16 + (lane & 3) * 4) * 2);
            o[0] = gate2(o[0], m2.x, r4.x, r4.y) ^ gsign;
            o[1] = gate2(o[1], m2.x, r4.x, r4.y) ^ gsign;
            o[2] = gate2(o[2], m2.y, r4.z, r4.w) ^ gsign;
            o[3] = gate2(o[3], m2.y, r4.z, r4.w) ^ gsign;
            asm volatile("st.shared.v2.u32 [%0], {%1,%2};" ::"r"(sb + OFF_SEL + 16), "r"(o[0] ^ o[1]), "r"(o[2] ^ o[3]) : "memory");
        }
        if (tid == 0) PROF_T(21);
        WAIT2(28);
        wg_wait<0>(); REL2(27);
        if (own) {
            const uint32_t t0 = clock32();
            bool ok;
            while (!(ok = mbar_test(BAR(B_UPD), 0)) && clock32() - t0 < wg * 1400u) __nanosleep(50);
            if (__all_sync(0xffffffffu, ok)) PATCH();
        }
        TS(0);
        TURN();
        wg_fence(); MMA2_H(0, 0, PSLOT(28), false); wg_commit();
        if (wg == 0) { wg_fence(); MMA2_H(64, 0, PSLOT(28), false); wg_commit(); }
        WAIT2(29); wg_fence(); MMA2_H(0, 1, PSLOT(29), false); wg_commit();
        WAIT2(30); wg_fence(); MMA2_H(0, 2, PSLOT(30), false); wg_commit();
        wg_wait<2>();
        if (tid == 0) mbar_arrive_cluster(mapa(BAR(B_RDY), c ^ 1));
        WAIT2(31); wg_fence(); MMA2_H(0, 3, PSLOT(31), false); wg_commit();
        TS(1);
#define KEEP(i) wgmma128<64, 1>(ac2, dS + PSLOT(29 + ((i) >> 2)) * SL + ((i) & 3) * 128 + 512, dL + (1 + ((i) >> 2)) * SL + ((i) & 3) * 2, 1)
        wg_fence();
#pragma unroll
        for (int i = 0; i < KQ; i++) KEEP(i);
        wg_commit();
        mbar_wait(BAR(B_RDY + wg), 0);
        wg_wait<1>();
        fence_regs64<0>(ac2);
        TS(2);
        wg_fence();
        {
            const uint32_t dst = mapa(sb + OFF_L + wg * SLOT + wt * 16, c ^ 1), rb = mapa(BAR(B_RECV + 2 * wg), c ^ 1);
#pragma unroll
            for (int v = 0; v < 8; v++) {
                if (KQ + v < 12) KEEP(KQ + v);
                if (KQ + v == 11) { wg_commit(); if (wg == 0) PASS(); }
                st_async4(dst + v * 2048, pack_bf(ac2[8 * v + 0], ac2[8 * v + 1]), pack_bf(ac2[8 * v + 2], ac2[8 * v + 3]),
                          pack_bf(ac2[8 * v + 4], ac2[8 * v + 5]), pack_bf(ac2[8 * v + 6], ac2[8 * v + 7]), rb + (v >> 2) * 8);
            }
        }
        if (wg == 1) { wg_fence(); MMA2_H(64, 0, PSLOT(28), false); wg_commit(); }
        TS(3);
        uint32_t xr[32];
#define LDX(v) ldmatrix4t(xrow + XOFF(v), xr[4 * (v)], xr[4 * (v) + 1], xr[4 * (v) + 2], xr[4 * (v) + 3])
#pragma unroll
        for (int v = 0; v < XE; v++) LDX(v);
        if (wg == 0) {
            wg_wait<0>();
            if (wt == 0) mbar_arrive_cluster(mapa(BAR(B_RDY + 1), c ^ 1));
        }
        TS(4);
        if (own) { mbar_wait(BAR(B_UPD), 0); PATCH(); }
        TS(5);
        uint4 rv[8];
#define FETCH(v0) do { if ((v0) == 0 || (v0) == 4) mbar_wait_cluster(BAR(B_RECV + 2 * wg + (v0) / 4), 0); \
            _Pragma("unroll") for (int v = (v0); v < (v0) + 2; v++) { \
                asm volatile("ld.shared.v4.u32 {%0,%1,%2,%3}, [%4];" : "=r"(rv[v].x), "=r"(rv[v].y), "=r"(rv[v].z), "=r"(rv[v].w) \
                             : "r"(sb + OFF_L + wg * SLOT + v * 2048 + wt * 16) : "memory"); \
                if (v >= XE) LDX(v); } } while (0)
        FETCH(0);
        TS(6);
        wg_wait<0>();
        fence_regs64<64>(ac2);
        TS(7);
#pragma unroll
        for (int v0 = 0; v0 < 8; v0 += 2) {
#pragma unroll
            for (int v = v0; v < v0 + 2; v++) {
                const float* a = &ac2[64 + 8 * v];
                stmatrix4t(xrow + XOFF(v),
                           bfma2(bsub2(pack_bf(a[0], a[1]), rv[v].x), gt[4 * v + 0], xr[4 * v + 0]),
                           bfma2(bsub2(pack_bf(a[2], a[3]), rv[v].y), gt[4 * v + 1], xr[4 * v + 1]),
                           bfma2(bsub2(pack_bf(a[4], a[5]), rv[v].z), gt[4 * v + 2], xr[4 * v + 2]),
                           bfma2(bsub2(pack_bf(a[6], a[7]), rv[v].w), gt[4 * v + 3], xr[4 * v + 3]));
            }
            WG_BAR();
            if (wt == 0) mbar_arrive(eL + 4 * v0);
            if (v0 + 2 < 8) FETCH(v0 + 2);
            if (v0 == 0) TS(8);
        }
        TS(9);
    }
}

typedef CUresult (*EncodeFn)(CUtensorMap*, CUtensorMapDataType, cuuint32_t, void*, const cuuint64_t*, const cuuint64_t*,
                             const cuuint32_t*, const cuuint32_t*, CUtensorMapInterleave, CUtensorMapSwizzle,
                             CUtensorMapL2promotion, CUtensorMapFloatOOBfill);

void make_map(EncodeFn fn, CUtensorMap* tm, const void* p, uint64_t rows, uint64_t cols, uint32_t box_rows) {
    cuuint64_t dims[2] = {cols, rows};
    cuuint64_t strides[1] = {cols * 2};
    cuuint32_t box[2] = {64, box_rows};
    cuuint32_t es[2] = {1, 1};
    fn(tm, CU_TENSOR_MAP_DATA_TYPE_BFLOAT16, 2, const_cast<void*>(p), dims, strides, box, es, CU_TENSOR_MAP_INTERLEAVE_NONE,
       CU_TENSOR_MAP_SWIZZLE_128B, CU_TENSOR_MAP_L2_PROMOTION_L2_128B, CU_TENSOR_MAP_FLOAT_OOB_FILL_NONE);
}

}

extern "C" void kernel_launch(void* const* d_in, const int* in_sizes, int n_in, void* d_out, int out_size) {
    (void)in_sizes; (void)n_in; (void)out_size;
    static EncodeFn fn = nullptr;
    if (!fn) {
        void* p = nullptr;
        cudaDriverEntryPointQueryResult q;
        cudaGetDriverEntryPoint("cuTensorMapEncodeTiled", &p, cudaEnableDefault, &q);
        fn = (EncodeFn)p;
        cudaFuncSetAttribute(fnet_fused_kernel, cudaFuncAttributeMaxDynamicSharedMemorySize, SMEM_BYTES);
    }
    CUtensorMap tx, tdre, tdim, tcre, tcim, tout, tx64;
    make_map(fn, &tx, d_in[0], S_, D_, 128);
    make_map(fn, &tcre, d_in[1], S_, S_, 128);
    make_map(fn, &tcim, d_in[2], S_, S_, 128);
    make_map(fn, &tdre, d_in[3], D_, D_, 128);
    make_map(fn, &tdim, d_in[4], D_, D_, 128);
    make_map(fn, &tx64, d_in[0], S_, D_, 64);
    make_map(fn, &tout, d_out, S_, D_, 32);
    Params P;
    P.x = (const __nv_bfloat16*)d_in[0];
    P.dre = (const __nv_bfloat16*)d_in[3];
    P.dim = (const __nv_bfloat16*)d_in[4];
    P.wr = (const __nv_bfloat16*)d_in[6];
    P.wg = (const __nv_bfloat16*)d_in[7];
    P.wu = (const __nv_bfloat16*)d_in[8];
    P.wd = (const __nv_bfloat16*)d_in[9];
    P.zero = 0;
    fnet_fused_kernel<<<NCTA, NTHREADS, SMEM_BYTES, cudaStreamPerThread>>>(tx, tdre, tdim, tcre, tcim, tout, tx64, P);
}
```

```cpp
#include <cuda_runtime.h>
#include <cuda_bf16.h>
#include <cuda.h>
#include <stdint.h>

#define GSL 200
#define SLEEP_NS 200
#define PDEL 1000
#define PGAP1 200
#define PGAP2 200
#define PGAP3 240
#define GOJ 2
#define LDEL 1300
#define LGAP 750
#define PTJ 10
#define X0 2
#define KQ 5
#define XE 2
#define PROD_REGS 32
#define CONS_REGS 184

namespace {

constexpr int S_ = 2048, D_ = 1024, F_ = 3584;
constexpr int NCTA = 128;
constexpr int XJ = 20;
constexpr uint32_t SLOT = 16384;
constexpr uint32_t OFF_L = 0;
constexpr uint32_t OFF_S = 8 * SLOT;
constexpr uint32_t OFF_RS = OFF_S + SLOT;
constexpr uint32_t OFF_BAR = 14 * SLOT;
constexpr uint32_t OFF_SEL = OFF_BAR + 360;
constexpr uint32_t OFF_RSTD = OFF_BAR + 384;
constexpr uint32_t OFF_MEAN = OFF_RSTD + 1024;
constexpr uint32_t OFF_XB = OFF_MEAN + 512;
constexpr uint32_t OFF_H = OFF_XB + 1024;
constexpr uint32_t SMEM_BYTES = OFF_H + 128;
constexpr uint32_t SB0 = 1024;
constexpr int NTHREADS = 512;
static_assert(SMEM_BYTES <= 232448, "smem");

enum { B_FS = 0, B_ES = 6, B_FL = 12, B_EL = 20, B_SRD = 28, B_RECV = 30  , B_RDY = 34, B_STATS = 36, B_LST = 37, B_UPD = 38,
       B_QUIET = 39, B_GO = 40, B_PEER = 41, B_SEL = 42, B_H = 43, B_COUNT = 44 };
static_assert(B_COUNT * 8 <= 360, "barriers");

__device__ __align__(1024) uint8_t g_ab[16u * 32u * SLOT];
__device__ __align__(128) uint4 g_part[56 * (D_ / 4)];
__device__ __align__(128) uint4 g_stat[S_];
__device__ __align__(128) uint4 g_rs[D_];
__device__ __align__(128) unsigned long long g_key[NCTA];
__device__ __align__(128) unsigned long long g_flag[16 * 16];
__device__ __align__(128) unsigned g_epoch[NCTA];
#define PROF_T(i) do {} while (0)
#define TRACE(i) do {} while (0)
#define PROF_G(i) do {} while (0)
#define TS(i) do {} while (0)
#define FINISH(wg) bulk_wait_read<0>()

#define MARK(it) do {} while (0)

__device__ __forceinline__ uint32_t smem_u32(const void* p) { return (uint32_t)__cvta_generic_to_shared(p); }
__device__ __forceinline__ void mbar_init(uint32_t bar, uint32_t cnt) {
    asm volatile("mbarrier.init.shared::cta.b64 [%0], %1;" ::"r"(bar), "r"(cnt) : "memory");
}
__device__ __forceinline__ bool mbar_try(uint32_t bar, uint32_t parity) {
    uint32_t ok;
    asm volatile("{\n.reg .pred p;\nmbarrier.try_wait.parity.shared::cta.b64 p, [%1], %2;\nselp.u32 %0, 1, 0, p;\n}"
                 : "=r"(ok) : "r"(bar), "r"(parity) : "memory");
    return ok;
}
__device__ __forceinline__ bool mbar_test(uint32_t bar, uint32_t parity) {
    uint32_t ok;
    asm volatile("{\n.reg .pred p;\nmbarrier.test_wait.parity.shared::cta.b64 p, [%1], %2;\nselp.u32 %0, 1, 0, p;\n}"
                 : "=r"(ok) : "r"(bar), "r"(parity) : "memory");
    return ok;
}
__device__ __forceinline__ bool mbar_try_cluster(uint32_t bar, uint32_t parity) {
    uint32_t ok;
    asm volatile("{\n.reg .pred p;\nmbarrier.try_wait.parity.acquire.cluster.shared::cta.b64 p, [%1], %2;\nselp.u32 %0, 1, 0, p;\n}"
                 : "=r"(ok) : "r"(bar), "r"(parity) : "memory");
    return ok;
}
constexpr int SPIN_LIMIT = 1 << 20;
__device__ __forceinline__ void mbar_wait(uint32_t bar, uint32_t parity) {
    if (mbar_try(bar, parity)) return;
    int n = 0;
    while (!mbar_try(bar, parity) && ++n < SPIN_LIMIT) {}
}
__device__ __forceinline__ void mbar_wait_cluster(uint32_t bar, uint32_t parity) {
    int n = 0;
    while (!mbar_try_cluster(bar, parity) && ++n < SPIN_LIMIT) {}
}
__device__ __forceinline__ void mbar_wait_sleep(uint32_t bar, uint32_t parity) {
    int n = 0;
    while (!mbar_try(bar, parity) && ++n < SPIN_LIMIT) __nanosleep(SLEEP_NS);
}
__device__ __forceinline__ void mbar_arrive(uint32_t bar) {
    asm volatile("mbarrier.arrive.shared::cta.b64 _, [%0];" ::"r"(bar) : "memory");
}
__device__ __forceinline__ void mbar_arrive_cluster(uint32_t cluster_bar) {
    asm volatile("mbarrier.arrive.shared::cluster.b64 _, [%0];" ::"r"(cluster_bar) : "memory");
}
__device__ __forceinline__ void mbar_expect_tx(uint32_t bar, uint32_t bytes) {
    asm volatile("mbarrier.arrive.expect_tx.shared::cta.b64 _, [%0], %1;" ::"r"(bar), "r"(bytes) : "memory");
}
__device__ __forceinline__ bool elect_one() {
    uint32_t p;
    asm volatile("{\n.reg .pred p;\nelect.sync _|p, 0xffffffff;\nselp.u32 %0, 1, 0, p;\n}" : "=r"(p));
    return p;
}
__device__ __forceinline__ uint32_t mapa(uint32_t addr, uint32_t rank) {
    uint32_t r;
    asm("mapa.shared::cluster.u32 %0, %1, %2;" : "=r"(r) : "r"(addr), "r"(rank));
    return r;
}
__device__ __forceinline__ uint32_t clock32() { uint32_t t; asm volatile("mov.u32 %0, %%clock;" : "=r"(t)); return t; }
__device__ __forceinline__ void sleep_until(uint32_t t) {
    int n = 0;
    while ((int)(clock32() - t) < 0 && ++n < SPIN_LIMIT) __nanosleep(20);
}
__device__ __forceinline__ void yield(float last, uint32_t zero) {
    asm volatile("nanosleep.u32 %0;" ::"r"(__float_as_uint(last) & zero));
}
template <typename T> __device__ __forceinline__ T* at(T* p, uint32_t bytes) {
    asm("" : "+r"(bytes));
    return reinterpret_cast<T*>(reinterpret_cast<uintptr_t>(p) + bytes);
}
__device__ __forceinline__ void tma_2d(uint32_t dst, const CUtensorMap* tm, int c0, int c1, uint32_t bar) {
    asm volatile("cp.async.bulk.tensor.2d.shared::cluster.global.mbarrier::complete_tx::bytes [%0], [%1, {%3, %4}], [%2];"
                 ::"r"(dst), "l"(tm), "r"(bar), "r"(c0), "r"(c1) : "memory");
}
__device__ __forceinline__ void tma_2d_store(const CUtensorMap* tm, int c0, int c1, uint32_t src) {
    asm volatile("cp.async.bulk.tensor.2d.global.shared::cta.bulk_group [%0, {%2, %3}], [%1];"
                 ::"l"(tm), "r"(src), "r"(c0), "r"(c1) : "memory");
}
__device__ __forceinline__ void bulk_g2s(uint32_t dst, const void* src, uint32_t bytes, uint32_t bar) {
    asm volatile("cp.async.bulk.shared::cluster.global.mbarrier::complete_tx::bytes [%0], [%1], %2, [%3];"
                 ::"r"(dst), "l"(src), "r"(bytes), "r"(bar) : "memory");
}
__device__ __forceinline__ void bulk_s2g(void* dst, uint32_t src, uint32_t bytes) {
    asm volatile("cp.async.bulk.global.shared::cta.bulk_group [%0], [%1], %2;" ::"l"(dst), "r"(src), "r"(bytes) : "memory");
}
__device__ __forceinline__ void st_async4(uint32_t dst, uint32_t a, uint32_t b, uint32_t c, uint32_t d, uint32_t bar) {
    asm volatile("st.async.weak.shared::cluster.mbarrier::complete_tx::bytes.v4.b32 [%0], {%1,%2,%3,%4}, [%5];"
                 ::"r"(dst), "r"(a), "r"(b), "r"(c), "r"(d), "r"(bar) : "memory");
}
__device__ __forceinline__ void bulk_commit() { asm volatile("cp.async.bulk.commit_group;" ::: "memory"); }
template <int N> __device__ __forceinline__ void bulk_wait_read() { asm volatile("cp.async.bulk.wait_group.read %0;" ::"n"(N) : "memory"); }
template <int N> __device__ __forceinline__ void bulk_wait() { asm volatile("cp.async.bulk.wait_group %0;" ::"n"(N) : "memory"); }
__device__ __forceinline__ void fence_async_smem() { asm volatile("fence.proxy.async.shared::cta;" ::: "memory"); }
__device__ __forceinline__ void fence_async_global() { asm volatile("fence.proxy.async.global;" ::: "memory"); }
__device__ __forceinline__ void prefetch_tmap(const CUtensorMap* tm) {
    asm volatile("prefetch.tensormap [%0];" ::"l"(tm) : "memory");
}
__device__ __forceinline__ unsigned long long ld_acquire64(const unsigned long long* p) {
    unsigned long long v; asm volatile("ld.acquire.gpu.global.u64 %0, [%1];" : "=l"(v) : "l"(p) : "memory"); return v;
}
__device__ __forceinline__ unsigned load_epoch(int b) {
    unsigned v; asm volatile("ld.global.u32 %0, [%1];" : "=r"(v) : "l"(at(g_epoch, b * 4)) : "memory"); return v + 1;
}
__device__ __forceinline__ unsigned ld_relaxed(const void* p) {
    unsigned v; asm volatile("ld.relaxed.gpu.global.u32 %0, [%1];" : "=r"(v) : "l"(p) : "memory"); return v;
}
__device__ __forceinline__ uint4 ld_relaxed128(const uint4* p) {
    uint4 v;
    asm volatile("{\n.reg .b128 t;\n.reg .b64 lo, hi;\nld.relaxed.gpu.global.b128 t, [%4];\nmov.b128 {lo, hi}, t;\n"
                 "mov.b64 {%0, %1}, lo;\nmov.b64 {%2, %3}, hi;\n}"
                 : "=r"(v.x), "=r"(v.y), "=r"(v.z), "=r"(v.w) : "l"(p) : "memory");
    return v;
}
__device__ __forceinline__ void st_relaxed128(uint4* p, const uint4& v) {
    asm volatile("{\n.reg .b128 t;\n.reg .b64 lo, hi;\nmov.b64 lo, {%1, %2};\nmov.b64 hi, {%3, %4};\nmov.b128 t, {lo, hi};\n"
                 "st.relaxed.gpu.global.b128 [%0], t;\n}"
                 ::"l"(p), "r"(v.x), "r"(v.y), "r"(v.z), "r"(v.w) : "memory");
}
__device__ __forceinline__ void st_relaxed64(unsigned long long* p, unsigned long long v) {
    asm volatile("st.relaxed.gpu.global.u64 [%0], %1;" ::"l"(p), "l"(v) : "memory");
}
__device__ __forceinline__ void st_release8(void* p, unsigned v) {
    asm volatile("st.release.gpu.global.u8 [%0], %1;" ::"l"(p), "r"(v) : "memory");
}
__device__ __forceinline__ uint64_t policy_evict_first() {
    uint64_t pol;
    asm("createpolicy.fractional.L2::evict_first.b64 %0, 1.0;" : "=l"(pol));
    return pol;
}
__device__ __forceinline__ uint4 ldg_stream(const void* p, uint64_t pol) {
    uint4 v;
    asm volatile("ld.global.nc.L1::no_allocate.L2::cache_hint.v4.u32 {%0,%1,%2,%3}, [%4], %5;"
                 : "=r"(v.x), "=r"(v.y), "=r"(v.z), "=r"(v.w) : "l"(p), "l"(pol));
    return v;
}
template <int ID, int N> __device__ __forceinline__ void named_arrive() { asm volatile("bar.arrive %0, %1;" ::"n"(ID), "n"(N) : "memory"); }
template <int ID, int N> __device__ __forceinline__ void named_bar() { asm volatile("bar.sync %0, %1;" ::"n"(ID), "n"(N) : "memory"); }

__device__ __forceinline__ float bf_lo(uint32_t u) { return __uint_as_float(u << 16); }
__device__ __forceinline__ float bf_hi(uint32_t u) { return __uint_as_float(u & 0xffff0000u); }
__device__ __forceinline__ uint32_t pack_bf(float lo, float hi) {
    uint32_t r; asm("cvt.rn.bf16x2.f32 %0, %1, %2;" : "=r"(r) : "f"(hi), "f"(lo)); return r;
}
__device__ __forceinline__ float rbf(float v) { return __uint_as_float(pack_bf(0.f, v)); }
__device__ __forceinline__ float sqrt_f(float v) { float r; asm("sqrt.approx.f32 %0, %1;" : "=f"(r) : "f"(v)); return r; }
__device__ __forceinline__ float rcp_f(float v) { float r; asm("rcp.approx.f32 %0, %1;" : "=f"(r) : "f"(v)); return r; }
__device__ __forceinline__ float silu_f(float z) { return __fdividef(z, 1.0f + __expf(-z)); }
__device__ __forceinline__ uint32_t bsub2(uint32_t a, uint32_t b) {
    uint32_t r; asm("sub.rn.bf16x2 %0, %1, %2;" : "=r"(r) : "r"(a), "r"(b)); return r;
}
__device__ __forceinline__ uint32_t bfma2(uint32_t a, uint32_t b, uint32_t c) {
    uint32_t r; asm("fma.rn.bf16x2 %0, %1, %2, %3;" : "=r"(r) : "r"(a), "r"(b), "r"(c)); return r;
}
__device__ __forceinline__ uint32_t norm2(uint32_t xv, float m, float rinv) {
    uint32_t t = pack_bf(bf_lo(xv) - m, bf_hi(xv) - m);
    return pack_bf(bf_lo(t) * rinv, bf_hi(t) * rinv);
}
__device__ __forceinline__ float gate1(float z) {
    float t;
    const float h = 0.5f * z;
    asm("tanh.approx.f32 %0, %1;" : "=f"(t) : "f"(h));
    return fmaf(h, t, h);
}
__device__ __forceinline__ uint32_t gate2(uint32_t xv, uint32_t mean2, float r0, float r1) {
    const uint32_t t = bsub2(xv, mean2);
    return pack_bf(gate1(bf_lo(t) * r0), gate1(bf_hi(t) * r1));
}
__device__ __forceinline__ uint32_t silu2(uint32_t z) { return pack_bf(silu_f(bf_lo(z)), silu_f(bf_hi(z))); }

__device__ __forceinline__ void stmatrix4(uint32_t addr, uint32_t r0, uint32_t r1, uint32_t r2, uint32_t r3) {
    asm volatile("stmatrix.sync.aligned.m8n8.x4.shared.b16 [%0], {%1,%2,%3,%4};"
                 ::"r"(addr), "r"(r0), "r"(r1), "r"(r2), "r"(r3));
}
__device__ __forceinline__ void stmatrix4t(uint32_t addr, uint32_t r0, uint32_t r1, uint32_t r2, uint32_t r3) {
    asm volatile("stmatrix.sync.aligned.m8n8.x4.trans.shared.b16 [%0], {%1,%2,%3,%4};"
                 ::"r"(addr), "r"(r0), "r"(r1), "r"(r2), "r"(r3));
}
__device__ __forceinline__ void ldmatrix4t(uint32_t addr, uint32_t& r0, uint32_t& r1, uint32_t& r2, uint32_t& r3) {
    asm volatile("ldmatrix.sync.aligned.m8n8.x4.trans.shared.b16 {%0,%1,%2,%3}, [%4];"
                 : "=r"(r0), "=r"(r1), "=r"(r2), "=r"(r3) : "r"(addr));
}

__device__ __forceinline__ void wg_fence() { asm volatile("wgmma.fence.sync.aligned;" ::: "memory"); }
__device__ __forceinline__ void wg_commit() { asm volatile("wgmma.commit_group.sync.aligned;" ::: "memory"); }
template <int N> __device__ __forceinline__ void wg_wait() { asm volatile("wgmma.wait_group.sync.aligned %0;" ::"n"(N) : "memory"); }

__host__ __device__ constexpr uint32_t desc_lo(uint32_t addr, uint32_t lbo) { return ((addr & 0x3FFFF) >> 4) | ((lbo >> 4) << 16); }
#define DESC_HI "0x40000040"

#define R8(a, o) "+f"(a[(o) + 0]), "+f"(a[(o) + 1]), "+f"(a[(o) + 2]), "+f"(a[(o) + 3]), \
                 "+f"(a[(o) + 4]), "+f"(a[(o) + 5]), "+f"(a[(o) + 6]), "+f"(a[(o) + 7])
#define R64(a, o) R8(a, (o) + 0), R8(a, (o) + 8), R8(a, (o) + 16), R8(a, (o) + 24), \
                  R8(a, (o) + 32), R8(a, (o) + 40), R8(a, (o) + 48), R8(a, (o) + 56)

template <int O, int TA>
__device__ __forceinline__ void wgmma128(float (&a)[128], uint32_t da, uint32_t db, int scale_d) {
    asm volatile(
        "{\n.reg .pred p;\n.reg .b64 da, db;\nsetp.ne.b32 p, %66, 0;\n"
        "mov.b64 da, {%64, " DESC_HI "};\nmov.b64 db, {%65, " DESC_HI "};\n"
        "wgmma.mma_async.sync.aligned.m64n128k16.f32.bf16.bf16 "
        "{%0,%1,%2,%3,%4,%5,%6,%7,%8,%9,%10,%11,%12,%13,%14,%15,"
        "%16,%17,%18,%19,%20,%21,%22,%23,%24,%25,%26,%27,%28,%29,%30,%31,"
        "%32,%33,%34,%35,%36,%37,%38,%39,%40,%41,%42,%43,%44,%45,%46,%47,"
        "%48,%49,%50,%51,%52,%53,%54,%55,%56,%57,%58,%59,%60,%61,%62,%63},"
        "da, db, p, 1, 1, %67, 0;\n}"
        : R64(a, O)
        : "r"(da), "r"(db), "r"(scale_d), "n"(TA));
}
template <int O>
__device__ __forceinline__ void wgmma128_rs(float (&a)[128], const uint32_t* f, uint32_t db) {
    asm volatile(
        "{\n.reg .b64 db;\nmov.b64 db, {%68, 8};\n"
        "wgmma.mma_async.sync.aligned.m64n128k16.f32.bf16.bf16 "
        "{%0,%1,%2,%3,%4,%5,%6,%7,%8,%9,%10,%11,%12,%13,%14,%15,"
        "%16,%17,%18,%19,%20,%21,%22,%23,%24,%25,%26,%27,%28,%29,%30,%31,"
        "%32,%33,%34,%35,%36,%37,%38,%39,%40,%41,%42,%43,%44,%45,%46,%47,"
        "%48,%49,%50,%51,%52,%53,%54,%55,%56,%57,%58,%59,%60,%61,%62,%63},"
        "{%64, %65, %66, %67}, db, 1, 1, 1, 0;\n}"
        : R64(a, O)
        : "r"(f[0]), "r"(f[1]), "r"(f[2]), "r"(f[3]), "r"(db));
}
template <int O>
__device__ __forceinline__ void fence_regs64(float (&a)[128]) {
    asm volatile("" : R64(a, O)::"memory");
}

struct Params {
    const __nv_bfloat16* x;
    const __nv_bfloat16* dre;
    const __nv_bfloat16* dim;
    const __nv_bfloat16* wr;
    const __nv_bfloat16* wg;
    const __nv_bfloat16* wu;
    const __nv_bfloat16* wd;
    uint32_t zero;
#define AB g_ab
};

__device__ __forceinline__ float warp_sum(float v) {
#pragma unroll
    for (int o = 16; o; o >>= 1) v += __shfl_xor_sync(0xffffffffu, v, o);
    return v;
}
__device__ __forceinline__ void fma8(float* acc, const uint4& w, float s) {
    acc[0] += s * bf_lo(w.x); acc[1] += s * bf_hi(w.x); acc[2] += s * bf_lo(w.y); acc[3] += s * bf_hi(w.y);
    acc[4] += s * bf_lo(w.z); acc[5] += s * bf_hi(w.z); acc[6] += s * bf_lo(w.w); acc[7] += s * bf_hi(w.w);
}
__device__ __forceinline__ int POS(int t) { return (t & ~15) | ((t & 6) << 1) | ((t & 8) >> 2) | (t & 1); }
__host__ __device__ constexpr int PSLOT(int j) { return j < 4 ? j : (j & 1) + ((j & 2) ? 0 : 4); }
__host__ __device__ constexpr int PPAR(int j) { return j < 4 ? 0 : ((j >> 2) ^ (j >> 1) ^ 1) & 1; }
__host__ __device__ constexpr int DSLOT(int it) { return (it & 3) + 2; }
__device__ __forceinline__ int SREC(int t) { return (t & ~15) | ((t & 3) << 2) | ((t >> 2) & 3); }
__device__ __forceinline__ int KO(int cl) { return ((cl & 1) << 1) | (cl >> 1); }

__global__ void __cluster_dims__(2, 1, 1) __launch_bounds__(NTHREADS, 1)
fnet_fused_kernel(const __grid_constant__ CUtensorMap tm_x, const __grid_constant__ CUtensorMap tm_dre,
                  const __grid_constant__ CUtensorMap tm_dim, const __grid_constant__ CUtensorMap tm_cre,
                  const __grid_constant__ CUtensorMap tm_cim, const __grid_constant__ CUtensorMap tm_out,
                  const __grid_constant__ CUtensorMap tm_x64,
                  const Params P) {
    extern __shared__ __align__(1024) uint8_t smem[];
    const unsigned long long tstart = clock64();
    const uint32_t sb = smem_u32(smem);
    const int tid = threadIdx.x, lane = tid & 31;
    const int warp = __shfl_sync(0xffffffffu, tid >> 5, 0);
    const int pr = blockIdx.x >> 1, p7 = ((pr - 36) * 37) >> 8;
    const int c = blockIdx.x & 1;
    const int gi = pr < 4 ? 7 : pr < 36 ? 2 * ((pr - 4) & 7) + (((pr - 4) >> 2) & 1) : 2 * (pr - 36 - 7 * p7) + 1 + (pr - 36 - 7 * p7 > 2);
    const int g = gi & 7;
    const int r = (gi >> 3) * 4 + (pr < 4 ? pr : pr < 36 ? (pr - 4) >> 3 : p7);
#define BLK(n) ((n) - ((n) <= g))
    const int grp = 2 * r + c;
    const int b = g * 16 + grp;
    const uint32_t bar0 = sb + OFF_BAR;
    const uint32_t zero = P.zero;
#define BAR(i) (bar0 + 8u * (i))
#define XBAR(i) (sb + OFF_XB + 64 + 8u * (i))
#define CLUSTER_ARRIVE() asm volatile("barrier.cluster.arrive.relaxed.aligned;" ::: "memory")
#define CLUSTER_WAIT() asm volatile("barrier.cluster.wait.aligned;" ::: "memory")
    if ((sb & 0xffffffu) != SB0) return;

#define LOAD0(it) do { \
            mbar_expect_tx(BAR(B_FS + DSLOT(it)), SLOT); tma_2d(sb + OFF_S + DSLOT(it) * SLOT, tmD, (it) * 64, r * 128, BAR(B_FS + DSLOT(it))); \
            mbar_expect_tx(BAR(B_FL + (it)), SLOT); tma_2d(sb + OFF_L + (it) * SLOT, &tm_x, (it) * 64, g * 256, BAR(B_FL + (it))); \
            mbar_expect_tx(BAR(B_FL + 4 + (it)), SLOT); tma_2d(sb + OFF_L + (4 + (it)) * SLOT, &tm_x, (it) * 64, g * 256 + 128, BAR(B_FL + 4 + (it))); \
        } while (0)
    if (warp == 13) {
        if (elect_one()) {
            const CUtensorMap* tmD = c ? &tm_dim : &tm_dre;
            prefetch_tmap(&tm_x);
            mbar_init(BAR(B_FS + 2), 1); mbar_init(BAR(B_FL), 1); mbar_init(BAR(B_FL + 4), 1);
            asm volatile("fence.mbarrier_init.release.cluster;" ::: "memory");
            LOAD0(0);
        }
        __syncwarp();
    }
    if (warp == 12) {
        if (elect_one()) {
#pragma unroll
            for (int i = 1; i < 4; i++) { mbar_init(BAR(B_FS + 2 + i), 1); mbar_init(BAR(B_FL + i), 1); mbar_init(BAR(B_FL + 4 + i), 1); }
#pragma unroll
            for (int i = 0; i < 4; i++) mbar_init(XBAR(i), 1);
            asm volatile("fence.mbarrier_init.release.cluster;" ::: "memory");
        }
        __syncwarp();
    }
    if (warp == 14) {
        if (elect_one()) {
#pragma unroll
            for (int i = 0; i < 8; i++) { mbar_init(BAR(B_EL + i), 1); mbar_init(XBAR(4 + i), 1); if (i < 6) mbar_init(BAR(B_ES + i), 2); }
            asm volatile("fence.mbarrier_init.release.cluster;" ::: "memory");
        }
        __syncwarp();
    }
    if (warp == 15) {
        if (elect_one()) {
            mbar_init(BAR(B_FS), 1); mbar_init(BAR(B_FS + 1), 1);
#pragma unroll
            for (int i = B_SRD; i < B_COUNT; i++) mbar_init(BAR(i), i == B_GO ? 2 : i == B_STATS || i == B_LST ? 4 : 1);
#pragma unroll
            for (int i = 0; i < 4; i++) mbar_expect_tx(BAR(B_RECV + i), SLOT / 2);
            mbar_expect_tx(BAR(B_PEER), 1024); mbar_expect_tx(BAR(B_H), 128);
            asm volatile("fence.mbarrier_init.release.cluster;" ::: "memory");
        }
        __syncwarp();
    }
    CLUSTER_ARRIVE();

#define GATHER(ptr, cnt, valid) do { int n = 0; bool ok; do { ok = true; \
                _Pragma("unroll") for (int i = 0; i < (cnt); i++) { f[i] = ld_relaxed128((ptr) + i * 32); ok = ok && (valid); } \
                if (__all_sync(0xffffffffu, ok)) break; \
                __nanosleep(GSL); \
            } while (++n < SPIN_LIMIT); } while (0)
    if (warp >= 8 && warp < 12) {
        asm volatile("setmaxnreg.dec.sync.aligned.u32 %0;" ::"n"(512 - PROD_REGS - 2 * CONS_REGS));
        const int aw = warp - 8, mt = tid - 256;
        unsigned ep;
        {
            const uint8_t* rp = smem + OFF_S + aw * 2048 + lane * 16;
            const __nv_bfloat16* dp = at(c ? P.dim : P.dre, (r * 128 + g * 16 + aw * 4) * D_ * 2);
            float wf[32], sw = 0.f;
#pragma unroll
            for (int i = 0; i < 4; i++) {
                const uint4 w = __ldg(reinterpret_cast<const uint4*>(at(P.wr, lane * 16) + i * 256));
                const uint32_t wv[4] = {w.x, w.y, w.z, w.w};
#pragma unroll
                for (int e = 0; e < 4; e++) { wf[8 * i + 2 * e] = bf_lo(wv[e]); wf[8 * i + 2 * e + 1] = bf_hi(wv[e]); sw = (sw + bf_lo(wv[e])) + bf_hi(wv[e]); }
            }
            ep = load_epoch(b);
            sw = warp_sum(sw);
            CLUSTER_WAIT();
            float x0[4] = {}, s1[4] = {}, s2[4] = {}, sx[4] = {}, sd[4] = {};
#define PUSH(a, v) do { a[0] = a[1]; a[1] = a[2]; a[2] = a[3]; a[3] = v; } while (0)
#pragma unroll 1
            for (int k = 0; k < 4; k++) {
                mbar_wait(XBAR(k), 0);
                uint4 v[4];
#pragma unroll
                for (int i = 0; i < 4; i++) v[i] = *reinterpret_cast<const uint4*>(rp + k * 8192 + i * 512);
                uint32_t sh = v[0].x << 16;
                float a1s = 0.f, a2s = 0.f, axs = 0.f;
#pragma unroll
                for (int i = 0; i < 4; i++) {
                    sh = __shfl_sync(0xffffffffu, sh | (__float_as_uint(axs) & zero), 0);
                    const uint32_t xv[4] = {v[i].x, v[i].y, v[i].z, v[i].w};
#pragma unroll
                    for (int e = 0; e < 4; e++) {
                        const float a0 = bf_lo(xv[e]) - __uint_as_float(sh), a1 = bf_hi(xv[e]) - __uint_as_float(sh);
                        a1s += a0 + a1;
                        a2s = fmaf(a0, a0, fmaf(a1, a1, a2s));
                        axs = fmaf(a0, wf[8 * i + 2 * e], fmaf(a1, wf[8 * i + 2 * e + 1], axs));
                    }
                }
                PUSH(x0, __uint_as_float(sh)); PUSH(s1, a1s); PUSH(s2, a2s); PUSH(sx, axs);
                fence_async_smem();
                __syncwarp();
                if (elect_one()) {
                    const uint32_t db = XBAR(k == 3 ? 8 + aw : 4 + aw);
                    if (k == 0 || k == 3) mbar_expect_tx(db, k ? 2048 : 6144);
                    bulk_g2s(sb + OFF_S + k * 8192 + aw * 2048, dp + k * D_, 2048, db);
                }
            }
#define FOLD4(a) do { const bool u16 = lane & 16, u8 = lane & 8; \
                float p0 = (u16 ? a[2] : a[0]) + __shfl_xor_sync(0xffffffffu, u16 ? a[0] : a[2], 16); \
                float p1 = (u16 ? a[3] : a[1]) + __shfl_xor_sync(0xffffffffu, u16 ? a[1] : a[3], 16); \
                a[0] = (u8 ? p1 : p0) + __shfl_xor_sync(0xffffffffu, u8 ? p0 : p1, 8); \
                _Pragma("unroll") for (int o = 4; o; o >>= 1) a[0] += __shfl_xor_sync(0xffffffffu, a[0], o); } while (0)
#pragma unroll 1
            for (int k = 0; k < 4; k++) {
                mbar_wait(XBAR(k == 3 ? 8 + aw : 4 + aw), 0);
                float run = 0.f;
#pragma unroll
                for (int i = 0; i < 4; i++) {
                    const uint4 v = *reinterpret_cast<const uint4*>(rp + k * 8192 + i * 512);
                    const uint32_t dv[4] = {v.x, v.y, v.z, v.w};
#pragma unroll
                    for (int e = 0; e < 4; e++) run += bf_lo(dv[e]) + bf_hi(dv[e]);
                }
                PUSH(sd, run);
            }
            named_bar<4, 128>();
            if (mt < 12) asm volatile("mbarrier.inval.shared::cta.b64 [%0];" ::"r"(XBAR(mt)) : "memory");
            FOLD4(sd); FOLD4(s1); FOLD4(s2); FOLD4(sx);
            const float nb = __shfl_down_sync(0xffffffffu, sd[0], 8);
            if ((lane & 15) == 0)
                st_relaxed128(at(g_rs, (grp * 64 + g * 8 + aw * 2 + (lane >> 4)) * 16), make_uint4(__float_as_uint(sd[0]), ep, __float_as_uint(nb), ep));
            if (mt == 0) PROF_T(6);
            const int rr = lane >> 3;
            const float c0 = rr == 0 ? x0[0] : rr == 1 ? x0[1] : rr == 2 ? x0[2] : x0[3];
            const float dm = s1[0] * (1.0f / D_);
            const float mb = rbf(c0 + dm);
            const float rinv = rcp_f(rbf(sqrt_f(rbf(rbf(fmaxf(s2[0] * (1.0f / D_) - dm * dm, 0.f)) + 1e-5f))));
            if ((lane & 7) == 0) st_relaxed128(at(g_stat, (b * 16 + aw * 4 + rr) * 16), make_uint4(__float_as_uint(mb), __float_as_uint(rinv), ep, 0));
            unsigned u = __bfloat16_as_ushort(__float2bfloat16_rn((sx[0] + (c0 - mb) * sw) * rinv));
            u = (u & 0x8000u) ? (~u & 0xffffu) : (u | 0x8000u);
            u = (u << 16) | (0xffffu - (unsigned)(b * 16 + rr * 4 + aw));
            u = __reduce_max_sync(0xffffffffu, u);
            if (lane == 0) { *reinterpret_cast<unsigned*>(smem + OFF_XB + aw * 4) = u; mbar_arrive(BAR(B_LST)); }
            if (mt == 0) PROF_T(2);
            uint4 f[4];
            if (aw < 2) {
                const int t = SREC(aw * 128 + lane);
                GATHER(at(g_stat, (g * 256 + aw * 128 + lane) * 16), 4, f[i].z == ep);
#pragma unroll
                for (int i = 0; i < 4; i++) {
                    *reinterpret_cast<uint32_t*>(smem + OFF_RSTD + (POS(t) + i * 32) * 4) = f[i].y;
                    *reinterpret_cast<uint16_t*>(smem + OFF_MEAN + (POS(t) + i * 32) * 2) = (uint16_t)(f[i].x >> 16);
                }
            } else {
                const int e2 = (aw - 2) * 32 + lane;
                GATHER(at(g_rs, (grp * 64 + e2) * 16), 1, f[i].y == ep && f[i].w == ep);
#pragma unroll
                for (int i = 0; i < 2; i++) {
                    const float v = __uint_as_float(i ? f[0].z : f[0].x);
                    const float hi = rbf(v), mid = rbf(v - hi), lo = v - hi - mid;
                    *reinterpret_cast<uint4*>(smem + OFF_RS + (e2 * 2 + i) * 16) = make_uint4(pack_bf(hi, mid), pack_bf(lo, 0.f), 0, 0);
                }
            }
            fence_async_smem();
            __syncwarp();
            if (lane == 0) mbar_arrive(BAR(B_STATS));
            if (mt == 127) PROF_T(9);
        }
        const int pair = g * 7 + r;
        if (r < 7) {
            const uint64_t pol = policy_evict_first();
            const __nv_bfloat16* wp = at((aw & 1) ? P.wu : P.wg, ((c * 512 + (aw >> 1) * 256 + (lane >> 3) * 8) * F_ + pair * 64 + (lane & 7) * 8) * 2);
            uint4 b0[8], b1[8];
#define FILL(buf, str) do { _Pragma("unroll") for (int q = 0; q < 8; q++) buf[q] = ldg_stream(wp + q * (str), pol); } while (0)
#define PAUSE() do { if (mbar_test(BAR(B_QUIET), 0)) mbar_wait_sleep(BAR(B_GO), 0); } while (0)
            FILL(b0, F_);
            mbar_wait(BAR(B_SEL), 0);
            uint4 xn;
            {
                const int sel = ~*reinterpret_cast<volatile unsigned*>(smem + OFF_SEL) & (S_ - 1);
                xn = __ldg(reinterpret_cast<const uint4*>(at(P.x, (sel * D_ + c * 512 + (aw >> 1) * 256 + (lane & 7) * 32 + (lane >> 3) * 8) * 2)));
                uint4 f[1];
                GATHER(at(g_stat, SREC(sel) * 16), 1, f[i].z == ep);
                wp += 32 * F_; FILL(b1, F_); wp -= 32 * F_;
                PAUSE();
                const float m = __uint_as_float(f[0].x), ri = __uint_as_float(f[0].y);
                xn = make_uint4(norm2(xn.x, m, ri), norm2(xn.y, m, ri), norm2(xn.z, m, ri), norm2(xn.w, m, ri));
            }
            float ag[8];
#pragma unroll
            for (int i = 0; i < 8; i++) ag[i] = 0.f;
#define ROUND(cur, nxt, rd) do { \
                PAUSE(); \
                if (lane == 0) TRACE(192 + aw * 12 + (rd)); \
                if ((rd) == 7) wp = at(P.wd - 16 * D_, ((pair * 64 + (lane >> 4) * 8) * D_ + c * 512 + aw * 128 + (lane & 15) * 8) * 2); \
                wp = at(wp, ((rd) < 7 ? 64 * F_ : 32 * D_) + (cur[7].x & zero)); \
                if ((rd) & 7) { if ((rd) < 7) FILL(nxt, F_); else if ((rd) < 11) FILL(nxt, D_); } \
                _Pragma("unroll") for (int q = 0; q < 8; q += 2) { \
                    const uint32_t xw = __shfl_sync(0xffffffffu, q == 0 ? xn.x : q == 2 ? xn.y : q == 4 ? xn.z : xn.w, (lane & 24) | ((rd) & 7)); \
                    fma8(ag, cur[q], bf_lo(xw)); \
                    fma8(ag, cur[q + 1], bf_hi(xw)); \
                    if (q < 6) yield(ag[7], zero); \
                } } while (0)
#pragma unroll 1
            for (int rd = 0; rd < 12; rd += 2) {
                ROUND(b0, b1, rd);
                ROUND(b1, b0, rd + 1);
                if (rd == 6 || rd == 10) {
#pragma unroll
                    for (int i = 0; i < 8; i++) ag[i] += __shfl_xor_sync(0xffffffffu, ag[i], 16);
                }
                if (rd == 6) {
#pragma unroll
                    for (int i = 0; i < 8; i++) ag[i] += __shfl_xor_sync(0xffffffffu, ag[i], 8);
                    if (lane < 8) {
                        const uint32_t dst = mapa(sb + OFF_XB + (c * 4 + aw) * 128 + (lane & 3) * 32, lane >> 2), pb = mapa(BAR(B_PEER), lane >> 2);
                        st_async4(dst, __float_as_uint(ag[0]), __float_as_uint(ag[1]), __float_as_uint(ag[2]), __float_as_uint(ag[3]), pb);
                        st_async4(dst + 16, __float_as_uint(ag[4]), __float_as_uint(ag[5]), __float_as_uint(ag[6]), __float_as_uint(ag[7]), pb);
                    }
                    __syncwarp();
                    wp += 16 * D_; FILL(b1, D_); wp -= 16 * D_;
                    if (aw == 3) {
                        mbar_wait_cluster(BAR(B_PEER), 0);
                        const float* ps = reinterpret_cast<const float*>(smem + OFF_XB) + lane;
                        const float go = (ps[0] + ps[64]) + (ps[128] + ps[192]), uo = (ps[32] + ps[96]) + (ps[160] + ps[224]);
                        const float h = rbf(silu_f(rbf(go))) * rbf(uo), ho = __shfl_xor_sync(0xffffffffu, h, 1);
                        asm volatile("st.async.weak.shared::cluster.mbarrier::complete_tx::bytes.b32 [%0], %1, [%2];"
                                     ::"r"(mapa(sb + OFF_H + c * 64 + (lane >> 1) * 4, lane & 1)), "r"((lane & 1) ? pack_bf(ho, h) : pack_bf(h, ho)),
                                       "r"(mapa(BAR(B_H), lane & 1)) : "memory");
                    }
                    mbar_wait_cluster(BAR(B_H), 0);
                    xn = *reinterpret_cast<const uint4*>(smem + OFF_H + (lane & 3) * 32 + (lane >> 4) * 16);
#pragma unroll
                    for (int i = 0; i < 8; i++) ag[i] = 0.f;
                    if (mt == 0) PROF_T(10);
                }
            }
            const int hi = lane >> 4;
            st_relaxed128(at(g_part, pair * 4096 + (c * 8 + aw * 2 + ((lane >> 3) & 1)) * 256 + hi * 128 + (lane & 7) * 16),
                          make_uint4((__float_as_uint(hi ? ag[4] : ag[0]) & ~15u) | (ep & 15u), __float_as_uint(hi ? ag[5] : ag[1]),
                                     __float_as_uint(hi ? ag[6] : ag[2]), __float_as_uint(hi ? ag[7] : ag[3])));
            if (mt == 0) PROF_T(11);
        } else {
            mbar_wait_sleep(BAR(B_SEL), 0);
        }
        const int sel = ~*reinterpret_cast<volatile unsigned*>(smem + OFF_SEL) & (S_ - 1);
        if ((sel >> 8) == g) {
            const int col = (lane & 7) * 8 + ((lane >> 3) & 1) * 4;
            const uint2 xv = __ldg(reinterpret_cast<const uint2*>(at(P.x, (sel * D_ + grp * 64 + col) * 2)));
            uint4 f[1];
            GATHER(at(g_stat, SREC(sel) * 16), 1, f[i].z == ep);
            const uint4 rec = f[0];
            const uint4* src = at(g_part, (aw * 14 + (lane >> 4)) * 4096 + grp * 256 + (lane & 15) * 16);
            if (r == 7) {
                int n = 0;
                while (((ld_relaxed(src) ^ ep) & 15u) != 0 && ++n < SPIN_LIMIT) __nanosleep(500);
            }
            uint4 t[7];
            int n = 0;
            bool ok;
            do {
                ok = true;
#pragma unroll
                for (int u = 0; u < 7; u++) { t[u] = ld_relaxed128(src + u * 512); ok = ok && ((t[u].x ^ ep) & 15u) == 0; }
            } while (!__all_sync(0xffffffffu, ok) && ++n < SPIN_LIMIT);
            float4 a = make_float4(0.f, 0.f, 0.f, 0.f);
#pragma unroll
            for (int u = 0; u < 7; u++) {
                a.x += __uint_as_float(t[u].x & ~15u); a.y += __uint_as_float(t[u].y); a.z += __uint_as_float(t[u].z); a.w += __uint_as_float(t[u].w);
            }
            a.x += __shfl_xor_sync(0xffffffffu, a.x, 16); a.y += __shfl_xor_sync(0xffffffffu, a.y, 16);
            a.z += __shfl_xor_sync(0xffffffffu, a.z, 16); a.w += __shfl_xor_sync(0xffffffffu, a.w, 16);
            float4* park = reinterpret_cast<float4*>(smem + OFF_XB) + (lane & 15);
            if (lane < 16) park[aw * 16] = a;
            named_bar<4, 128>();
            if (aw == 0) {
                const float4 p1 = park[16], p2 = park[32], p3 = park[48];
                a.x = (a.x + p1.x) + (p2.x + p3.x); a.y = (a.y + p1.y) + (p2.y + p3.y);
                a.z = (a.z + p1.z) + (p2.z + p3.z); a.w = (a.w + p1.w) + (p2.w + p3.w);
                unsigned u = *reinterpret_cast<volatile unsigned*>(smem + OFF_SEL) >> 16;
                u = (u & 0x8000u) ? (u & 0x7fffu) : (~u & 0xffffu);
                const float sg = rbf(__fdividef(1.0f, 1.0f + __expf(-__uint_as_float(u << 16))));
                const float m = __uint_as_float(rec.x), ri = __uint_as_float(rec.y);
                const uint32_t n0 = norm2(xv.x, m, ri), n1 = norm2(xv.y, m, ri);
                uint2 o;
                o.x = silu2(pack_bf(bf_lo(n0) + rbf(rbf(a.x) * sg), bf_hi(n0) + rbf(rbf(a.y) * sg)));
                o.y = silu2(pack_bf(bf_lo(n1) + rbf(rbf(a.z) * sg), bf_hi(n1) + rbf(rbf(a.w) * sg)));
                if (lane < 16) *reinterpret_cast<uint2*>(smem + OFF_H + col * 2) = o;
                __syncwarp();
                if (lane == 0) { mbar_arrive(BAR(B_UPD)); PROF_T(12); }
            }
        }
    } else if (warp < 8) {
        asm volatile("setmaxnreg.inc.sync.aligned.u32 %0;" ::"n"(CONS_REGS));
        CLUSTER_WAIT();
        const int wg = warp >> 2, wq = warp & 3;
        const int wt = tid & 127;
        float acc[128];
        const uint32_t fL = BAR(B_FL + 4 * wg), eL = BAR(B_EL + 4 * wg);
        const uint32_t dL = desc_lo(SB0 + OFF_L, 16) + wg * 4096;
        constexpr uint32_t dS = desc_lo(SB0 + OFF_S, 16);
        constexpr uint32_t SL = SLOT >> 4;
#define RELEASE(ls, ss) do { if (wt == 0) { mbar_arrive(eL + 8u * (ls)); mbar_arrive(BAR(B_ES + (ss))); } } while (0)
#define WAIT_FULL(ls, lph, ss, sph) do { mbar_wait(BAR(B_FS + (ss)), sph); mbar_wait(fL + 8u * (ls), lph); } while (0)
#define TURN() do { if (wg) named_bar<6, 256>(); else named_bar<5, 256>(); } while (0)
#define PASS() do { if (wg) named_arrive<5, 256>(); else named_arrive<6, 256>(); } while (0)
#define WG_BAR() do { if (wg) named_bar<2, 128>(); else named_bar<1, 128>(); } while (0)
        if (wg == 1) PASS();

#define MMA1_H(O, s, first) do { _Pragma("unroll") for (int kk = 0; kk < 4; kk++) \
            wgmma128<O, 0>(acc, dL + (s) * SL + kk * 2 + (O) * 8, dS + DSLOT(s) * SL + kk * 2, !((first) && kk == 0)); } while (0)
#define WAIT1(s, ph) WAIT_FULL(s, ph, DSLOT(s), ph)
#define PROBE(ls, lph, ss, sph) (mbar_test(BAR(B_FS + (ss)), sph) & mbar_test(fL + 8u * (ls), lph))
#define REL1(s) RELEASE(s, DSLOT(s))
#pragma unroll 1
        for (int it = 0; it < 12; it++) {
            const int s = it & 3;
            const bool ok = PROBE(s, (it >> 2) & 1, DSLOT(s), (it >> 2) & 1);
            if (it) { wg_wait<0>(); REL1((s + 3) & 3); }
            if (!ok) WAIT1(s, (it >> 2) & 1);
            TURN();
            wg_fence(); MMA1_H(0, s, it == 0); MMA1_H(64, s, it == 0); wg_commit();
            PASS();
            if (it == 0 && tid == 0) PROF_T(16);
        }
        TS(12);
        float rs[4] = {};
        uint32_t nm[8] = {};
#define GET_STATS() do { mbar_wait(BAR(B_STATS), 0); \
            const int p0 = POS(wg * 128 + wq * 16 + (lane >> 2));                   \
            const uint32_t msk = (lane & 3) == 0 ? 0xffffffffu : (lane & 3) == 1 ? 0x0000ffffu : 0u; \
            _Pragma("unroll") for (int i = 0; i < 4; i++) { \
                const int p = p0 + (i & 1) * 2 + (i >> 1) * 64; \
                rs[i] = *reinterpret_cast<const float*>(smem + OFF_RSTD + p * 4); \
                const uint32_t m = *reinterpret_cast<const uint16_t*>(smem + OFF_MEAN + p * 2) ^ 0x8000u; \
                nm[i + (i & 2)] = (m | (m << 16)) & msk; \
            } } while (0)
        const bool early = wg || __all_sync(0xffffffffu, mbar_test(BAR(B_STATS), 0));
        if (early && !wg) GET_STATS();
        WAIT1(0, 1);
        TS(13);
        wg_wait<0>(); REL1(3);
        if (wg) GET_STATS();
        TS(14);
        TURN();
        wg_fence();
        MMA1_H(0, 0, false);
        if (tid == 0) { mbar_arrive(BAR(B_QUIET)); PROF_T(15); }
        WAIT1(1, 1); wg_fence(); MMA1_H(0, 1, false);
        WAIT1(2, 1); wg_fence(); MMA1_H(0, 2, false); wg_commit();
        if (!early) GET_STATS();
        asm volatile("" : "+r"(nm[0]), "+r"(nm[1]), "+r"(nm[2]), "+r"(nm[3]), "+r"(nm[4]), "+r"(nm[5]), "+r"(nm[6]), "+r"(nm[7])::"memory");
        wg_fence();
        wgmma128_rs<64>(acc, nm + 4, (SB0 + OFF_RS) >> 4);
        wgmma128_rs<0>(acc, nm, (SB0 + OFF_RS) >> 4);
        WAIT1(3, 1); wg_fence(); MMA1_H(0, 3, false); wg_commit();
        PASS();
        const int mrow = wq * 16 + ((lane >> 3) & 1) * 8 + (lane & 7);
#define EPI1(O, slot, FREE) do { const uint32_t dst = sb + OFF_S + (slot) * SLOT + mrow * 128; \
            uint32_t pk[32]; \
            _Pragma("unroll") for (int i = 0; i < 32; i += 4) { \
                _Pragma("unroll") for (int k = 0; k < 4; k++) \
                    pk[i + k] = pack_bf(acc[(O) + 2 * (i + k)] * rs[(O) / 32 + (k & 1)], acc[(O) + 2 * (i + k) + 1] * rs[(O) / 32 + (k & 1)]); \
                if (i == EF) { FREE; } \
                if (i >= EF) { _Pragma("unroll") for (int v = (i == EF ? 0 : i); v <= i; v += 4) \
                    stmatrix4(dst + ((v >> 4) ^ c ^ 1) * 8192 + ((((v >> 1) & 7) + (lane >> 4)) ^ (lane & 7)) * 16, pk[v], pk[v + 1], pk[v + 2], pk[v + 3]); } } \
            WG_BAR(); \
            if (wt == 0) mbar_arrive(BAR(B_FS + (slot))); } while (0)
        TS(15);
        wg_wait<0>();
        fence_regs64<0>(acc);
        TS(16);
        {
            constexpr int EF = 0;
            EPI1(0, wg, if (wg) mbar_wait(BAR(B_FS), 0));
        }
        TS(17);
        TURN();
        wg_fence();
        MMA1_H(64, 0, false); wg_commit();
        MMA1_H(64, 1, false); wg_commit();
        MMA1_H(64, 2, false); wg_commit();
        wg_wait<2>(); REL1(0);
        MMA1_H(64, 3, false); wg_commit();
        PASS();
        TS(18);
        wg_wait<2>(); REL1(1);
        mbar_wait(BAR(B_FS), 0); mbar_wait(BAR(B_FS + 1), 0); fence_async_smem();
        wg_wait<1>(); REL1(2);
        wg_wait<0>(); REL1(3);
        fence_regs64<64>(acc);
        TS(19);
        {
            constexpr int EF = 16;
            EPI1(64, 2 + wg, mbar_wait(BAR(B_ES + 2 + wg), 1));
        }
        TS(20);

        float ac2[128];
#define MMA2_H(O, ls, ss, first) do { _Pragma("unroll") for (int kk = 0; kk < 4; kk++) \
            wgmma128<O, 1>(ac2, dS + (ss) * SL + kk * 128 + (O) * 8, dL + (ls) * SL + kk * 2, !((first) && kk == 0)); } while (0)
#define WAIT2(j) WAIT_FULL((j) & 3, ((j) >> 2) & 1, PSLOT(j), PPAR(j))
#define MMA2(j) do { wg_fence(); MMA2_H(0, (j) & 3, PSLOT(j), (j) == 0); MMA2_H(64, (j) & 3, PSLOT(j), (j) == 0); wg_commit(); } while (0)
#define REL2(j) RELEASE((j) & 3, PSLOT(j))
        WAIT2(0); TURN(); MMA2(0);
        WAIT2(1); MMA2(1); PASS();
        TS(21);
        wg_wait<1>(); REL2(0);
        mbar_wait(BAR(B_FS + 2), 0); mbar_wait(BAR(B_FS + 3), 0); fence_async_smem();
        TS(22);
        {
            uint32_t sp = 1;
#pragma unroll 1
            for (int j = 2; j < XJ; j++) {
                const uint32_t ss = PSLOT(j);
                const bool ok = PROBE(j & 3, (j >> 2) & 1, ss, PPAR(j));
                wg_wait<0>(); RELEASE((j - 1) & 3, sp);
                if (!ok) WAIT_FULL(j & 3, (j >> 2) & 1, ss, PPAR(j));
                TURN();
                wg_fence(); MMA2_H(0, j & 3, ss, false); MMA2_H(64, j & 3, ss, false); wg_commit();
                PASS();
                if (j == GOJ && wt == 0) { mbar_arrive(BAR(B_GO)); if (wg == 0) PROF_T(19); }
                sp = ss;
            }
        }
        if (tid == 0) PROF_T(20);
        uint32_t gt[32];
        const uint32_t xrow = sb + OFF_S + 2 * SLOT + wg * 8192 + ((lane >> 4) * 8 + (lane & 7)) * 128 + (((2 * wq + ((lane >> 3) & 1)) ^ (lane & 7)) << 4);
        const uint32_t gsign = c ? 0x80008000u : 0u;
#define XOFF(v) (((v) >> 2) * SLOT + ((v) & 3) * 2048)
        mbar_wait(BAR(B_SEL), 0);
        const int sel = ~*reinterpret_cast<volatile unsigned*>(smem + OFF_SEL) & (S_ - 1);
        bool own = (sel >> 7) == 2 * g + wg;
#define PATCH() do { own = false; \
            const uint32_t v0 = *reinterpret_cast<const uint16_t*>(smem + OFF_H + (wq * 16 + (lane >> 2)) * 2) ^ gsign; \
            const uint32_t v1 = *reinterpret_cast<const uint16_t*>(smem + OFF_H + (wq * 16 + (lane >> 2)) * 2 + 16) ^ gsign; \
            const uint32_t pick = (lane & 3) != ((sel >> 1) & 3) ? 0x3210u : (sel & 1) ? 0x5410u : 0x3254u; \
            _Pragma("unroll") for (int i = 0; i < 16; i++) { \
                const uint32_t m = ((sel >> 3) & 15) == i ? pick : 0x3210u; \
                gt[2 * i] = __byte_perm(gt[2 * i], v0, m); \
                gt[2 * i + 1] = __byte_perm(gt[2 * i + 1], v1, m); \
            } } while (0)
#pragma unroll
        for (int u = 0; u < 8; u++) {
            WAIT2(XJ + u); wg_wait<0>(); REL2(XJ + u - 1); TURN(); MMA2(XJ + u); PASS();
            uint32_t* o = &gt[4 * u];
            if (!(u & 3)) mbar_wait(BAR(B_FS + 2 + (u >> 2)), 1);
            ldmatrix4t(xrow + XOFF(u), o[0], o[1], o[2], o[3]);
            const float4 r4 = *reinterpret_cast<const float4*>(smem + OFF_RSTD + (wg * 128 + u * 16 + (lane & 3) * 4) * 4);
            const uint2 m2 = *reinterpret_cast<const uint2*>(smem + OFF_MEAN + (wg * 128 + u * 16 + (lane & 3) * 4) * 2);
            o[0] = gate2(o[0], m2.x, r4.x, r4.y) ^ gsign;
            o[1] = gate2(o[1], m2.x, r4.x, r4.y) ^ gsign;
            o[2] = gate2(o[2], m2.y, r4.z, r4.w) ^ gsign;
            o[3] = gate2(o[3], m2.y, r4.z, r4.w) ^ gsign;
            asm volatile("st.shared.v2.u32 [%0], {%1,%2};" ::"r"(sb + OFF_SEL + 16), "r"(o[0] ^ o[1]), "r"(o[2] ^ o[3]) : "memory");
        }
        if (tid == 0) PROF_T(21);
        WAIT2(28);
        wg_wait<0>(); REL2(27);
        if (own) {
            const uint32_t t0 = clock32();
            bool ok;
            while (!(ok = mbar_test(BAR(B_UPD), 0)) && clock32() - t0 < wg * 1400u) __nanosleep(50);
            if (__all_sync(0xffffffffu, ok)) PATCH();
        }
        TS(0);
        TURN();
        wg_fence(); MMA2_H(0, 0, PSLOT(28), false); wg_commit();
        if (wg == 0) { wg_fence(); MMA2_H(64, 0, PSLOT(28), false); wg_commit(); }
        WAIT2(29); wg_fence(); MMA2_H(0, 1, PSLOT(29), false); wg_commit();
        WAIT2(30); wg_fence(); MMA2_H(0, 2, PSLOT(30), false); wg_commit();
        wg_wait<2>();
        if (tid == 0) mbar_arrive_cluster(mapa(BAR(B_RDY), c ^ 1));
        WAIT2(31); wg_fence(); MMA2_H(0, 3, PSLOT(31), false); wg_commit();
        TS(1);
#define KEEP(i) wgmma128<64, 1>(ac2, dS + PSLOT(29 + ((i) >> 2)) * SL + ((i) & 3) * 128 + 512, dL + (1 + ((i) >> 2)) * SL + ((i) & 3) * 2, 1)
        wg_fence();
#pragma unroll
        for (int i = 0; i < KQ; i++) KEEP(i);
        wg_commit();
        mbar_wait(BAR(B_RDY + wg), 0);
        wg_wait<1>();
        fence_regs64<0>(ac2);
        TS(2);
        wg_fence();
        {
            const uint32_t dst = mapa(sb + OFF_L + wg * SLOT + wt * 16, c ^ 1), rb = mapa(BAR(B_RECV + 2 * wg), c ^ 1);
#pragma unroll
            for (int v = 0; v < 8; v++) {
                if (KQ + v < 12) KEEP(KQ + v);
                if (KQ + v == 11) { wg_commit(); if (wg == 0) PASS(); }
                st_async4(dst + v * 2048, pack_bf(ac2[8 * v + 0], ac2[8 * v + 1]), pack_bf(ac2[8 * v + 2], ac2[8 * v + 3]),
                          pack_bf(ac2[8 * v + 4], ac2[8 * v + 5]), pack_bf(ac2[8 * v + 6], ac2[8 * v + 7]), rb + (v >> 2) * 8);
            }
        }
        if (wg == 1) { wg_fence(); MMA2_H(64, 0, PSLOT(28), false); wg_commit(); }
        TS(3);
        uint32_t xr[32];
#define LDX(v) ldmatrix4t(xrow + XOFF(v), xr[4 * (v)], xr[4 * (v) + 1], xr[4 * (v) + 2], xr[4 * (v) + 3])
#pragma unroll
        for (int v = 0; v < XE; v++) LDX(v);
        if (wg == 0) {
            wg_wait<0>();
            if (wt == 0) mbar_arrive_cluster(mapa(BAR(B_RDY + 1), c ^ 1));
        }
        TS(4);
        if (own) { mbar_wait(BAR(B_UPD), 0); PATCH(); }
        TS(5);
        uint4 rv[8];
#define FETCH(v0) do { if ((v0) == 0 || (v0) == 4) mbar_wait_cluster(BAR(B_RECV + 2 * wg + (v0) / 4), 0); \
            _Pragma("unroll") for (int v = (v0); v < (v0) + 2; v++) { \
                asm volatile("ld.shared.v4.u32 {%0,%1,%2,%3}, [%4];" : "=r"(rv[v].x), "=r"(rv[v].y), "=r"(rv[v].z), "=r"(rv[v].w) \
                             : "r"(sb + OFF_L + wg * SLOT + v * 2048 + wt * 16) : "memory"); \
                if (v >= XE) LDX(v); } } while (0)
        FETCH(0);
        TS(6);
        wg_wait<0>();
        fence_regs64<64>(ac2);
        TS(7);
#pragma unroll
        for (int v0 = 0; v0 < 8; v0 += 2) {
#pragma unroll
            for (int v = v0; v < v0 + 2; v++) {
                const float* a = &ac2[64 + 8 * v];
                stmatrix4t(xrow + XOFF(v),
                           bfma2(bsub2(pack_bf(a[0], a[1]), rv[v].x), gt[4 * v + 0], xr[4 * v + 0]),
                           bfma2(bsub2(pack_bf(a[2], a[3]), rv[v].y), gt[4 * v + 1], xr[4 * v + 1]),
                           bfma2(bsub2(pack_bf(a[4], a[5]), rv[v].z), gt[4 * v + 2], xr[4 * v + 2]),
                           bfma2(bsub2(pack_bf(a[6], a[7]), rv[v].w), gt[4 * v + 3], xr[4 * v + 3]));
            }
            WG_BAR();
            if (wt == 0) mbar_arrive(eL + 4 * v0);
            if (v0 + 2 < 8) FETCH(v0 + 2);
            if (v0 == 0) TS(8);
        }
        TS(9);
    } else {
        asm volatile("setmaxnreg.dec.sync.aligned.u32 %0;" ::"n"(PROD_REGS));
#define XROWS(k) do { mbar_expect_tx(XBAR(k), 8192); bulk_g2s(sb + OFF_S + (k) * 8192, at(P.x, (b * 16 + (k) * 4) * D_ * 2), 8192, XBAR(k)); } while (0)
        if (warp == 12) {
            if (elect_one()) {
                const CUtensorMap* tmD = c ? &tm_dim : &tm_dre;
#pragma unroll 1
                for (int it = 1; it < 4; it++) {
                    while (clock32() - (uint32_t)tstart < LDEL + (it - 1) * LGAP) {}
                    LOAD0(it);
                    if (it >= X0) XROWS(it - X0);
                }
            }
            __syncwarp();
        }
        CLUSTER_WAIT();
        if (warp == 12) {
            if (elect_one()) {
                const CUtensorMap* tmD = c ? &tm_dim : &tm_dre;
#pragma unroll 1
                for (int it = 4; it < 16; it++) {
                    const int s = DSLOT(it);
                    mbar_wait(BAR(B_ES + s), ((it >> 2) & 1) ^ 1);
                    TRACE(it);
                    mbar_expect_tx(BAR(B_FS + s), SLOT);
                    tma_2d(sb + OFF_S + s * SLOT, tmD, it * 64, r * 128, BAR(B_FS + s));
                    if (it < 4 + X0) XROWS(it - X0);
                }
                const unsigned ep = load_epoch(b), e8 = ep & 0xffu;
                const uint8_t* abg = at(AB, grp * 32 * SLOT);
                const unsigned long long* fl = at(g_flag, grp * 128);
                unsigned long long rdy = ld_acquire64(fl);
                mbar_wait(BAR(B_SRD), 0);
                st_release8(at(g_flag, grp * 128 + g), e8);
                PROF_T(7);
                int j = 4;
#pragma unroll 1
                for (int cl = 0; cl < 4; cl++) {
                    if (cl) rdy = ld_acquire64(++fl);
                    fence_async_global();
#pragma unroll 1
                    for (int n = 1; n < 8; n++, j++) {
                        const int q = BLK(n), s = (j & 1) + ((j & 2) ? 0 : 4);
                        mbar_wait(BAR(B_ES + s), ((j >> 2) ^ (j >> 1)) & 1);
                        if (j == 7) mbar_wait(BAR(B_SRD + 1), 0);
                        if (((unsigned)(rdy >> (8 * q)) & 0xffu) != e8) {
                            int m = 0;
                            do { rdy = ld_acquire64(fl); } while (((unsigned)(rdy >> (8 * q)) & 0xffu) != e8 && ++m < SPIN_LIMIT);
                            fence_async_global();
                        }
                        TRACE(16 + j);
                        mbar_expect_tx(BAR(B_FS + s), SLOT);
                        bulk_g2s(sb + OFF_S + s * SLOT, at(abg, (4 * q + KO(cl)) * SLOT), SLOT, BAR(B_FS + s));
                    }
                }
                *at(g_epoch, b * 4) = ep;
            }
        } else if (warp < 15) {
            if (elect_one()) {
                const int w = warp - 13, row0 = g * 256 + w * 128;
                const CUtensorMap* tmC = c ? &tm_cim : &tm_cre;
                const uint32_t fb = BAR(B_FL + 4 * w), eb = BAR(B_EL + 4 * w), dst = sb + OFF_L + w * 4 * SLOT;
                [[maybe_unused]] unsigned long long mk = 0, mg = 0;
                int n = 0, cl = 0;
#pragma unroll 1
                for (int it = 4; it < 48; it++) {
                    const int s = it & 3;
                    mbar_wait(eb + 8 * s, ((it >> 2) & 1) ^ 1);
                    TRACE(64 + w * 64 + it - 4);
                    MARK(it);
                    mbar_expect_tx(fb + 8 * s, SLOT);
                    tma_2d(dst + s * SLOT, it < 16 ? &tm_x : tmC, (it < 16 ? it : 4 * (n ? BLK(n) : g) + KO(cl)) * 64, row0, fb + 8 * s);
                    if (it == PTJ) prefetch_tmap(w ? &tm_x64 : tmC);
                    if (it == PTJ && w) prefetch_tmap(&tm_out);
                    if (it >= 16) {
                        if (it == 19) { n = 1; cl = 0; } else if (it < 19) cl++; else if (++n == 8) { n = 1; cl++; }
                    }
                }
#pragma unroll 1
                for (int h = 0; h < 4; h++) {
                    mbar_wait(eb + 8 * h, 1);
                    fence_async_smem();
                    tma_2d_store(&tm_out, grp * 64, row0 + h * 32, sb + OFF_S + (2 + (h >> 1)) * SLOT + w * 8192 + (h & 1) * 4096);
                    bulk_commit();
                }
                FINISH(w);
            }
        } else {
            const unsigned ep = load_epoch(b);
            uint4 f[4];
            {
                sleep_until((uint32_t)tstart + 6000);
                const uint4* keys = at(reinterpret_cast<const uint4*>(g_key), lane * 16);
                bool mine = false;
                int n = 0;
                do {
                    f[0] = ld_relaxed128(keys); f[1] = ld_relaxed128(keys + 32);
                    if (__all_sync(0xffffffffu, f[0].y == ep && f[0].w == ep && f[1].y == ep && f[1].w == ep)) break;
                    if (!mine) {
                        mbar_wait(BAR(B_LST), 0);
                        const uint4 k = *reinterpret_cast<const uint4*>(smem + OFF_XB);
                        if (lane == 0) st_relaxed64(at(g_key, b * 8), ((unsigned long long)ep << 32) | max(max(k.x, k.y), max(k.z, k.w)));
                        mine = true;
                    }
                    __nanosleep(GSL);
                } while (++n < SPIN_LIMIT);
                const unsigned key = __reduce_max_sync(0xffffffffu, max(max(f[0].x, f[0].z), max(f[1].x, f[1].z)));
                if (lane == 0) { *reinterpret_cast<unsigned*>(smem + OFF_SEL) = key; mbar_arrive(BAR(B_SEL)); PROF_T(8); }
            }
            if (elect_one()) {
#pragma unroll 1
                for (int cl = 0; cl < 4; cl++) {
                    uint8_t* dst = at(AB, (grp * 32 + 4 * g + KO(cl)) * SLOT);
                    const uint32_t src = sb + OFF_S + cl * SLOT, chunk = cl ? 1024 : SLOT;
                    mbar_wait(BAR(B_FS + cl), 0);
                    fence_async_smem();
                    if (cl == 0) PROF_T(3);
                    uint32_t t0 = clock32() + (cl == 1 ? PDEL : 0);
#pragma unroll 1
                    for (uint32_t o = 0; o < SLOT; o += chunk) {
                        sleep_until(t0);
                        bulk_s2g(dst + o, src + o, chunk);
                        bulk_commit();
                        t0 += cl == 1 ? PGAP1 : cl == 2 ? PGAP2 : PGAP3;
                    }
                    bulk_wait<0>();
                    TRACE(252 + cl);
                    if (cl < 2) mbar_arrive(BAR(B_SRD + cl));
                    else {
                        mbar_wait(BAR(B_ES + cl), 0);
                        mbar_expect_tx(BAR(B_FS + cl), SLOT);
                        tma_2d(src, &tm_x64, grp * 64, g * 256 + (cl - 2) * 64, BAR(B_FS + cl));
                        tma_2d(src + 8192, &tm_x64, grp * 64, g * 256 + (cl - 2) * 64 + 128, BAR(B_FS + cl));
                    }
                    if (cl) st_release8(at(g_flag, grp * 128 + cl * 8 + g), ep & 0xffu);
                    if (cl == 1) PROF_T(5);
                    if (cl == 3) PROF_T(4);
                }
            }
        }
    }
}

typedef CUresult (*EncodeFn)(CUtensorMap*, CUtensorMapDataType, cuuint32_t, void*, const cuuint64_t*, const cuuint64_t*,
                             const cuuint32_t*, const cuuint32_t*, CUtensorMapInterleave, CUtensorMapSwizzle,
                             CUtensorMapL2promotion, CUtensorMapFloatOOBfill);

void make_map(EncodeFn fn, CUtensorMap* tm, const void* p, uint64_t rows, uint64_t cols, uint32_t box_rows) {
    cuuint64_t dims[2] = {cols, rows};
    cuuint64_t strides[1] = {cols * 2};
    cuuint32_t box[2] = {64, box_rows};
    cuuint32_t es[2] = {1, 1};
    fn(tm, CU_TENSOR_MAP_DATA_TYPE_BFLOAT16, 2, const_cast<void*>(p), dims, strides, box, es, CU_TENSOR_MAP_INTERLEAVE_NONE,
       CU_TENSOR_MAP_SWIZZLE_128B, CU_TENSOR_MAP_L2_PROMOTION_L2_128B, CU_TENSOR_MAP_FLOAT_OOB_FILL_NONE);
}

}

extern "C" void kernel_launch(void* const* d_in, const int* in_sizes, int n_in, void* d_out, int out_size) {
    (void)in_sizes; (void)n_in; (void)out_size;
    static EncodeFn fn = nullptr;
    if (!fn) {
        void* p = nullptr;
        cudaDriverEntryPointQueryResult q;
        cudaGetDriverEntryPoint("cuTensorMapEncodeTiled", &p, cudaEnableDefault, &q);
        fn = (EncodeFn)p;
        cudaFuncSetAttribute(fnet_fused_kernel, cudaFuncAttributeMaxDynamicSharedMemorySize, SMEM_BYTES);
    }
    CUtensorMap tx, tdre, tdim, tcre, tcim, tout, tx64;
    make_map(fn, &tx, d_in[0], S_, D_, 128);
    make_map(fn, &tcre, d_in[1], S_, S_, 128);
    make_map(fn, &tcim, d_in[2], S_, S_, 128);
    make_map(fn, &tdre, d_in[3], D_, D_, 128);
    make_map(fn, &tdim, d_in[4], D_, D_, 128);
    make_map(fn, &tx64, d_in[0], S_, D_, 64);
    make_map(fn, &tout, d_out, S_, D_, 32);
    Params P;
    P.x = (const __nv_bfloat16*)d_in[0];
    P.dre = (const __nv_bfloat16*)d_in[3];
    P.dim = (const __nv_bfloat16*)d_in[4];
    P.wr = (const __nv_bfloat16*)d_in[6];
    P.wg = (const __nv_bfloat16*)d_in[7];
    P.wu = (const __nv_bfloat16*)d_in[8];
    P.wd = (const __nv_bfloat16*)d_in[9];
    P.zero = 0;
    fnet_fused_kernel<<<NCTA, NTHREADS, SMEM_BYTES, cudaStreamPerThread>>>(tx, tdre, tdim, tcre, tcim, tout, tx64, P);
}
```

```cpp
#include <cuda_runtime.h>
#include <cuda_bf16.h>
#include <cuda.h>
#include <stdint.h>

#define GSL 200
#define SLEEP_NS 200
#define PDEL 1000
#define PGAP1 200
#define PGAP2 200
#define PGAP3 240
#define GOJ 2
#define LDEL 1300
#define LGAP 750
#define PTJ 10
#define X0 2
#define KQ 5
#define XE 2
#define PROD_REGS 32
#define CONS_REGS 184

namespace {

constexpr int S_ = 2048, D_ = 1024, F_ = 3584;
constexpr int NCTA = 128;
constexpr int XJ = 20;
constexpr uint32_t SLOT = 16384;
constexpr uint32_t OFF_L = 0;
constexpr uint32_t OFF_S = 8 * SLOT;
constexpr uint32_t OFF_RS = OFF_S + SLOT;
constexpr uint32_t OFF_BAR = 14 * SLOT;
constexpr uint32_t OFF_SEL = OFF_BAR + 360;
constexpr uint32_t OFF_RSTD = OFF_BAR + 384;
constexpr uint32_t OFF_MEAN = OFF_RSTD + 1024;
constexpr uint32_t OFF_XB = OFF_MEAN + 512;
constexpr uint32_t OFF_H = OFF_XB + 1024;
constexpr uint32_t SMEM_BYTES = OFF_H + 128;
constexpr uint32_t SB0 = 1024;
constexpr int NTHREADS = 512;
static_assert(SMEM_BYTES <= 232448, "smem");

enum { B_FS = 0, B_ES = 6, B_FL = 12, B_EL = 20, B_SRD = 28, B_RECV = 30  , B_RDY = 34, B_STATS = 36, B_LST = 37, B_UPD = 38,
       B_QUIET = 39, B_GO = 40, B_PEER = 41, B_SEL = 42, B_H = 43, B_COUNT = 44 };
static_assert(B_COUNT * 8 <= 360, "barriers");

__device__ __align__(1024) uint8_t g_ab[16u * 32u * SLOT];
__device__ __align__(128) uint4 g_part[56 * (D_ / 4)];
__device__ __align__(128) uint4 g_stat[S_];
__device__ __align__(128) uint4 g_rs[D_];
__device__ __align__(128) unsigned long long g_key[NCTA];
__device__ __align__(128) unsigned long long g_flag[16 * 16];
__device__ __align__(128) unsigned g_epoch[NCTA];
#define PROF_T(i) do {} while (0)
#define TRACE(i) do {} while (0)
#define PROF_G(i) do {} while (0)
#define TS(i) do {} while (0)
#define FINISH(wg) bulk_wait_read<0>()

#define MARK(it) do {} while (0)

__device__ __forceinline__ uint32_t smem_u32(const void* p) { return (uint32_t)__cvta_generic_to_shared(p); }
__device__ __forceinline__ void mbar_init(uint32_t bar, uint32_t cnt) {
    asm volatile("mbarrier.init.shared::cta.b64 [%0], %1;" ::"r"(bar), "r"(cnt) : "memory");
}
__device__ __forceinline__ bool mbar_try(uint32_t bar, uint32_t parity) {
    uint32_t ok;
    asm volatile("{\n.reg .pred p;\nmbarrier.try_wait.parity.shared::cta.b64 p, [%1], %2;\nselp.u32 %0, 1, 0, p;\n}"
                 : "=r"(ok) : "r"(bar), "r"(parity) : "memory");
    return ok;
}
__device__ __forceinline__ bool mbar_test(uint32_t bar, uint32_t parity) {
    uint32_t ok;
    asm volatile("{\n.reg .pred p;\nmbarrier.test_wait.parity.shared::cta.b64 p, [%1], %2;\nselp.u32 %0, 1, 0, p;\n}"
                 : "=r"(ok) : "r"(bar), "r"(parity) : "memory");
    return ok;
}
__device__ __forceinline__ bool mbar_try_cluster(uint32_t bar, uint32_t parity) {
    uint32_t ok;
    asm volatile("{\n.reg .pred p;\nmbarrier.try_wait.parity.acquire.cluster.shared::cta.b64 p, [%1], %2;\nselp.u32 %0, 1, 0, p;\n}"
                 : "=r"(ok) : "r"(bar), "r"(parity) : "memory");
    return ok;
}
constexpr int SPIN_LIMIT = 1 << 20;
__device__ __forceinline__ void mbar_wait(uint32_t bar, uint32_t parity) {
    if (mbar_try(bar, parity)) return;
    int n = 0;
    while (!mbar_try(bar, parity) && ++n < SPIN_LIMIT) {}
}
__device__ __forceinline__ void mbar_wait_cluster(uint32_t bar, uint32_t parity) {
    int n = 0;
    while (!mbar_try_cluster(bar, parity) && ++n < SPIN_LIMIT) {}
}
__device__ __forceinline__ void mbar_wait_sleep(uint32_t bar, uint32_t parity) {
    int n = 0;
    while (!mbar_try(bar, parity) && ++n < SPIN_LIMIT) __nanosleep(SLEEP_NS);
}
__device__ __forceinline__ void mbar_arrive(uint32_t bar) {
    asm volatile("mbarrier.arrive.shared::cta.b64 _, [%0];" ::"r"(bar) : "memory");
}
__device__ __forceinline__ void mbar_arrive_cluster(uint32_t cluster_bar) {
    asm volatile("mbarrier.arrive.shared::cluster.b64 _, [%0];" ::"r"(cluster_bar) : "memory");
}
__device__ __forceinline__ void mbar_expect_tx(uint32_t bar, uint32_t bytes) {
    asm volatile("mbarrier.arrive.expect_tx.shared::cta.b64 _, [%0], %1;" ::"r"(bar), "r"(bytes) : "memory");
}
__device__ __forceinline__ bool elect_one() {
    uint32_t p;
    asm volatile("{\n.reg .pred p;\nelect.sync _|p, 0xffffffff;\nselp.u32 %0, 1, 0, p;\n}" : "=r"(p));
    return p;
}
__device__ __forceinline__ uint32_t mapa(uint32_t addr, uint32_t rank) {
    uint32_t r;
    asm("mapa.shared::cluster.u32 %0, %1, %2;" : "=r"(r) : "r"(addr), "r"(rank));
    return r;
}
__device__ __forceinline__ uint32_t clock32() { uint32_t t; asm volatile("mov.u32 %0, %%clock;" : "=r"(t)); return t; }
__device__ __forceinline__ void sleep_until(uint32_t t) {
    int n = 0;
    while ((int)(clock32() - t) < 0 && ++n < SPIN_LIMIT) __nanosleep(20);
}
__device__ __forceinline__ void yield(float last, uint32_t zero) {
    asm volatile("nanosleep.u32 %0;" ::"r"(__float_as_uint(last) & zero));
}
template <typename T> __device__ __forceinline__ T* at(T* p, uint32_t bytes) {
    asm("" : "+r"(bytes));
    return reinterpret_cast<T*>(reinterpret_cast<uintptr_t>(p) + bytes);
}
__device__ __forceinline__ void tma_2d(uint32_t dst, const CUtensorMap* tm, int c0, int c1, uint32_t bar) {
    asm volatile("cp.async.bulk.tensor.2d.shared::cluster.global.mbarrier::complete_tx::bytes [%0], [%1, {%3, %4}], [%2];"
                 ::"r"(dst), "l"(tm), "r"(bar), "r"(c0), "r"(c1) : "memory");
}
__device__ __forceinline__ void tma_2d_store(const CUtensorMap* tm, int c0, int c1, uint32_t src) {
    asm volatile("cp.async.bulk.tensor.2d.global.shared::cta.bulk_group [%0, {%2, %3}], [%1];"
                 ::"l"(tm), "r"(src), "r"(c0), "r"(c1) : "memory");
}
__device__ __forceinline__ void bulk_g2s(uint32_t dst, const void* src, uint32_t bytes, uint32_t bar) {
    asm volatile("cp.async.bulk.shared::cluster.global.mbarrier::complete_tx::bytes [%0], [%1], %2, [%3];"
                 ::"r"(dst), "l"(src), "r"(bytes), "r"(bar) : "memory");
}
__device__ __forceinline__ void bulk_s2g(void* dst, uint32_t src, uint32_t bytes) {
    asm volatile("cp.async.bulk.global.shared::cta.bulk_group [%0], [%1], %2;" ::"l"(dst), "r"(src), "r"(bytes) : "memory");
}
__device__ __forceinline__ void st_async4(uint32_t dst, uint32_t a, uint32_t b, uint32_t c, uint32_t d, uint32_t bar) {
    asm volatile("st.async.weak.shared::cluster.mbarrier::complete_tx::bytes.v4.b32 [%0], {%1,%2,%3,%4}, [%5];"
                 ::"r"(dst), "r"(a), "r"(b), "r"(c), "r"(d), "r"(bar) : "memory");
}
__device__ __forceinline__ void bulk_commit() { asm volatile("cp.async.bulk.commit_group;" ::: "memory"); }
template <int N> __device__ __forceinline__ void bulk_wait_read() { asm volatile("cp.async.bulk.wait_group.read %0;" ::"n"(N) : "memory"); }
template <int N> __device__ __forceinline__ void bulk_wait() { asm volatile("cp.async.bulk.wait_group %0;" ::"n"(N) : "memory"); }
__device__ __forceinline__ void fence_async_smem() { asm volatile("fence.proxy.async.shared::cta;" ::: "memory"); }
__device__ __forceinline__ void fence_async_global() { asm volatile("fence.proxy.async.global;" ::: "memory"); }
__device__ __forceinline__ void prefetch_tmap(const CUtensorMap* tm) {
    asm volatile("prefetch.tensormap [%0];" ::"l"(tm) : "memory");
}
__device__ __forceinline__ unsigned long long ld_acquire64(const unsigned long long* p) {
    unsigned long long v; asm volatile("ld.acquire.gpu.global.u64 %0, [%1];" : "=l"(v) : "l"(p) : "memory"); return v;
}
__device__ __forceinline__ unsigned load_epoch(int b) {
    unsigned v; asm volatile("ld.global.u32 %0, [%1];" : "=r"(v) : "l"(at(g_epoch, b * 4)) : "memory"); return v + 1;
}
__device__ __forceinline__ unsigned ld_relaxed(const void* p) {
    unsigned v; asm volatile("ld.relaxed.gpu.global.u32 %0, [%1];" : "=r"(v) : "l"(p) : "memory"); return v;
}
__device__ __forceinline__ uint4 ld_relaxed128(const uint4* p) {
    uint4 v;
    asm volatile("{\n.reg .b128 t;\n.reg .b64 lo, hi;\nld.relaxed.gpu.global.b128 t, [%4];\nmov.b128 {lo, hi}, t;\n"
                 "mov.b64 {%0, %1}, lo;\nmov.b64 {%2, %3}, hi;\n}"
                 : "=r"(v.x), "=r"(v.y), "=r"(v.z), "=r"(v.w) : "l"(p) : "memory");
    return v;
}
__device__ __forceinline__ void st_relaxed128(uint4* p, const uint4& v) {
    asm volatile("{\n.reg .b128 t;\n.reg .b64 lo, hi;\nmov.b64 lo, {%1, %2};\nmov.b64 hi, {%3, %4};\nmov.b128 t, {lo, hi};\n"
                 "st.relaxed.gpu.global.b128 [%0], t;\n}"
                 ::"l"(p), "r"(v.x), "r"(v.y), "r"(v.z), "r"(v.w) : "memory");
}
__device__ __forceinline__ void st_relaxed64(unsigned long long* p, unsigned long long v) {
    asm volatile("st.relaxed.gpu.global.u64 [%0], %1;" ::"l"(p), "l"(v) : "memory");
}
__device__ __forceinline__ void st_release8(void* p, unsigned v) {
    asm volatile("st.release.gpu.global.u8 [%0], %1;" ::"l"(p), "r"(v) : "memory");
}
__device__ __forceinline__ uint64_t policy_evict_first() {
    uint64_t pol;
    asm("createpolicy.fractional.L2::evict_first.b64 %0, 1.0;" : "=l"(pol));
    return pol;
}
__device__ __forceinline__ uint4 ldg_stream(const void* p, uint64_t pol) {
    uint4 v;
    asm volatile("ld.global.nc.L1::no_allocate.L2::cache_hint.v4.u32 {%0,%1,%2,%3}, [%4], %5;"
                 : "=r"(v.x), "=r"(v.y), "=r"(v.z), "=r"(v.w) : "l"(p), "l"(pol));
    return v;
}
template <int ID, int N> __device__ __forceinline__ void named_arrive() { asm volatile("bar.arrive %0, %1;" ::"n"(ID), "n"(N) : "memory"); }
template <int ID, int N> __device__ __forceinline__ void named_bar() { asm volatile("bar.sync %0, %1;" ::"n"(ID), "n"(N) : "memory"); }

__device__ __forceinline__ float bf_lo(uint32_t u) { return __uint_as_float(u << 16); }
__device__ __forceinline__ float bf_hi(uint32_t u) { return __uint_as_float(u & 0xffff0000u); }
__device__ __forceinline__ uint32_t pack_bf(float lo, float hi) {
    uint32_t r; asm("cvt.rn.bf16x2.f32 %0, %1, %2;" : "=r"(r) : "f"(hi), "f"(lo)); return r;
}
__device__ __forceinline__ float rbf(float v) { return __uint_as_float(pack_bf(0.f, v)); }
__device__ __forceinline__ float sqrt_f(float v) { float r; asm("sqrt.approx.f32 %0, %1;" : "=f"(r) : "f"(v)); return r; }
__device__ __forceinline__ float rcp_f(float v) { float r; asm("rcp.approx.f32 %0, %1;" : "=f"(r) : "f"(v)); return r; }
__device__ __forceinline__ float silu_f(float z) { return __fdividef(z, 1.0f + __expf(-z)); }
__device__ __forceinline__ uint32_t bsub2(uint32_t a, uint32_t b) {
    uint32_t r; asm("sub.rn.bf16x2 %0, %1, %2;" : "=r"(r) : "r"(a), "r"(b)); return r;
}
__device__ __forceinline__ uint32_t bfma2(uint32_t a, uint32_t b, uint32_t c) {
    uint32_t r; asm("fma.rn.bf16x2 %0, %1, %2, %3;" : "=r"(r) : "r"(a), "r"(b), "r"(c)); return r;
}
__device__ __forceinline__ uint32_t norm2(uint32_t xv, float m, float rinv) {
    uint32_t t = pack_bf(bf_lo(xv) - m, bf_hi(xv) - m);
    return pack_bf(bf_lo(t) * rinv, bf_hi(t) * rinv);
}
__device__ __forceinline__ float gate1(float z) {
    float t;
    const float h = 0.5f * z;
    asm("tanh.approx.f32 %0, %1;" : "=f"(t) : "f"(h));
    return fmaf(h, t, h);
}
__device__ __forceinline__ uint32_t gate2(uint32_t xv, uint32_t mean2, float r0, float r1) {
    const uint32_t t = bsub2(xv, mean2);
    return pack_bf(gate1(bf_lo(t) * r0), gate1(bf_hi(t) * r1));
}
__device__ __forceinline__ uint32_t silu2(uint32_t z) { return pack_bf(silu_f(bf_lo(z)), silu_f(bf_hi(z))); }

__device__ __forceinline__ void stmatrix4(uint32_t addr, uint32_t r0, uint32_t r1, uint32_t r2, uint32_t r3) {
    asm volatile("stmatrix.sync.aligned.m8n8.x4.shared.b16 [%0], {%1,%2,%3,%4};"
                 ::"r"(addr), "r"(r0), "r"(r1), "r"(r2), "r"(r3));
}
__device__ __forceinline__ void stmatrix4t(uint32_t addr, uint32_t r0, uint32_t r1, uint32_t r2, uint32_t r3) {
    asm volatile("stmatrix.sync.aligned.m8n8.x4.trans.shared.b16 [%0], {%1,%2,%3,%4};"
                 ::"r"(addr), "r"(r0), "r"(r1), "r"(r2), "r"(r3));
}
__device__ __forceinline__ void ldmatrix4t(uint32_t addr, uint32_t& r0, uint32_t& r1, uint32_t& r2, uint32_t& r3) {
    asm volatile("ldmatrix.sync.aligned.m8n8.x4.trans.shared.b16 {%0,%1,%2,%3}, [%4];"
                 : "=r"(r0), "=r"(r1), "=r"(r2), "=r"(r3) : "r"(addr));
}

__device__ __forceinline__ void wg_fence() { asm volatile("wgmma.fence.sync.aligned;" ::: "memory"); }
__device__ __forceinline__ void wg_commit() { asm volatile("wgmma.commit_group.sync.aligned;" ::: "memory"); }
template <int N> __device__ __forceinline__ void wg_wait() { asm volatile("wgmma.wait_group.sync.aligned %0;" ::"n"(N) : "memory"); }

__host__ __device__ constexpr uint32_t desc_lo(uint32_t addr, uint32_t lbo) { return ((addr & 0x3FFFF) >> 4) | ((lbo >> 4) << 16); }
#define DESC_HI "0x40000040"

#define R8(a, o) "+f"(a[(o) + 0]), "+f"(a[(o) + 1]), "+f"(a[(o) + 2]), "+f"(a[(o) + 3]), \
                 "+f"(a[(o) + 4]), "+f"(a[(o) + 5]), "+f"(a[(o) + 6]), "+f"(a[(o) + 7])
#define R64(a, o) R8(a, (o) + 0), R8(a, (o) + 8), R8(a, (o) + 16), R8(a, (o) + 24), \
                  R8(a, (o) + 32), R8(a, (o) + 40), R8(a, (o) + 48), R8(a, (o) + 56)

template <int O, int TA>
__device__ __forceinline__ void wgmma128(float (&a)[128], uint32_t da, uint32_t db, int scale_d) {
    asm volatile(
        "{\n.reg .pred p;\n.reg .b64 da, db;\nsetp.ne.b32 p, %66, 0;\n"
        "mov.b64 da, {%64, " DESC_HI "};\nmov.b64 db, {%65, " DESC_HI "};\n"
        "wgmma.mma_async.sync.aligned.m64n128k16.f32.bf16.bf16 "
        "{%0,%1,%2,%3,%4,%5,%6,%7,%8,%9,%10,%11,%12,%13,%14,%15,"
        "%16,%17,%18,%19,%20,%21,%22,%23,%24,%25,%26,%27,%28,%29,%30,%31,"
        "%32,%33,%34,%35,%36,%37,%38,%39,%40,%41,%42,%43,%44,%45,%46,%47,"
        "%48,%49,%50,%51,%52,%53,%54,%55,%56,%57,%58,%59,%60,%61,%62,%63},"
        "da, db, p, 1, 1, %67, 0;\n}"
        : R64(a, O)
        : "r"(da), "r"(db), "r"(scale_d), "n"(TA));
}
template <int O>
__device__ __forceinline__ void wgmma128_rs(float (&a)[128], const uint32_t* f, uint32_t db) {
    asm volatile(
        "{\n.reg .b64 db;\nmov.b64 db, {%68, 8};\n"
        "wgmma.mma_async.sync.aligned.m64n128k16.f32.bf16.bf16 "
        "{%0,%1,%2,%3,%4,%5,%6,%7,%8,%9,%10,%11,%12,%13,%14,%15,"
        "%16,%17,%18,%19,%20,%21,%22,%23,%24,%25,%26,%27,%28,%29,%30,%31,"
        "%32,%33,%34,%35,%36,%37,%38,%39,%40,%41,%42,%43,%44,%45,%46,%47,"
        "%48,%49,%50,%51,%52,%53,%54,%55,%56,%57,%58,%59,%60,%61,%62,%63},"
        "{%64, %65, %66, %67}, db, 1, 1, 1, 0;\n}"
        : R64(a, O)
        : "r"(f[0]), "r"(f[1]), "r"(f[2]), "r"(f[3]), "r"(db));
}
template <int O>
__device__ __forceinline__ void fence_regs64(float (&a)[128]) {
    asm volatile("" : R64(a, O)::"memory");
}

struct Params {
    const __nv_bfloat16* x;
    const __nv_bfloat16* dre;
    const __nv_bfloat16* dim;
    const __nv_bfloat16* wr;
    const __nv_bfloat16* wg;
    const __nv_bfloat16* wu;
    const __nv_bfloat16* wd;
    uint32_t zero;
#define AB g_ab
};

__device__ __forceinline__ float warp_sum(float v) {
#pragma unroll
    for (int o = 16; o; o >>= 1) v += __shfl_xor_sync(0xffffffffu, v, o);
    return v;
}
__device__ __forceinline__ void fma8(float* acc, const uint4& w, float s) {
    acc[0] += s * bf_lo(w.x); acc[1] += s * bf_hi(w.x); acc[2] += s * bf_lo(w.y); acc[3] += s * bf_hi(w.y);
    acc[4] += s * bf_lo(w.z); acc[5] += s * bf_hi(w.z); acc[6] += s * bf_lo(w.w); acc[7] += s * bf_hi(w.w);
}
__device__ __forceinline__ int POS(int t) { return (t & ~15) | ((t & 6) << 1) | ((t & 8) >> 2) | (t & 1); }
__host__ __device__ constexpr int PSLOT(int j) { return j < 4 ? j : (j & 1) + ((j & 2) ? 0 : 4); }
__host__ __device__ constexpr int PPAR(int j) { return j < 4 ? 0 : ((j >> 2) ^ (j >> 1) ^ 1) & 1; }
__host__ __device__ constexpr int DSLOT(int it) { return (it & 3) + 2; }
__device__ __forceinline__ int SREC(int t) { return (t & ~15) | ((t & 3) << 2) | ((t >> 2) & 3); }
__device__ __forceinline__ int KO(int cl) { return ((cl & 1) << 1) | (cl >> 1); }

__global__ void __cluster_dims__(2, 1, 1) __launch_bounds__(NTHREADS, 1)
fnet_fused_kernel(const __grid_constant__ CUtensorMap tm_x, const __grid_constant__ CUtensorMap tm_dre,
                  const __grid_constant__ CUtensorMap tm_dim, const __grid_constant__ CUtensorMap tm_cre,
                  const __grid_constant__ CUtensorMap tm_cim, const __grid_constant__ CUtensorMap tm_out,
                  const __grid_constant__ CUtensorMap tm_x64,
                  const Params P) {
    extern __shared__ __align__(1024) uint8_t smem[];
    const unsigned long long tstart = clock64();
    const uint32_t sb = smem_u32(smem);
    const int tid = threadIdx.x, lane = tid & 31;
    const int warp = __shfl_sync(0xffffffffu, tid >> 5, 0);
    const int pr = blockIdx.x >> 1, p7 = ((pr - 36) * 37) >> 8;
    const int c = blockIdx.x & 1;
    const int gi = pr < 4 ? 7 : pr < 36 ? 2 * ((pr - 4) & 7) + (((pr - 4) >> 2) & 1) : 2 * (pr - 36 - 7 * p7) + 1 + (pr - 36 - 7 * p7 > 2);
    const int g = gi & 7;
    const int r = (gi >> 3) * 4 + (pr < 4 ? pr : pr < 36 ? (pr - 4) >> 3 : p7);
#define BLK(n) ((n) - ((n) <= g))
    const int grp = 2 * r + c;
    const int b = g * 16 + grp;
    const uint32_t bar0 = sb + OFF_BAR;
    const uint32_t zero = P.zero;
#define BAR(i) (bar0 + 8u * (i))
#define XBAR(i) (sb + OFF_XB + 64 + 8u * (i))
#define CLUSTER_ARRIVE() asm volatile("barrier.cluster.arrive.relaxed.aligned;" ::: "memory")
#define CLUSTER_WAIT() asm volatile("barrier.cluster.wait.aligned;" ::: "memory")
    if ((sb & 0xffffffu) != SB0) return;

#define LOAD0(it) do { \
            mbar_expect_tx(BAR(B_FS + DSLOT(it)), SLOT); tma_2d(sb + OFF_S + DSLOT(it) * SLOT, tmD, (it) * 64, r * 128, BAR(B_FS + DSLOT(it))); \
            mbar_expect_tx(BAR(B_FL + (it)), SLOT); tma_2d(sb + OFF_L + (it) * SLOT, &tm_x, (it) * 64, g * 256, BAR(B_FL + (it))); \
            mbar_expect_tx(BAR(B_FL + 4 + (it)), SLOT); tma_2d(sb + OFF_L + (4 + (it)) * SLOT, &tm_x, (it) * 64, g * 256 + 128, BAR(B_FL + 4 + (it))); \
        } while (0)
    if (warp == 13) {
        if (elect_one()) {
            const CUtensorMap* tmD = c ? &tm_dim : &tm_dre;
            prefetch_tmap(&tm_x);
            mbar_init(BAR(B_FS + 2), 1); mbar_init(BAR(B_FL), 1); mbar_init(BAR(B_FL + 4), 1);
            asm volatile("fence.mbarrier_init.release.cluster;" ::: "memory");
            LOAD0(0);
        }
        __syncwarp();
    }
    if (warp == 12) {
        if (elect_one()) {
#pragma unroll
            for (int i = 1; i < 4; i++) { mbar_init(BAR(B_FS + 2 + i), 1); mbar_init(BAR(B_FL + i), 1); mbar_init(BAR(B_FL + 4 + i), 1); }
#pragma unroll
            for (int i = 0; i < 4; i++) mbar_init(XBAR(i), 1);
            asm volatile("fence.mbarrier_init.release.cluster;" ::: "memory");
        }
        __syncwarp();
    }
    if (warp == 14) {
        if (elect_one()) {
#pragma unroll
            for (int i = 0; i < 8; i++) { mbar_init(BAR(B_EL + i), 1); mbar_init(XBAR(4 + i), 1); if (i < 6) mbar_init(BAR(B_ES + i), 2); }
            asm volatile("fence.mbarrier_init.release.cluster;" ::: "memory");
        }
        __syncwarp();
    }
    if (warp == 15) {
        if (elect_one()) {
            mbar_init(BAR(B_FS), 1); mbar_init(BAR(B_FS + 1), 1);
#pragma unroll
            for (int i = B_SRD; i < B_COUNT; i++) mbar_init(BAR(i), i == B_GO ? 2 : i == B_STATS || i == B_LST ? 4 : 1);
#pragma unroll
            for (int i = 0; i < 4; i++) mbar_expect_tx(BAR(B_RECV + i), SLOT / 2);
            mbar_expect_tx(BAR(B_PEER), 1024); mbar_expect_tx(BAR(B_H), 128);
            asm volatile("fence.mbarrier_init.release.cluster;" ::: "memory");
        }
        __syncwarp();
    }
    CLUSTER_ARRIVE();

#define GATHER(ptr, cnt, valid) do { int n = 0; bool ok; do { ok = true; \
                _Pragma("unroll") for (int i = 0; i < (cnt); i++) { f[i] = ld_relaxed128((ptr) + i * 32); ok = ok && (valid); } \
                if (__all_sync(0xffffffffu, ok)) break; \
                __nanosleep(GSL); \
            } while (++n < SPIN_LIMIT); } while (0)
    if (warp >= 8 && warp < 12) {
        asm volatile("setmaxnreg.dec.sync.aligned.u32 %0;" ::"n"(512 - PROD_REGS - 2 * CONS_REGS));
        const int aw = warp - 8, mt = tid - 256;
        unsigned ep;
        {
            const uint8_t* rp = smem + OFF_S + aw * 2048 + lane * 16;
            const __nv_bfloat16* dp = at(c ? P.dim : P.dre, (r * 128 + g * 16 + aw * 4) * D_ * 2);
            float wf[32], sw = 0.f;
#pragma unroll
            for (int i = 0; i < 4; i++) {
                const uint4 w = __ldg(reinterpret_cast<const uint4*>(at(P.wr, lane * 16) + i * 256));
                const uint32_t wv[4] = {w.x, w.y, w.z, w.w};
#pragma unroll
                for (int e = 0; e < 4; e++) { wf[8 * i + 2 * e] = bf_lo(wv[e]); wf[8 * i + 2 * e + 1] = bf_hi(wv[e]); sw = (sw + bf_lo(wv[e])) + bf_hi(wv[e]); }
            }
            ep = load_epoch(b);
            sw = warp_sum(sw);
            CLUSTER_WAIT();
            float x0[4] = {}, s1[4] = {}, s2[4] = {}, sx[4] = {}, sd[4] = {};
#define PUSH(a, v) do { a[0] = a[1]; a[1] = a[2]; a[2] = a[3]; a[3] = v; } while (0)
#pragma unroll 1
            for (int k = 0; k < 4; k++) {
                mbar_wait(XBAR(k), 0);
                uint4 v[4];
#pragma unroll
                for (int i = 0; i < 4; i++) v[i] = *reinterpret_cast<const uint4*>(rp + k * 8192 + i * 512);
                uint32_t sh = v[0].x << 16;
                float a1s = 0.f, a2s = 0.f, axs = 0.f;
#pragma unroll
                for (int i = 0; i < 4; i++) {
                    sh = __shfl_sync(0xffffffffu, sh | (__float_as_uint(axs) & zero), 0);
                    const uint32_t xv[4] = {v[i].x, v[i].y, v[i].z, v[i].w};
#pragma unroll
                    for (int e = 0; e < 4; e++) {
                        const float a0 = bf_lo(xv[e]) - __uint_as_float(sh), a1 = bf_hi(xv[e]) - __uint_as_float(sh);
                        a1s += a0 + a1;
                        a2s = fmaf(a0, a0, fmaf(a1, a1, a2s));
                        axs = fmaf(a0, wf[8 * i + 2 * e], fmaf(a1, wf[8 * i + 2 * e + 1], axs));
                    }
                }
                PUSH(x0, __uint_as_float(sh)); PUSH(s1, a1s); PUSH(s2, a2s); PUSH(sx, axs);
                fence_async_smem();
                __syncwarp();
                if (elect_one()) {
                    const uint32_t db = XBAR(k == 3 ? 8 + aw : 4 + aw);
                    if (k == 0 || k == 3) mbar_expect_tx(db, k ? 2048 : 6144);
                    bulk_g2s(sb + OFF_S + k * 8192 + aw * 2048, dp + k * D_, 2048, db);
                }
            }
#define FOLD4(a) do { const bool u16 = lane & 16, u8 = lane & 8; \
                float p0 = (u16 ? a[2] : a[0]) + __shfl_xor_sync(0xffffffffu, u16 ? a[0] : a[2], 16); \
                float p1 = (u16 ? a[3] : a[1]) + __shfl_xor_sync(0xffffffffu, u16 ? a[1] : a[3], 16); \
                a[0] = (u8 ? p1 : p0) + __shfl_xor_sync(0xffffffffu, u8 ? p0 : p1, 8); \
                _Pragma("unroll") for (int o = 4; o; o >>= 1) a[0] += __shfl_xor_sync(0xffffffffu, a[0], o); } while (0)
#pragma unroll 1
            for (int k = 0; k < 4; k++) {
                mbar_wait(XBAR(k == 3 ? 8 + aw : 4 + aw), 0);
                float run = 0.f;
#pragma unroll
                for (int i = 0; i < 4; i++) {
                    const uint4 v = *reinterpret_cast<const uint4*>(rp + k * 8192 + i * 512);
                    const uint32_t dv[4] = {v.x, v.y, v.z, v.w};
#pragma unroll
                    for (int e = 0; e < 4; e++) run += bf_lo(dv[e]) + bf_hi(dv[e]);
                }
                PUSH(sd, run);
            }
            named_bar<4, 128>();
            if (mt < 12) asm volatile("mbarrier.inval.shared::cta.b64 [%0];" ::"r"(XBAR(mt)) : "memory");
            FOLD4(sd); FOLD4(s1); FOLD4(s2); FOLD4(sx);
            const float nb = __shfl_down_sync(0xffffffffu, sd[0], 8);
            if ((lane & 15) == 0)
                st_relaxed128(at(g_rs, (grp * 64 + g * 8 + aw * 2 + (lane >> 4)) * 16), make_uint4(__float_as_uint(sd[0]), ep, __float_as_uint(nb), ep));
            if (mt == 0) PROF_T(6);
            const int rr = lane >> 3;
            const float c0 = rr == 0 ? x0[0] : rr == 1 ? x0[1] : rr == 2 ? x0[2] : x0[3];
            const float dm = s1[0] * (1.0f / D_);
            const float mb = rbf(c0 + dm);
            const float rinv = rcp_f(rbf(sqrt_f(rbf(rbf(fmaxf(s2[0] * (1.0f / D_) - dm * dm, 0.f)) + 1e-5f))));
            if ((lane & 7) == 0) st_relaxed128(at(g_stat, (b * 16 + aw * 4 + rr) * 16), make_uint4(__float_as_uint(mb), __float_as_uint(rinv), ep, 0));
            unsigned u = __bfloat16_as_ushort(__float2bfloat16_rn((sx[0] + (c0 - mb) * sw) * rinv));
            u = (u & 0x8000u) ? (~u & 0xffffu) : (u | 0x8000u);
            u = (u << 16) | (0xffffu - (unsigned)(b * 16 + rr * 4 + aw));
            u = __reduce_max_sync(0xffffffffu, u);
            if (lane == 0) { *reinterpret_cast<unsigned*>(smem + OFF_XB + aw * 4) = u; mbar_arrive(BAR(B_LST)); }
            if (mt == 0) PROF_T(2);
            uint4 f[4];
            if (aw < 2) {
                const int t = SREC(aw * 128 + lane);
                GATHER(at(g_stat, (g * 256 + aw * 128 + lane) * 16), 4, f[i].z == ep);
#pragma unroll
                for (int i = 0; i < 4; i++) {
                    *reinterpret_cast<uint32_t*>(smem + OFF_RSTD + (POS(t) + i * 32) * 4) = f[i].y;
                    *reinterpret_cast<uint16_t*>(smem + OFF_MEAN + (POS(t) + i * 32) * 2) = (uint16_t)(f[i].x >> 16);
                }
            } else {
                const int e2 = (aw - 2) * 32 + lane;
                GATHER(at(g_rs, (grp * 64 + e2) * 16), 1, f[i].y == ep && f[i].w == ep);
#pragma unroll
                for (int i = 0; i < 2; i++) {
                    const float v = __uint_as_float(i ? f[0].z : f[0].x);
                    const float hi = rbf(v), mid = rbf(v - hi), lo = v - hi - mid;
                    *reinterpret_cast<uint4*>(smem + OFF_RS + (e2 * 2 + i) * 16) = make_uint4(pack_bf(hi, mid), pack_bf(lo, 0.f), 0, 0);
                }
            }
            fence_async_smem();
            __syncwarp();
            if (lane == 0) mbar_arrive(BAR(B_STATS));
            if (mt == 127) PROF_T(9);
        }
        const bool moe = pr < 28 || pr >= 36;
        const int pair = pr < 28 ? pr : pr - 8;
        if (moe) {
            const uint64_t pol = policy_evict_first();
            const __nv_bfloat16* wp = at((aw & 1) ? P.wu : P.wg, ((c * 512 + (aw >> 1) * 256 + (lane >> 3) * 8) * F_ + pair * 64 + (lane & 7) * 8) * 2);
            uint4 b0[8], b1[8];
#define FILL(buf, str) do { _Pragma("unroll") for (int q = 0; q < 8; q++) buf[q] = ldg_stream(wp + q * (str), pol); } while (0)
#define PAUSE() do { if (mbar_test(BAR(B_QUIET), 0)) mbar_wait_sleep(BAR(B_GO), 0); } while (0)
            FILL(b0, F_);
            mbar_wait(BAR(B_SEL), 0);
            uint4 xn;
            {
                const int sel = ~*reinterpret_cast<volatile unsigned*>(smem + OFF_SEL) & (S_ - 1);
                xn = __ldg(reinterpret_cast<const uint4*>(at(P.x, (sel * D_ + c * 512 + (aw >> 1) * 256 + (lane & 7) * 32 + (lane >> 3) * 8) * 2)));
                uint4 f[1];
                GATHER(at(g_stat, SREC(sel) * 16), 1, f[i].z == ep);
                wp += 32 * F_; FILL(b1, F_); wp -= 32 * F_;
                PAUSE();
                const float m = __uint_as_float(f[0].x), ri = __uint_as_float(f[0].y);
                xn = make_uint4(norm2(xn.x, m, ri), norm2(xn.y, m, ri), norm2(xn.z, m, ri), norm2(xn.w, m, ri));
            }
            float ag[8];
#pragma unroll
            for (int i = 0; i < 8; i++) ag[i] = 0.f;
#define ROUND(cur, nxt, rd) do { \
                PAUSE(); \
                if (lane == 0) TRACE(192 + aw * 12 + (rd)); \
                if ((rd) == 7) wp = at(P.wd - 16 * D_, ((pair * 64 + (lane >> 4) * 8) * D_ + c * 512 + aw * 128 + (lane & 15) * 8) * 2); \
                wp = at(wp, ((rd) < 7 ? 64 * F_ : 32 * D_) + (cur[7].x & zero)); \
                if ((rd) & 7) { if ((rd) < 7) FILL(nxt, F_); else if ((rd) < 11) FILL(nxt, D_); } \
                _Pragma("unroll") for (int q = 0; q < 8; q += 2) { \
                    const uint32_t xw = __shfl_sync(0xffffffffu, q == 0 ? xn.x : q == 2 ? xn.y : q == 4 ? xn.z : xn.w, (lane & 24) | ((rd) & 7)); \
                    fma8(ag, cur[q], bf_lo(xw)); \
                    fma8(ag, cur[q + 1], bf_hi(xw)); \
                    if (q < 6) yield(ag[7], zero); \
                } } while (0)
#pragma unroll 1
            for (int rd = 0; rd < 12; rd += 2) {
                ROUND(b0, b1, rd);
                ROUND(b1, b0, rd + 1);
                if (rd == 6 || rd == 10) {
#pragma unroll
                    for (int i = 0; i < 8; i++) ag[i] += __shfl_xor_sync(0xffffffffu, ag[i], 16);
                }
                if (rd == 6) {
#pragma unroll
                    for (int i = 0; i < 8; i++) ag[i] += __shfl_xor_sync(0xffffffffu, ag[i], 8);
                    if (lane < 8) {
                        const uint32_t dst = mapa(sb + OFF_XB + (c * 4 + aw) * 128 + (lane & 3) * 32, lane >> 2), pb = mapa(BAR(B_PEER), lane >> 2);
                        st_async4(dst, __float_as_uint(ag[0]), __float_as_uint(ag[1]), __float_as_uint(ag[2]), __float_as_uint(ag[3]), pb);
                        st_async4(dst + 16, __float_as_uint(ag[4]), __float_as_uint(ag[5]), __float_as_uint(ag[6]), __float_as_uint(ag[7]), pb);
                    }
                    __syncwarp();
                    wp += 16 * D_; FILL(b1, D_); wp -= 16 * D_;
                    if (aw == 3) {
                        mbar_wait_cluster(BAR(B_PEER), 0);
                        const float* ps = reinterpret_cast<const float*>(smem + OFF_XB) + lane;
                        const float go = (ps[0] + ps[64]) + (ps[128] + ps[192]), uo = (ps[32] + ps[96]) + (ps[160] + ps[224]);
                        const float h = rbf(silu_f(rbf(go))) * rbf(uo), ho = __shfl_xor_sync(0xffffffffu, h, 1);
                        asm volatile("st.async.weak.shared::cluster.mbarrier::complete_tx::bytes.b32 [%0], %1, [%2];"
                                     ::"r"(mapa(sb + OFF_H + c * 64 + (lane >> 1) * 4, lane & 1)), "r"((lane & 1) ? pack_bf(ho, h) : pack_bf(h, ho)),
                                       "r"(mapa(BAR(B_H), lane & 1)) : "memory");
                    }
                    mbar_wait_cluster(BAR(B_H), 0);
                    xn = *reinterpret_cast<const uint4*>(smem + OFF_H + (lane & 3) * 32 + (lane >> 4) * 16);
#pragma unroll
                    for (int i = 0; i < 8; i++) ag[i] = 0.f;
                    if (mt == 0) PROF_T(10);
                }
            }
            const int hi = lane >> 4;
            st_relaxed128(at(g_part, pair * 4096 + (c * 8 + aw * 2 + ((lane >> 3) & 1)) * 256 + hi * 128 + (lane & 7) * 16),
                          make_uint4((__float_as_uint(hi ? ag[4] : ag[0]) & ~15u) | (ep & 15u), __float_as_uint(hi ? ag[5] : ag[1]),
                                     __float_as_uint(hi ? ag[6] : ag[2]), __float_as_uint(hi ? ag[7] : ag[3])));
            if (mt == 0) PROF_T(11);
        } else {
            mbar_wait_sleep(BAR(B_SEL), 0);
        }
        const int sel = ~*reinterpret_cast<volatile unsigned*>(smem + OFF_SEL) & (S_ - 1);
        if ((sel >> 8) == g) {
            const int col = (lane & 7) * 8 + ((lane >> 3) & 1) * 4;
            const uint2 xv = __ldg(reinterpret_cast<const uint2*>(at(P.x, (sel * D_ + grp * 64 + col) * 2)));
            uint4 f[1];
            GATHER(at(g_stat, SREC(sel) * 16), 1, f[i].z == ep);
            const uint4 rec = f[0];
            const uint4* src = at(g_part, (aw * 14 + (lane >> 4)) * 4096 + grp * 256 + (lane & 15) * 16);
            if (!moe) {
                int n = 0;
                while (((ld_relaxed(src) ^ ep) & 15u) != 0 && ++n < SPIN_LIMIT) __nanosleep(500);
            }
            uint4 t[7];
            int n = 0;
            bool ok;
            do {
                ok = true;
#pragma unroll
                for (int u = 0; u < 7; u++) { t[u] = ld_relaxed128(src + u * 512); ok = ok && ((t[u].x ^ ep) & 15u) == 0; }
            } while (!__all_sync(0xffffffffu, ok) && ++n < SPIN_LIMIT);
            float4 a = make_float4(0.f, 0.f, 0.f, 0.f);
#pragma unroll
            for (int u = 0; u < 7; u++) {
                a.x += __uint_as_float(t[u].x & ~15u); a.y += __uint_as_float(t[u].y); a.z += __uint_as_float(t[u].z); a.w += __uint_as_float(t[u].w);
            }
            a.x += __shfl_xor_sync(0xffffffffu, a.x, 16); a.y += __shfl_xor_sync(0xffffffffu, a.y, 16);
            a.z += __shfl_xor_sync(0xffffffffu, a.z, 16); a.w += __shfl_xor_sync(0xffffffffu, a.w, 16);
            float4* park = reinterpret_cast<float4*>(smem + OFF_XB) + (lane & 15);
            if (lane < 16) park[aw * 16] = a;
            named_bar<4, 128>();
            if (aw == 0) {
                const float4 p1 = park[16], p2 = park[32], p3 = park[48];
                a.x = (a.x + p1.x) + (p2.x + p3.x); a.y = (a.y + p1.y) + (p2.y + p3.y);
                a.z = (a.z + p1.z) + (p2.z + p3.z); a.w = (a.w + p1.w) + (p2.w + p3.w);
                unsigned u = *reinterpret_cast<volatile unsigned*>(smem + OFF_SEL) >> 16;
                u = (u & 0x8000u) ? (u & 0x7fffu) : (~u & 0xffffu);
                const float sg = rbf(__fdividef(1.0f, 1.0f + __expf(-__uint_as_float(u << 16))));
                const float m = __uint_as_float(rec.x), ri = __uint_as_float(rec.y);
                const uint32_t n0 = norm2(xv.x, m, ri), n1 = norm2(xv.y, m, ri);
                uint2 o;
                o.x = silu2(pack_bf(bf_lo(n0) + rbf(rbf(a.x) * sg), bf_hi(n0) + rbf(rbf(a.y) * sg)));
                o.y = silu2(pack_bf(bf_lo(n1) + rbf(rbf(a.z) * sg), bf_hi(n1) + rbf(rbf(a.w) * sg)));
                if (lane < 16) *reinterpret_cast<uint2*>(smem + OFF_H + col * 2) = o;
                __syncwarp();
                if (lane == 0) { mbar_arrive(BAR(B_UPD)); PROF_T(12); }
            }
        }
    } else if (warp < 8) {
        asm volatile("setmaxnreg.inc.sync.aligned.u32 %0;" ::"n"(CONS_REGS));
        CLUSTER_WAIT();
        const int wg = warp >> 2, wq = warp & 3;
        const int wt = tid & 127;
        float acc[128];
        const uint32_t fL = BAR(B_FL + 4 * wg), eL = BAR(B_EL + 4 * wg);
        const uint32_t dL = desc_lo(SB0 + OFF_L, 16) + wg * 4096;
        constexpr uint32_t dS = desc_lo(SB0 + OFF_S, 16);
        constexpr uint32_t SL = SLOT >> 4;
#define RELEASE(ls, ss) do { if (wt == 0) { mbar_arrive(eL + 8u * (ls)); mbar_arrive(BAR(B_ES + (ss))); } } while (0)
#define WAIT_FULL(ls, lph, ss, sph) do { mbar_wait(BAR(B_FS + (ss)), sph); mbar_wait(fL + 8u * (ls), lph); } while (0)
#define TURN() do { if (wg) named_bar<6, 256>(); else named_bar<5, 256>(); } while (0)
#define PASS() do { if (wg) named_arrive<5, 256>(); else named_arrive<6, 256>(); } while (0)
#define WG_BAR() do { if (wg) named_bar<2, 128>(); else named_bar<1, 128>(); } while (0)
        if (wg == 1) PASS();

#define MMA1_H(O, s, first) do { _Pragma("unroll") for (int kk = 0; kk < 4; kk++) \
            wgmma128<O, 0>(acc, dL + (s) * SL + kk * 2 + (O) * 8, dS + DSLOT(s) * SL + kk * 2, !((first) && kk == 0)); } while (0)
#define WAIT1(s, ph) WAIT_FULL(s, ph, DSLOT(s), ph)
#define PROBE(ls, lph, ss, sph) (mbar_test(BAR(B_FS + (ss)), sph) & mbar_test(fL + 8u * (ls), lph))
#define REL1(s) RELEASE(s, DSLOT(s))
#pragma unroll 1
        for (int it = 0; it < 12; it++) {
            const int s = it & 3;
            const bool ok = PROBE(s, (it >> 2) & 1, DSLOT(s), (it >> 2) & 1);
            if (it) { wg_wait<0>(); REL1((s + 3) & 3); }
            if (!ok) WAIT1(s, (it >> 2) & 1);
            TURN();
            wg_fence(); MMA1_H(0, s, it == 0); MMA1_H(64, s, it == 0); wg_commit();
            PASS();
            if (it == 0 && tid == 0) PROF_T(16);
        }
        TS(12);
        float rs[4] = {};
        uint32_t nm[8] = {};
#define GET_STATS() do { mbar_wait(BAR(B_STATS), 0); \
            const int p0 = POS(wg * 128 + wq * 16 + (lane >> 2));                   \
            const uint32_t msk = (lane & 3) == 0 ? 0xffffffffu : (lane & 3) == 1 ? 0x0000ffffu : 0u; \
            _Pragma("unroll") for (int i = 0; i < 4; i++) { \
                const int p = p0 + (i & 1) * 2 + (i >> 1) * 64; \
                rs[i] = *reinterpret_cast<const float*>(smem + OFF_RSTD + p * 4); \
                const uint32_t m = *reinterpret_cast<const uint16_t*>(smem + OFF_MEAN + p * 2) ^ 0x8000u; \
                nm[i + (i & 2)] = (m | (m << 16)) & msk; \
            } } while (0)
        const bool early = wg || __all_sync(0xffffffffu, mbar_test(BAR(B_STATS), 0));
        if (early && !wg) GET_STATS();
        WAIT1(0, 1);
        TS(13);
        wg_wait<0>(); REL1(3);
        if (wg) GET_STATS();
        TS(14);
        TURN();
        wg_fence();
        MMA1_H(0, 0, false);
        if (tid == 0) { mbar_arrive(BAR(B_QUIET)); PROF_T(15); }
        WAIT1(1, 1); wg_fence(); MMA1_H(0, 1, false);
        WAIT1(2, 1); wg_fence(); MMA1_H(0, 2, false); wg_commit();
        if (!early) GET_STATS();
        asm volatile("" : "+r"(nm[0]), "+r"(nm[1]), "+r"(nm[2]), "+r"(nm[3]), "+r"(nm[4]), "+r"(nm[5]), "+r"(nm[6]), "+r"(nm[7])::"memory");
        wg_fence();
        wgmma128_rs<64>(acc, nm + 4, (SB0 + OFF_RS) >> 4);
        wgmma128_rs<0>(acc, nm, (SB0 + OFF_RS) >> 4);
        WAIT1(3, 1); wg_fence(); MMA1_H(0, 3, false); wg_commit();
        PASS();
        const int mrow = wq * 16 + ((lane >> 3) & 1) * 8 + (lane & 7);
#define EPI1(O, slot, FREE) do { const uint32_t dst = sb + OFF_S + (slot) * SLOT + mrow * 128; \
            uint32_t pk[32]; \
            _Pragma("unroll") for (int i = 0; i < 32; i += 4) { \
                _Pragma("unroll") for (int k = 0; k < 4; k++) \
                    pk[i + k] = pack_bf(acc[(O) + 2 * (i + k)] * rs[(O) / 32 + (k & 1)], acc[(O) + 2 * (i + k) + 1] * rs[(O) / 32 + (k & 1)]); \
                if (i == EF) { FREE; } \
                if (i >= EF) { _Pragma("unroll") for (int v = (i == EF ? 0 : i); v <= i; v += 4) \
                    stmatrix4(dst + ((v >> 4) ^ c ^ 1) * 8192 + ((((v >> 1) & 7) + (lane >> 4)) ^ (lane & 7)) * 16, pk[v], pk[v + 1], pk[v + 2], pk[v + 3]); } } \
            WG_BAR(); \
            if (wt == 0) mbar_arrive(BAR(B_FS + (slot))); } while (0)
        TS(15);
        wg_wait<0>();
        fence_regs64<0>(acc);
        TS(16);
        {
            constexpr int EF = 0;
            EPI1(0, wg, if (wg) mbar_wait(BAR(B_FS), 0));
        }
        TS(17);
        TURN();
        wg_fence();
        MMA1_H(64, 0, false); wg_commit();
        MMA1_H(64, 1, false); wg_commit();
        MMA1_H(64, 2, false); wg_commit();
        wg_wait<2>(); REL1(0);
        MMA1_H(64, 3, false); wg_commit();
        PASS();
        TS(18);
        wg_wait<2>(); REL1(1);
        mbar_wait(BAR(B_FS), 0); mbar_wait(BAR(B_FS + 1), 0); fence_async_smem();
        wg_wait<1>(); REL1(2);
        wg_wait<0>(); REL1(3);
        fence_regs64<64>(acc);
        TS(19);
        {
            constexpr int EF = 16;
            EPI1(64, 2 + wg, mbar_wait(BAR(B_ES + 2 + wg), 1));
        }
        TS(20);

        float ac2[128];
#define MMA2_H(O, ls, ss, first) do { _Pragma("unroll") for (int kk = 0; kk < 4; kk++) \
            wgmma128<O, 1>(ac2, dS + (ss) * SL + kk * 128 + (O) * 8, dL + (ls) * SL + kk * 2, !((first) && kk == 0)); } while (0)
#define WAIT2(j) WAIT_FULL((j) & 3, ((j) >> 2) & 1, PSLOT(j), PPAR(j))
#define MMA2(j) do { wg_fence(); MMA2_H(0, (j) & 3, PSLOT(j), (j) == 0); MMA2_H(64, (j) & 3, PSLOT(j), (j) == 0); wg_commit(); } while (0)
#define REL2(j) RELEASE((j) & 3, PSLOT(j))
        WAIT2(0); TURN(); MMA2(0);
        WAIT2(1); MMA2(1); PASS();
        TS(21);
        wg_wait<1>(); REL2(0);
        mbar_wait(BAR(B_FS + 2), 0); mbar_wait(BAR(B_FS + 3), 0); fence_async_smem();
        TS(22);
        {
            uint32_t sp = 1;
#pragma unroll 1
            for (int j = 2; j < XJ; j++) {
                const uint32_t ss = PSLOT(j);
                const bool ok = PROBE(j & 3, (j >> 2) & 1, ss, PPAR(j));
                wg_wait<0>(); RELEASE((j - 1) & 3, sp);
                if (!ok) WAIT_FULL(j & 3, (j >> 2) & 1, ss, PPAR(j));
                TURN();
                wg_fence(); MMA2_H(0, j & 3, ss, false); MMA2_H(64, j & 3, ss, false); wg_commit();
                PASS();
                if (j == GOJ && wt == 0) { mbar_arrive(BAR(B_GO)); if (wg == 0) PROF_T(19); }
                sp = ss;
            }
        }
        if (tid == 0) PROF_T(20);
        uint32_t gt[32];
        const uint32_t xrow = sb + OFF_S + 2 * SLOT + wg * 8192 + ((lane >> 4) * 8 + (lane & 7)) * 128 + (((2 * wq + ((lane >> 3) & 1)) ^ (lane & 7)) << 4);
        const uint32_t gsign = c ? 0x80008000u : 0u;
#define XOFF(v) (((v) >> 2) * SLOT + ((v) & 3) * 2048)
        mbar_wait(BAR(B_SEL), 0);
        const int sel = ~*reinterpret_cast<volatile unsigned*>(smem + OFF_SEL) & (S_ - 1);
        bool own = (sel >> 7) == 2 * g + wg;
#define PATCH() do { own = false; \
            const uint32_t v0 = *reinterpret_cast<const uint16_t*>(smem + OFF_H + (wq * 16 + (lane >> 2)) * 2) ^ gsign; \
            const uint32_t v1 = *reinterpret_cast<const uint16_t*>(smem + OFF_H + (wq * 16 + (lane >> 2)) * 2 + 16) ^ gsign; \
            const uint32_t pick = (lane & 3) != ((sel >> 1) & 3) ? 0x3210u : (sel & 1) ? 0x5410u : 0x3254u; \
            _Pragma("unroll") for (int i = 0; i < 16; i++) { \
                const uint32_t m = ((sel >> 3) & 15) == i ? pick : 0x3210u; \
                gt[2 * i] = __byte_perm(gt[2 * i], v0, m); \
                gt[2 * i + 1] = __byte_perm(gt[2 * i + 1], v1, m); \
            } } while (0)
#pragma unroll
        for (int u = 0; u < 8; u++) {
            WAIT2(XJ + u); wg_wait<0>(); REL2(XJ + u - 1); TURN(); MMA2(XJ + u); PASS();
            uint32_t* o = &gt[4 * u];
            if (!(u & 3)) mbar_wait(BAR(B_FS + 2 + (u >> 2)), 1);
            ldmatrix4t(xrow + XOFF(u), o[0], o[1], o[2], o[3]);
            const float4 r4 = *reinterpret_cast<const float4*>(smem + OFF_RSTD + (wg * 128 + u * 16 + (lane & 3) * 4) * 4);
            const uint2 m2 = *reinterpret_cast<const uint2*>(smem + OFF_MEAN + (wg * 128 + u * 16 + (lane & 3) * 4) * 2);
            o[0] = gate2(o[0], m2.x, r4.x, r4.y) ^ gsign;
            o[1] = gate2(o[1], m2.x, r4.x, r4.y) ^ gsign;
            o[2] = gate2(o[2], m2.y, r4.z, r4.w) ^ gsign;
            o[3] = gate2(o[3], m2.y, r4.z, r4.w) ^ gsign;
            asm volatile("st.shared.v2.u32 [%0], {%1,%2};" ::"r"(sb + OFF_SEL + 16), "r"(o[0] ^ o[1]), "r"(o[2] ^ o[3]) : "memory");
        }
        if (tid == 0) PROF_T(21);
        WAIT2(28);
        wg_wait<0>(); REL2(27);
        if (own) {
            const uint32_t t0 = clock32();
            bool ok;
            while (!(ok = mbar_test(BAR(B_UPD), 0)) && clock32() - t0 < wg * 1400u) __nanosleep(50);
            if (__all_sync(0xffffffffu, ok)) PATCH();
        }
        TS(0);
        TURN();
        wg_fence(); MMA2_H(0, 0, PSLOT(28), false); wg_commit();
        if (wg == 0) { wg_fence(); MMA2_H(64, 0, PSLOT(28), false); wg_commit(); }
        WAIT2(29); wg_fence(); MMA2_H(0, 1, PSLOT(29), false); wg_commit();
        WAIT2(30); wg_fence(); MMA2_H(0, 2, PSLOT(30), false); wg_commit();
        wg_wait<2>();
        if (tid == 0) mbar_arrive_cluster(mapa(BAR(B_RDY), c ^ 1));
        WAIT2(31); wg_fence(); MMA2_H(0, 3, PSLOT(31), false); wg_commit();
        TS(1);
#define KEEP(i) wgmma128<64, 1>(ac2, dS + PSLOT(29 + ((i) >> 2)) * SL + ((i) & 3) * 128 + 512, dL + (1 + ((i) >> 2)) * SL + ((i) & 3) * 2, 1)
        wg_fence();
#pragma unroll
        for (int i = 0; i < KQ; i++) KEEP(i);
        wg_commit();
        mbar_wait(BAR(B_RDY + wg), 0);
        wg_wait<1>();
        fence_regs64<0>(ac2);
        TS(2);
        wg_fence();
        {
            const uint32_t dst = mapa(sb + OFF_L + wg * SLOT + wt * 16, c ^ 1), rb = mapa(BAR(B_RECV + 2 * wg), c ^ 1);
#pragma unroll
            for (int v = 0; v < 8; v++) {
                if (KQ + v < 12) KEEP(KQ + v);
                if (KQ + v == 11) { wg_commit(); if (wg == 0) PASS(); }
                st_async4(dst + v * 2048, pack_bf(ac2[8 * v + 0], ac2[8 * v + 1]), pack_bf(ac2[8 * v + 2], ac2[8 * v + 3]),
                          pack_bf(ac2[8 * v + 4], ac2[8 * v + 5]), pack_bf(ac2[8 * v + 6], ac2[8 * v + 7]), rb + (v >> 2) * 8);
            }
        }
        if (wg == 1) { wg_fence(); MMA2_H(64, 0, PSLOT(28), false); wg_commit(); }
        TS(3);
        uint32_t xr[32];
#define LDX(v) ldmatrix4t(xrow + XOFF(v), xr[4 * (v)], xr[4 * (v) + 1], xr[4 * (v) + 2], xr[4 * (v) + 3])
#pragma unroll
        for (int v = 0; v < XE; v++) LDX(v);
        if (wg == 0) {
            wg_wait<0>();
            if (wt == 0) mbar_arrive_cluster(mapa(BAR(B_RDY + 1), c ^ 1));
        }
        TS(4);
        if (own) { mbar_wait(BAR(B_UPD), 0); PATCH(); }
        TS(5);
        uint4 rv[8];
#define FETCH(v0) do { if ((v0) == 0 || (v0) == 4) mbar_wait_cluster(BAR(B_RECV + 2 * wg + (v0) / 4), 0); \
            _Pragma("unroll") for (int v = (v0); v < (v0) + 2; v++) { \
                asm volatile("ld.shared.v4.u32 {%0,%1,%2,%3}, [%4];" : "=r"(rv[v].x), "=r"(rv[v].y), "=r"(rv[v].z), "=r"(rv[v].w) \
                             : "r"(sb + OFF_L + wg * SLOT + v * 2048 + wt * 16) : "memory"); \
                if (v >= XE) LDX(v); } } while (0)
        FETCH(0);
        TS(6);
        wg_wait<0>();
        fence_regs64<64>(ac2);
        TS(7);
#pragma unroll
        for (int v0 = 0; v0 < 8; v0 += 2) {
#pragma unroll
            for (int v = v0; v < v0 + 2; v++) {
                const float* a = &ac2[64 + 8 * v];
                stmatrix4t(xrow + XOFF(v),
                           bfma2(bsub2(pack_bf(a[0], a[1]), rv[v].x), gt[4 * v + 0], xr[4 * v + 0]),
                           bfma2(bsub2(pack_bf(a[2], a[3]), rv[v].y), gt[4 * v + 1], xr[4 * v + 1]),
                           bfma2(bsub2(pack_bf(a[4], a[5]), rv[v].z), gt[4 * v + 2], xr[4 * v + 2]),
                           bfma2(bsub2(pack_bf(a[6], a[7]), rv[v].w), gt[4 * v + 3], xr[4 * v + 3]));
            }
            WG_BAR();
            if (wt == 0) mbar_arrive(eL + 4 * v0);
            if (v0 + 2 < 8) FETCH(v0 + 2);
            if (v0 == 0) TS(8);
        }
        TS(9);
    } else {
        asm volatile("setmaxnreg.dec.sync.aligned.u32 %0;" ::"n"(PROD_REGS));
#define XROWS(k) do { mbar_expect_tx(XBAR(k), 8192); bulk_g2s(sb + OFF_S + (k) * 8192, at(P.x, (b * 16 + (k) * 4) * D_ * 2), 8192, XBAR(k)); } while (0)
        if (warp == 12) {
            if (elect_one()) {
                const CUtensorMap* tmD = c ? &tm_dim : &tm_dre;
#pragma unroll 1
                for (int it = 1; it < 4; it++) {
                    while (clock32() - (uint32_t)tstart < LDEL + (it - 1) * LGAP) {}
                    LOAD0(it);
                    if (it >= X0) XROWS(it - X0);
                }
            }
            __syncwarp();
        }
        CLUSTER_WAIT();
        if (warp == 12) {
            if (elect_one()) {
                const CUtensorMap* tmD = c ? &tm_dim : &tm_dre;
#pragma unroll 1
                for (int it = 4; it < 16; it++) {
                    const int s = DSLOT(it);
                    mbar_wait(BAR(B_ES + s), ((it >> 2) & 1) ^ 1);
                    TRACE(it);
                    mbar_expect_tx(BAR(B_FS + s), SLOT);
                    tma_2d(sb + OFF_S + s * SLOT, tmD, it * 64, r * 128, BAR(B_FS + s));
                    if (it < 4 + X0) XROWS(it - X0);
                }
                const unsigned ep = load_epoch(b), e8 = ep & 0xffu;
                const uint8_t* abg = at(AB, grp * 32 * SLOT);
                const unsigned long long* fl = at(g_flag, grp * 128);
                unsigned long long rdy = ld_acquire64(fl);
                mbar_wait(BAR(B_SRD), 0);
                st_release8(at(g_flag, grp * 128 + g), e8);
                PROF_T(7);
                int j = 4;
#pragma unroll 1
                for (int cl = 0; cl < 4; cl++) {
                    if (cl) rdy = ld_acquire64(++fl);
                    fence_async_global();
#pragma unroll 1
                    for (int n = 1; n < 8; n++, j++) {
                        const int q = BLK(n), s = (j & 1) + ((j & 2) ? 0 : 4);
                        mbar_wait(BAR(B_ES + s), ((j >> 2) ^ (j >> 1)) & 1);
                        if (j == 7) mbar_wait(BAR(B_SRD + 1), 0);
                        if (((unsigned)(rdy >> (8 * q)) & 0xffu) != e8) {
                            int m = 0;
                            do { rdy = ld_acquire64(fl); } while (((unsigned)(rdy >> (8 * q)) & 0xffu) != e8 && ++m < SPIN_LIMIT);
                            fence_async_global();
                        }
                        TRACE(16 + j);
                        mbar_expect_tx(BAR(B_FS + s), SLOT);
                        bulk_g2s(sb + OFF_S + s * SLOT, at(abg, (4 * q + KO(cl)) * SLOT), SLOT, BAR(B_FS + s));
                    }
                }
                *at(g_epoch, b * 4) = ep;
            }
        } else if (warp < 15) {
            if (elect_one()) {
                const int w = warp - 13, row0 = g * 256 + w * 128;
                const CUtensorMap* tmC = c ? &tm_cim : &tm_cre;
                const uint32_t fb = BAR(B_FL + 4 * w), eb = BAR(B_EL + 4 * w), dst = sb + OFF_L + w * 4 * SLOT;
                [[maybe_unused]] unsigned long long mk = 0, mg = 0;
                int n = 0, cl = 0;
#pragma unroll 1
                for (int it = 4; it < 48; it++) {
                    const int s = it & 3;
                    mbar_wait(eb + 8 * s, ((it >> 2) & 1) ^ 1);
                    TRACE(64 + w * 64 + it - 4);
                    MARK(it);
                    mbar_expect_tx(fb + 8 * s, SLOT);
                    tma_2d(dst + s * SLOT, it < 16 ? &tm_x : tmC, (it < 16 ? it : 4 * (n ? BLK(n) : g) + KO(cl)) * 64, row0, fb + 8 * s);
                    if (it == PTJ) prefetch_tmap(w ? &tm_x64 : tmC);
                    if (it == PTJ && w) prefetch_tmap(&tm_out);
                    if (it >= 16) {
                        if (it == 19) { n = 1; cl = 0; } else if (it < 19) cl++; else if (++n == 8) { n = 1; cl++; }
                    }
                }
#pragma unroll 1
                for (int h = 0; h < 4; h++) {
                    mbar_wait(eb + 8 * h, 1);
                    fence_async_smem();
                    tma_2d_store(&tm_out, grp * 64, row0 + h * 32, sb + OFF_S + (2 + (h >> 1)) * SLOT + w * 8192 + (h & 1) * 4096);
                    bulk_commit();
                }
                FINISH(w);
            }
        } else {
            const unsigned ep = load_epoch(b);
            uint4 f[4];
            {
                sleep_until((uint32_t)tstart + 6000);
                const uint4* keys = at(reinterpret_cast<const uint4*>(g_key), lane * 16);
                bool mine = false;
                int n = 0;
                do {
                    f[0] = ld_relaxed128(keys); f[1] = ld_relaxed128(keys + 32);
                    if (__all_sync(0xffffffffu, f[0].y == ep && f[0].w == ep && f[1].y == ep && f[1].w == ep)) break;
                    if (!mine) {
                        mbar_wait(BAR(B_LST), 0);
                        const uint4 k = *reinterpret_cast<const uint4*>(smem + OFF_XB);
                        if (lane == 0) st_relaxed64(at(g_key, b * 8), ((unsigned long long)ep << 32) | max(max(k.x, k.y), max(k.z, k.w)));
                        mine = true;
                    }
                    __nanosleep(GSL);
                } while (++n < SPIN_LIMIT);
                const unsigned key = __reduce_max_sync(0xffffffffu, max(max(f[0].x, f[0].z), max(f[1].x, f[1].z)));
                if (lane == 0) { *reinterpret_cast<unsigned*>(smem + OFF_SEL) = key; mbar_arrive(BAR(B_SEL)); PROF_T(8); }
            }
            if (elect_one()) {
#pragma unroll 1
                for (int cl = 0; cl < 4; cl++) {
                    uint8_t* dst = at(AB, (grp * 32 + 4 * g + KO(cl)) * SLOT);
                    const uint32_t src = sb + OFF_S + cl * SLOT, chunk = cl ? 1024 : SLOT;
                    mbar_wait(BAR(B_FS + cl), 0);
                    fence_async_smem();
                    if (cl == 0) PROF_T(3);
                    uint32_t t0 = clock32() + (cl == 1 ? PDEL : 0);
#pragma unroll 1
                    for (uint32_t o = 0; o < SLOT; o += chunk) {
                        sleep_until(t0);
                        bulk_s2g(dst + o, src + o, chunk);
                        bulk_commit();
                        t0 += cl == 1 ? PGAP1 : cl == 2 ? PGAP2 : PGAP3;
                    }
                    bulk_wait<0>();
                    fence_async_global();
                    TRACE(252 + cl);
                    if (cl < 2) mbar_arrive(BAR(B_SRD + cl));
                    else {
                        mbar_wait(BAR(B_ES + cl), 0);
                        mbar_expect_tx(BAR(B_FS + cl), SLOT);
                        tma_2d(src, &tm_x64, grp * 64, g * 256 + (cl - 2) * 64, BAR(B_FS + cl));
                        tma_2d(src + 8192, &tm_x64, grp * 64, g * 256 + (cl - 2) * 64 + 128, BAR(B_FS + cl));
                    }
                    if (cl) st_release8(at(g_flag, grp * 128 + cl * 8 + g), ep & 0xffu);
                    if (cl == 1) PROF_T(5);
                    if (cl == 3) PROF_T(4);
                }
            }
        }
    }
}

typedef CUresult (*EncodeFn)(CUtensorMap*, CUtensorMapDataType, cuuint32_t, void*, const cuuint64_t*, const cuuint64_t*,
                             const cuuint32_t*, const cuuint32_t*, CUtensorMapInterleave, CUtensorMapSwizzle,
                             CUtensorMapL2promotion, CUtensorMapFloatOOBfill);

void make_map(EncodeFn fn, CUtensorMap* tm, const void* p, uint64_t rows, uint64_t cols, uint32_t box_rows) {
    cuuint64_t dims[2] = {cols, rows};
    cuuint64_t strides[1] = {cols * 2};
    cuuint32_t box[2] = {64, box_rows};
    cuuint32_t es[2] = {1, 1};
    fn(tm, CU_TENSOR_MAP_DATA_TYPE_BFLOAT16, 2, const_cast<void*>(p), dims, strides, box, es, CU_TENSOR_MAP_INTERLEAVE_NONE,
       CU_TENSOR_MAP_SWIZZLE_128B, CU_TENSOR_MAP_L2_PROMOTION_L2_128B, CU_TENSOR_MAP_FLOAT_OOB_FILL_NONE);
}

}

extern "C" void kernel_launch(void* const* d_in, const int* in_sizes, int n_in, void* d_out, int out_size) {
    (void)in_sizes; (void)n_in; (void)out_size;
    static EncodeFn fn = nullptr;
    if (!fn) {
        void* p = nullptr;
        cudaDriverEntryPointQueryResult q;
        cudaGetDriverEntryPoint("cuTensorMapEncodeTiled", &p, cudaEnableDefault, &q);
        fn = (EncodeFn)p;
        cudaFuncSetAttribute(fnet_fused_kernel, cudaFuncAttributeMaxDynamicSharedMemorySize, SMEM_BYTES);
    }
    CUtensorMap tx, tdre, tdim, tcre, tcim, tout, tx64;
    make_map(fn, &tx, d_in[0], S_, D_, 128);
    make_map(fn, &tcre, d_in[1], S_, S_, 128);
    make_map(fn, &tcim, d_in[2], S_, S_, 128);
    make_map(fn, &tdre, d_in[3], D_, D_, 128);
    make_map(fn, &tdim, d_in[4], D_, D_, 128);
    make_map(fn, &tx64, d_in[0], S_, D_, 64);
    make_map(fn, &tout, d_out, S_, D_, 32);
    Params P;
    P.x = (const __nv_bfloat16*)d_in[0];
    P.dre = (const __nv_bfloat16*)d_in[3];
    P.dim = (const __nv_bfloat16*)d_in[4];
    P.wr = (const __nv_bfloat16*)d_in[6];
    P.wg = (const __nv_bfloat16*)d_in[7];
    P.wu = (const __nv_bfloat16*)d_in[8];
    P.wd = (const __nv_bfloat16*)d_in[9];
    P.zero = 0;
    fnet_fused_kernel<<<NCTA, NTHREADS, SMEM_BYTES, cudaStreamPerThread>>>(tx, tdre, tdim, tcre, tcim, tout, tx64, P);
}
```

```cpp
#include <cuda_runtime.h>
#include <cuda_bf16.h>
#include <cuda.h>
#include <stdint.h>

#define GSL 200
#define SLEEP_NS 200
#define PDEL 1000
#define PGAP1 200
#define PGAP2 200
#define PGAP3 240
#define GOJ 2
#define LDEL 1300
#define LGAP 750
#define PTJ 10
#define X0 2
#define KQ 5
#define XE 2
#define PROD_REGS 32
#define CONS_REGS 184

namespace {

constexpr int S_ = 2048, D_ = 1024, F_ = 3584;
constexpr int NCTA = 128;
constexpr int XJ = 20;
constexpr uint32_t SLOT = 16384;
constexpr uint32_t OFF_L = 0;
constexpr uint32_t OFF_S = 8 * SLOT;
constexpr uint32_t OFF_RS = OFF_S + SLOT;
constexpr uint32_t OFF_BAR = 14 * SLOT;
constexpr uint32_t OFF_SEL = OFF_BAR + 360;
constexpr uint32_t OFF_RSTD = OFF_BAR + 384;
constexpr uint32_t OFF_MEAN = OFF_RSTD + 1024;
constexpr uint32_t OFF_XB = OFF_MEAN + 512;
constexpr uint32_t OFF_H = OFF_XB + 1024;
constexpr uint32_t SMEM_BYTES = OFF_H + 128;
constexpr uint32_t SB0 = 1024;
constexpr int NTHREADS = 512;
static_assert(SMEM_BYTES <= 232448, "smem");

enum { B_FS = 0, B_ES = 6, B_FL = 12, B_EL = 20, B_SRD = 28, B_RECV = 30  , B_RDY = 34, B_STATS = 36, B_LST = 37, B_UPD = 38,
       B_QUIET = 39, B_GO = 40, B_PEER = 41, B_SEL = 42, B_H = 43, B_COUNT = 44 };
static_assert(B_COUNT * 8 <= 360, "barriers");

__device__ __align__(1024) uint8_t g_ab[16u * 32u * SLOT];
__device__ __align__(128) uint4 g_part[56 * (D_ / 4)];
__device__ __align__(128) uint4 g_stat[S_];
__device__ __align__(128) uint4 g_rs[D_];
__device__ __align__(128) unsigned long long g_key[NCTA];
__device__ __align__(128) unsigned long long g_flag[16 * 16];
__device__ __align__(128) unsigned g_epoch[NCTA];
#define PROF_T(i) do {} while (0)
#define TRACE(i) do {} while (0)
#define PROF_G(i) do {} while (0)
#define TS(i) do {} while (0)
#define FINISH(wg) bulk_wait_read<0>()

#define MARK(it) do {} while (0)

__device__ __forceinline__ uint32_t smem_u32(const void* p) { return (uint32_t)__cvta_generic_to_shared(p); }
__device__ __forceinline__ void mbar_init(uint32_t bar, uint32_t cnt) {
    asm volatile("mbarrier.init.shared::cta.b64 [%0], %1;" ::"r"(bar), "r"(cnt) : "memory");
}
__device__ __forceinline__ bool mbar_try(uint32_t bar, uint32_t parity) {
    uint32_t ok;
    asm volatile("{\n.reg .pred p;\nmbarrier.try_wait.parity.shared::cta.b64 p, [%1], %2;\nselp.u32 %0, 1, 0, p;\n}"
                 : "=r"(ok) : "r"(bar), "r"(parity) : "memory");
    return ok;
}
__device__ __forceinline__ bool mbar_test(uint32_t bar, uint32_t parity) {
    uint32_t ok;
    asm volatile("{\n.reg .pred p;\nmbarrier.test_wait.parity.shared::cta.b64 p, [%1], %2;\nselp.u32 %0, 1, 0, p;\n}"
                 : "=r"(ok) : "r"(bar), "r"(parity) : "memory");
    return ok;
}
__device__ __forceinline__ bool mbar_try_cluster(uint32_t bar, uint32_t parity) {
    uint32_t ok;
    asm volatile("{\n.reg .pred p;\nmbarrier.try_wait.parity.acquire.cluster.shared::cta.b64 p, [%1], %2;\nselp.u32 %0, 1, 0, p;\n}"
                 : "=r"(ok) : "r"(bar), "r"(parity) : "memory");
    return ok;
}
constexpr int SPIN_LIMIT = 1 << 20;
__device__ __forceinline__ void mbar_wait(uint32_t bar, uint32_t parity) {
    if (mbar_try(bar, parity)) return;
    int n = 0;
    while (!mbar_try(bar, parity) && ++n < SPIN_LIMIT) {}
}
__device__ __forceinline__ void mbar_wait_cluster(uint32_t bar, uint32_t parity) {
    int n = 0;
    while (!mbar_try_cluster(bar, parity) && ++n < SPIN_LIMIT) {}
}
__device__ __forceinline__ void mbar_wait_sleep(uint32_t bar, uint32_t parity) {
    int n = 0;
    while (!mbar_try(bar, parity) && ++n < SPIN_LIMIT) __nanosleep(SLEEP_NS);
}
__device__ __forceinline__ void mbar_arrive(uint32_t bar) {
    asm volatile("mbarrier.arrive.shared::cta.b64 _, [%0];" ::"r"(bar) : "memory");
}
__device__ __forceinline__ void mbar_arrive_cluster(uint32_t cluster_bar) {
    asm volatile("mbarrier.arrive.shared::cluster.b64 _, [%0];" ::"r"(cluster_bar) : "memory");
}
__device__ __forceinline__ void mbar_expect_tx(uint32_t bar, uint32_t bytes) {
    asm volatile("mbarrier.arrive.expect_tx.shared::cta.b64 _, [%0], %1;" ::"r"(bar), "r"(bytes) : "memory");
}
__device__ __forceinline__ bool elect_one() {
    uint32_t p;
    asm volatile("{\n.reg .pred p;\nelect.sync _|p, 0xffffffff;\nselp.u32 %0, 1, 0, p;\n}" : "=r"(p));
    return p;
}
__device__ __forceinline__ uint32_t mapa(uint32_t addr, uint32_t rank) {
    uint32_t r;
    asm("mapa.shared::cluster.u32 %0, %1, %2;" : "=r"(r) : "r"(addr), "r"(rank));
    return r;
}
__device__ __forceinline__ uint32_t clock32() { uint32_t t; asm volatile("mov.u32 %0, %%clock;" : "=r"(t)); return t; }
__device__ __forceinline__ void sleep_until(uint32_t t) {
    int n = 0;
    while ((int)(clock32() - t) < 0 && ++n < SPIN_LIMIT) __nanosleep(20);
}
__device__ __forceinline__ void yield(float last, uint32_t zero) {
    asm volatile("nanosleep.u32 %0;" ::"r"(__float_as_uint(last) & zero));
}
template <typename T> __device__ __forceinline__ T* at(T* p, uint32_t bytes) {
    asm("" : "+r"(bytes));
    return reinterpret_cast<T*>(reinterpret_cast<uintptr_t>(p) + bytes);
}
__device__ __forceinline__ void tma_2d(uint32_t dst, const CUtensorMap* tm, int c0, int c1, uint32_t bar) {
    asm volatile("cp.async.bulk.tensor.2d.shared::cluster.global.mbarrier::complete_tx::bytes [%0], [%1, {%3, %4}], [%2];"
                 ::"r"(dst), "l"(tm), "r"(bar), "r"(c0), "r"(c1) : "memory");
}
__device__ __forceinline__ void tma_2d_store(const CUtensorMap* tm, int c0, int c1, uint32_t src) {
    asm volatile("cp.async.bulk.tensor.2d.global.shared::cta.bulk_group [%0, {%2, %3}], [%1];"
                 ::"l"(tm), "r"(src), "r"(c0), "r"(c1) : "memory");
}
__device__ __forceinline__ void bulk_g2s(uint32_t dst, const void* src, uint32_t bytes, uint32_t bar) {
    asm volatile("cp.async.bulk.shared::cluster.global.mbarrier::complete_tx::bytes [%0], [%1], %2, [%3];"
                 ::"r"(dst), "l"(src), "r"(bytes), "r"(bar) : "memory");
}
__device__ __forceinline__ void bulk_s2g(void* dst, uint32_t src, uint32_t bytes) {
    asm volatile("cp.async.bulk.global.shared::cta.bulk_group [%0], [%1], %2;" ::"l"(dst), "r"(src), "r"(bytes) : "memory");
}
__device__ __forceinline__ void st_async4(uint32_t dst, uint32_t a, uint32_t b, uint32_t c, uint32_t d, uint32_t bar) {
    asm volatile("st.async.weak.shared::cluster.mbarrier::complete_tx::bytes.v4.b32 [%0], {%1,%2,%3,%4}, [%5];"
                 ::"r"(dst), "r"(a), "r"(b), "r"(c), "r"(d), "r"(bar) : "memory");
}
__device__ __forceinline__ void bulk_commit() { asm volatile("cp.async.bulk.commit_group;" ::: "memory"); }
template <int N> __device__ __forceinline__ void bulk_wait_read() { asm volatile("cp.async.bulk.wait_group.read %0;" ::"n"(N) : "memory"); }
template <int N> __device__ __forceinline__ void bulk_wait() { asm volatile("cp.async.bulk.wait_group %0;" ::"n"(N) : "memory"); }
__device__ __forceinline__ void fence_async_smem() { asm volatile("fence.proxy.async.shared::cta;" ::: "memory"); }
__device__ __forceinline__ void fence_async_global() { asm volatile("fence.proxy.async.global;" ::: "memory"); }
__device__ __forceinline__ void prefetch_tmap(const CUtensorMap* tm) {
    asm volatile("prefetch.tensormap [%0];" ::"l"(tm) : "memory");
}
__device__ __forceinline__ unsigned long long ld_acquire64(const unsigned long long* p) {
    unsigned long long v; asm volatile("ld.acquire.gpu.global.u64 %0, [%1];" : "=l"(v) : "l"(p) : "memory"); return v;
}
__device__ __forceinline__ unsigned load_epoch(int b) {
    unsigned v; asm volatile("ld.global.u32 %0, [%1];" : "=r"(v) : "l"(at(g_epoch, b * 4)) : "memory"); return v + 1;
}
__device__ __forceinline__ unsigned ld_relaxed(const void* p) {
    unsigned v; asm volatile("ld.relaxed.gpu.global.u32 %0, [%1];" : "=r"(v) : "l"(p) : "memory"); return v;
}
__device__ __forceinline__ uint4 ld_relaxed128(const uint4* p) {
    uint4 v;
    asm volatile("{\n.reg .b128 t;\n.reg .b64 lo, hi;\nld.relaxed.gpu.global.b128 t, [%4];\nmov.b128 {lo, hi}, t;\n"
                 "mov.b64 {%0, %1}, lo;\nmov.b64 {%2, %3}, hi;\n}"
                 : "=r"(v.x), "=r"(v.y), "=r"(v.z), "=r"(v.w) : "l"(p) : "memory");
    return v;
}
__device__ __forceinline__ void st_relaxed128(uint4* p, const uint4& v) {
    asm volatile("{\n.reg .b128 t;\n.reg .b64 lo, hi;\nmov.b64 lo, {%1, %2};\nmov.b64 hi, {%3, %4};\nmov.b128 t, {lo, hi};\n"
                 "st.relaxed.gpu.global.b128 [%0], t;\n}"
                 ::"l"(p), "r"(v.x), "r"(v.y), "r"(v.z), "r"(v.w) : "memory");
}
__device__ __forceinline__ void st_relaxed64(unsigned long long* p, unsigned long long v) {
    asm volatile("st.relaxed.gpu.global.u64 [%0], %1;" ::"l"(p), "l"(v) : "memory");
}
__device__ __forceinline__ void st_release8(void* p, unsigned v) {
    asm volatile("st.release.gpu.global.u8 [%0], %1;" ::"l"(p), "r"(v) : "memory");
}
__device__ __forceinline__ uint64_t policy_evict_first() {
    uint64_t pol;
    asm("createpolicy.fractional.L2::evict_first.b64 %0, 1.0;" : "=l"(pol));
    return pol;
}
__device__ __forceinline__ uint4 ldg_stream(const void* p, uint64_t pol) {
    uint4 v;
    asm volatile("ld.global.nc.L1::no_allocate.L2::cache_hint.v4.u32 {%0,%1,%2,%3}, [%4], %5;"
                 : "=r"(v.x), "=r"(v.y), "=r"(v.z), "=r"(v.w) : "l"(p), "l"(pol));
    return v;
}
template <int ID, int N> __device__ __forceinline__ void named_arrive() { asm volatile("bar.arrive %0, %1;" ::"n"(ID), "n"(N) : "memory"); }
template <int ID, int N> __device__ __forceinline__ void named_bar() { asm volatile("bar.sync %0, %1;" ::"n"(ID), "n"(N) : "memory"); }

__device__ __forceinline__ float bf_lo(uint32_t u) { return __uint_as_float(u << 16); }
__device__ __forceinline__ float bf_hi(uint32_t u) { return __uint_as_float(u & 0xffff0000u); }
__device__ __forceinline__ uint32_t pack_bf(float lo, float hi) {
    uint32_t r; asm("cvt.rn.bf16x2.f32 %0, %1, %2;" : "=r"(r) : "f"(hi), "f"(lo)); return r;
}
__device__ __forceinline__ float rbf(float v) { return __uint_as_float(pack_bf(0.f, v)); }
__device__ __forceinline__ float sqrt_f(float v) { float r; asm("sqrt.approx.f32 %0, %1;" : "=f"(r) : "f"(v)); return r; }
__device__ __forceinline__ float rcp_f(float v) { float r; asm("rcp.approx.f32 %0, %1;" : "=f"(r) : "f"(v)); return r; }
__device__ __forceinline__ float silu_f(float z) { return __fdividef(z, 1.0f + __expf(-z)); }
__device__ __forceinline__ uint32_t bsub2(uint32_t a, uint32_t b) {
    uint32_t r; asm("sub.rn.bf16x2 %0, %1, %2;" : "=r"(r) : "r"(a), "r"(b)); return r;
}
__device__ __forceinline__ uint32_t bfma2(uint32_t a, uint32_t b, uint32_t c) {
    uint32_t r; asm("fma.rn.bf16x2 %0, %1, %2, %3;" : "=r"(r) : "r"(a), "r"(b), "r"(c)); return r;
}
__device__ __forceinline__ uint32_t norm2(uint32_t xv, float m, float rinv) {
    uint32_t t = pack_bf(bf_lo(xv) - m, bf_hi(xv) - m);
    return pack_bf(bf_lo(t) * rinv, bf_hi(t) * rinv);
}
__device__ __forceinline__ float gate1(float z) {
    float t;
    const float h = 0.5f * z;
    asm("tanh.approx.f32 %0, %1;" : "=f"(t) : "f"(h));
    return fmaf(h, t, h);
}
__device__ __forceinline__ uint32_t gate2(uint32_t xv, uint32_t mean2, float r0, float r1) {
    const uint32_t t = bsub2(xv, mean2);
    return pack_bf(gate1(bf_lo(t) * r0), gate1(bf_hi(t) * r1));
}
__device__ __forceinline__ uint32_t silu2(uint32_t z) { return pack_bf(silu_f(bf_lo(z)), silu_f(bf_hi(z))); }

__device__ __forceinline__ void stmatrix4(uint32_t addr, uint32_t r0, uint32_t r1, uint32_t r2, uint32_t r3) {
    asm volatile("stmatrix.sync.aligned.m8n8.x4.shared.b16 [%0], {%1,%2,%3,%4};"
                 ::"r"(addr), "r"(r0), "r"(r1), "r"(r2), "r"(r3));
}
__device__ __forceinline__ void stmatrix4t(uint32_t addr, uint32_t r0, uint32_t r1, uint32_t r2, uint32_t r3) {
    asm volatile("stmatrix.sync.aligned.m8n8.x4.trans.shared.b16 [%0], {%1,%2,%3,%4};"
                 ::"r"(addr), "r"(r0), "r"(r1), "r"(r2), "r"(r3));
}
__device__ __forceinline__ void ldmatrix4t(uint32_t addr, uint32_t& r0, uint32_t& r1, uint32_t& r2, uint32_t& r3) {
    asm volatile("ldmatrix.sync.aligned.m8n8.x4.trans.shared.b16 {%0,%1,%2,%3}, [%4];"
                 : "=r"(r0), "=r"(r1), "=r"(r2), "=r"(r3) : "r"(addr));
}

__device__ __forceinline__ void wg_fence() { asm volatile("wgmma.fence.sync.aligned;" ::: "memory"); }
__device__ __forceinline__ void wg_commit() { asm volatile("wgmma.commit_group.sync.aligned;" ::: "memory"); }
template <int N> __device__ __forceinline__ void wg_wait() { asm volatile("wgmma.wait_group.sync.aligned %0;" ::"n"(N) : "memory"); }

__host__ __device__ constexpr uint32_t desc_lo(uint32_t addr, uint32_t lbo) { return ((addr & 0x3FFFF) >> 4) | ((lbo >> 4) << 16); }
#define DESC_HI "0x40000040"

#define R8(a, o) "+f"(a[(o) + 0]), "+f"(a[(o) + 1]), "+f"(a[(o) + 2]), "+f"(a[(o) + 3]), \
                 "+f"(a[(o) + 4]), "+f"(a[(o) + 5]), "+f"(a[(o) + 6]), "+f"(a[(o) + 7])
#define R64(a, o) R8(a, (o) + 0), R8(a, (o) + 8), R8(a, (o) + 16), R8(a, (o) + 24), \
                  R8(a, (o) + 32), R8(a, (o) + 40), R8(a, (o) + 48), R8(a, (o) + 56)

template <int O, int TA>
__device__ __forceinline__ void wgmma128(float (&a)[128], uint32_t da, uint32_t db, int scale_d) {
    asm volatile(
        "{\n.reg .pred p;\n.reg .b64 da, db;\nsetp.ne.b32 p, %66, 0;\n"
        "mov.b64 da, {%64, " DESC_HI "};\nmov.b64 db, {%65, " DESC_HI "};\n"
        "wgmma.mma_async.sync.aligned.m64n128k16.f32.bf16.bf16 "
        "{%0,%1,%2,%3,%4,%5,%6,%7,%8,%9,%10,%11,%12,%13,%14,%15,"
        "%16,%17,%18,%19,%20,%21,%22,%23,%24,%25,%26,%27,%28,%29,%30,%31,"
        "%32,%33,%34,%35,%36,%37,%38,%39,%40,%41,%42,%43,%44,%45,%46,%47,"
        "%48,%49,%50,%51,%52,%53,%54,%55,%56,%57,%58,%59,%60,%61,%62,%63},"
        "da, db, p, 1, 1, %67, 0;\n}"
        : R64(a, O)
        : "r"(da), "r"(db), "r"(scale_d), "n"(TA));
}
template <int O>
__device__ __forceinline__ void wgmma128_rs(float (&a)[128], const uint32_t* f, uint32_t db) {
    asm volatile(
        "{\n.reg .b64 db;\nmov.b64 db, {%68, 8};\n"
        "wgmma.mma_async.sync.aligned.m64n128k16.f32.bf16.bf16 "
        "{%0,%1,%2,%3,%4,%5,%6,%7,%8,%9,%10,%11,%12,%13,%14,%15,"
        "%16,%17,%18,%19,%20,%21,%22,%23,%24,%25,%26,%27,%28,%29,%30,%31,"
        "%32,%33,%34,%35,%36,%37,%38,%39,%40,%41,%42,%43,%44,%45,%46,%47,"
        "%48,%49,%50,%51,%52,%53,%54,%55,%56,%57,%58,%59,%60,%61,%62,%63},"
        "{%64, %65, %66, %67}, db, 1, 1, 1, 0;\n}"
        : R64(a, O)
        : "r"(f[0]), "r"(f[1]), "r"(f[2]), "r"(f[3]), "r"(db));
}
template <int O>
__device__ __forceinline__ void fence_regs64(float (&a)[128]) {
    asm volatile("" : R64(a, O)::"memory");
}

struct Params {
    const __nv_bfloat16* x;
    const __nv_bfloat16* dre;
    const __nv_bfloat16* dim;
    const __nv_bfloat16* wr;
    const __nv_bfloat16* wg;
    const __nv_bfloat16* wu;
    const __nv_bfloat16* wd;
    uint32_t zero;
#define AB g_ab
};

__device__ __forceinline__ float warp_sum(float v) {
#pragma unroll
    for (int o = 16; o; o >>= 1) v += __shfl_xor_sync(0xffffffffu, v, o);
    return v;
}
__device__ __forceinline__ void fma8(float* acc, const uint4& w, float s) {
    acc[0] += s * bf_lo(w.x); acc[1] += s * bf_hi(w.x); acc[2] += s * bf_lo(w.y); acc[3] += s * bf_hi(w.y);
    acc[4] += s * bf_lo(w.z); acc[5] += s * bf_hi(w.z); acc[6] += s * bf_lo(w.w); acc[7] += s * bf_hi(w.w);
}
__device__ __forceinline__ int POS(int t) { return (t & ~15) | ((t & 6) << 1) | ((t & 8) >> 2) | (t & 1); }
__host__ __device__ constexpr int PSLOT(int j) { return j < 4 ? j : (j & 1) + ((j & 2) ? 0 : 4); }
__host__ __device__ constexpr int PPAR(int j) { return j < 4 ? 0 : ((j >> 2) ^ (j >> 1) ^ 1) & 1; }
__host__ __device__ constexpr int DSLOT(int it) { return (it & 3) + 2; }
__device__ __forceinline__ int SREC(int t) { return (t & ~15) | ((t & 3) << 2) | ((t >> 2) & 3); }
__device__ __forceinline__ int KO(int cl) { return ((cl & 1) << 1) | (cl >> 1); }

__global__ void __cluster_dims__(2, 1, 1) __launch_bounds__(NTHREADS, 1)
fnet_fused_kernel(const __grid_constant__ CUtensorMap tm_x, const __grid_constant__ CUtensorMap tm_dre,
                  const __grid_constant__ CUtensorMap tm_dim, const __grid_constant__ CUtensorMap tm_cre,
                  const __grid_constant__ CUtensorMap tm_cim, const __grid_constant__ CUtensorMap tm_out,
                  const __grid_constant__ CUtensorMap tm_x64,
                  const Params P) {
    extern __shared__ __align__(1024) uint8_t smem[];
    const unsigned long long tstart = clock64();
    const uint32_t sb = smem_u32(smem);
    const int tid = threadIdx.x, lane = tid & 31;
    const int warp = __shfl_sync(0xffffffffu, tid >> 5, 0);
    const int pr = blockIdx.x >> 1, p7 = ((pr - 36) * 37) >> 8;
    const int c = blockIdx.x & 1;
    const int gi = pr < 4 ? 7 : pr < 36 ? 2 * ((pr - 4) & 7) + (((pr - 4) >> 2) & 1) : 2 * (pr - 36 - 7 * p7) + 1 + (pr - 36 - 7 * p7 > 2);
    const int g = gi & 7;
    const int r = (gi >> 3) * 4 + (pr < 4 ? pr : pr < 36 ? (pr - 4) >> 3 : p7);
#define BLK(n) ((n) - ((n) <= g))
    const int grp = 2 * r + c;
    const int b = g * 16 + grp;
    const uint32_t bar0 = sb + OFF_BAR;
    const uint32_t zero = P.zero;
#define BAR(i) (bar0 + 8u * (i))
#define XBAR(i) (sb + OFF_XB + 64 + 8u * (i))
#define CLUSTER_ARRIVE() asm volatile("barrier.cluster.arrive.relaxed.aligned;" ::: "memory")
#define CLUSTER_WAIT() asm volatile("barrier.cluster.wait.aligned;" ::: "memory")
    if ((sb & 0xffffffu) != SB0) return;

#define LOAD0(it) do { \
            mbar_expect_tx(BAR(B_FS + DSLOT(it)), SLOT); tma_2d(sb + OFF_S + DSLOT(it) * SLOT, tmD, (it) * 64, r * 128, BAR(B_FS + DSLOT(it))); \
            mbar_expect_tx(BAR(B_FL + (it)), SLOT); tma_2d(sb + OFF_L + (it) * SLOT, &tm_x, (it) * 64, g * 256, BAR(B_FL + (it))); \
            mbar_expect_tx(BAR(B_FL + 4 + (it)), SLOT); tma_2d(sb + OFF_L + (4 + (it)) * SLOT, &tm_x, (it) * 64, g * 256 + 128, BAR(B_FL + 4 + (it))); \
        } while (0)
    if (warp == 13) {
        if (elect_one()) {
            const CUtensorMap* tmD = c ? &tm_dim : &tm_dre;
            prefetch_tmap(&tm_x);
            mbar_init(BAR(B_FS + 2), 1); mbar_init(BAR(B_FL), 1); mbar_init(BAR(B_FL + 4), 1);
            asm volatile("fence.mbarrier_init.release.cluster;" ::: "memory");
            LOAD0(0);
        }
        __syncwarp();
    }
    if (warp == 12) {
        if (elect_one()) {
#pragma unroll
            for (int i = 1; i < 4; i++) { mbar_init(BAR(B_FS + 2 + i), 1); mbar_init(BAR(B_FL + i), 1); mbar_init(BAR(B_FL + 4 + i), 1); }
#pragma unroll
            for (int i = 0; i < 4; i++) mbar_init(XBAR(i), 1);
            asm volatile("fence.mbarrier_init.release.cluster;" ::: "memory");
        }
        __syncwarp();
    }
    if (warp == 14) {
        if (elect_one()) {
#pragma unroll
            for (int i = 0; i < 8; i++) { mbar_init(BAR(B_EL + i), 1); mbar_init(XBAR(4 + i), 1); if (i < 6) mbar_init(BAR(B_ES + i), 2); }
            asm volatile("fence.mbarrier_init.release.cluster;" ::: "memory");
        }
        __syncwarp();
    }
    if (warp == 15) {
        if (elect_one()) {
            mbar_init(BAR(B_FS), 1); mbar_init(BAR(B_FS + 1), 1);
#pragma unroll
            for (int i = B_SRD; i < B_COUNT; i++) mbar_init(BAR(i), i == B_GO ? 2 : i == B_STATS || i == B_LST ? 4 : 1);
#pragma unroll
            for (int i = 0; i < 4; i++) mbar_expect_tx(BAR(B_RECV + i), SLOT / 2);
            mbar_expect_tx(BAR(B_PEER), 1024); mbar_expect_tx(BAR(B_H), 128);
            asm volatile("fence.mbarrier_init.release.cluster;" ::: "memory");
        }
        __syncwarp();
    }
    CLUSTER_ARRIVE();

#define GATHER(ptr, cnt, valid) do { int n = 0; bool ok; do { ok = true; \
                _Pragma("unroll") for (int i = 0; i < (cnt); i++) { f[i] = ld_relaxed128((ptr) + i * 32); ok = ok && (valid); } \
                if (__all_sync(0xffffffffu, ok)) break; \
                __nanosleep(GSL); \
            } while (++n < SPIN_LIMIT); } while (0)
    if (warp >= 8 && warp < 12) {
        asm volatile("setmaxnreg.dec.sync.aligned.u32 %0;" ::"n"(512 - PROD_REGS - 2 * CONS_REGS));
        const int aw = warp - 8, mt = tid - 256;
        unsigned ep;
        {
            const uint8_t* rp = smem + OFF_S + aw * 2048 + lane * 16;
            const __nv_bfloat16* dp = at(c ? P.dim : P.dre, (r * 128 + g * 16 + aw * 4) * D_ * 2);
            float wf[32], sw = 0.f;
#pragma unroll
            for (int i = 0; i < 4; i++) {
                const uint4 w = __ldg(reinterpret_cast<const uint4*>(at(P.wr, lane * 16) + i * 256));
                const uint32_t wv[4] = {w.x, w.y, w.z, w.w};
#pragma unroll
                for (int e = 0; e < 4; e++) { wf[8 * i + 2 * e] = bf_lo(wv[e]); wf[8 * i + 2 * e + 1] = bf_hi(wv[e]); sw = (sw + bf_lo(wv[e])) + bf_hi(wv[e]); }
            }
            ep = load_epoch(b);
            sw = warp_sum(sw);
            CLUSTER_WAIT();
            float x0[4] = {}, s1[4] = {}, s2[4] = {}, sx[4] = {}, sd[4] = {};
#define PUSH(a, v) do { a[0] = a[1]; a[1] = a[2]; a[2] = a[3]; a[3] = v; } while (0)
#pragma unroll 1
            for (int k = 0; k < 4; k++) {
                mbar_wait(XBAR(k), 0);
                uint4 v[4];
#pragma unroll
                for (int i = 0; i < 4; i++) v[i] = *reinterpret_cast<const uint4*>(rp + k * 8192 + i * 512);
                uint32_t sh = v[0].x << 16;
                float a1s = 0.f, a2s = 0.f, axs = 0.f;
#pragma unroll
                for (int i = 0; i < 4; i++) {
                    sh = __shfl_sync(0xffffffffu, sh | (__float_as_uint(axs) & zero), 0);
                    const uint32_t xv[4] = {v[i].x, v[i].y, v[i].z, v[i].w};
#pragma unroll
                    for (int e = 0; e < 4; e++) {
                        const float a0 = bf_lo(xv[e]) - __uint_as_float(sh), a1 = bf_hi(xv[e]) - __uint_as_float(sh);
                        a1s += a0 + a1;
                        a2s = fmaf(a0, a0, fmaf(a1, a1, a2s));
                        axs = fmaf(a0, wf[8 * i + 2 * e], fmaf(a1, wf[8 * i + 2 * e + 1], axs));
                    }
                }
                PUSH(x0, __uint_as_float(sh)); PUSH(s1, a1s); PUSH(s2, a2s); PUSH(sx, axs);
                fence_async_smem();
                __syncwarp();
                if (elect_one()) {
                    const uint32_t db = XBAR(k == 3 ? 8 + aw : 4 + aw);
                    if (k == 0 || k == 3) mbar_expect_tx(db, k ? 2048 : 6144);
                    bulk_g2s(sb + OFF_S + k * 8192 + aw * 2048, dp + k * D_, 2048, db);
                }
            }
#define FOLD4(a) do { const bool u16 = lane & 16, u8 = lane & 8; \
                float p0 = (u16 ? a[2] : a[0]) + __shfl_xor_sync(0xffffffffu, u16 ? a[0] : a[2], 16); \
                float p1 = (u16 ? a[3] : a[1]) + __shfl_xor_sync(0xffffffffu, u16 ? a[1] : a[3], 16); \
                a[0] = (u8 ? p1 : p0) + __shfl_xor_sync(0xffffffffu, u8 ? p0 : p1, 8); \
                _Pragma("unroll") for (int o = 4; o; o >>= 1) a[0] += __shfl_xor_sync(0xffffffffu, a[0], o); } while (0)
#pragma unroll 1
            for (int k = 0; k < 4; k++) {
                mbar_wait(XBAR(k == 3 ? 8 + aw : 4 + aw), 0);
                float run = 0.f;
#pragma unroll
                for (int i = 0; i < 4; i++) {
                    const uint4 v = *reinterpret_cast<const uint4*>(rp + k * 8192 + i * 512);
                    const uint32_t dv[4] = {v.x, v.y, v.z, v.w};
#pragma unroll
                    for (int e = 0; e < 4; e++) run += bf_lo(dv[e]) + bf_hi(dv[e]);
                }
                PUSH(sd, run);
            }
            named_bar<4, 128>();
            if (mt < 12) asm volatile("mbarrier.inval.shared::cta.b64 [%0];" ::"r"(XBAR(mt)) : "memory");
            FOLD4(sd); FOLD4(s1); FOLD4(s2); FOLD4(sx);
            const float nb = __shfl_down_sync(0xffffffffu, sd[0], 8);
            if ((lane & 15) == 0)
                st_relaxed128(at(g_rs, (grp * 64 + g * 8 + aw * 2 + (lane >> 4)) * 16), make_uint4(__float_as_uint(sd[0]), ep, __float_as_uint(nb), ep));
            if (mt == 0) PROF_T(6);
            const int rr = lane >> 3;
            const float c0 = rr == 0 ? x0[0] : rr == 1 ? x0[1] : rr == 2 ? x0[2] : x0[3];
            const float dm = s1[0] * (1.0f / D_);
            const float mb = rbf(c0 + dm);
            const float rinv = rcp_f(rbf(sqrt_f(rbf(rbf(fmaxf(s2[0] * (1.0f / D_) - dm * dm, 0.f)) + 1e-5f))));
            if ((lane & 7) == 0) st_relaxed128(at(g_stat, (b * 16 + aw * 4 + rr) * 16), make_uint4(__float_as_uint(mb), __float_as_uint(rinv), ep, 0));
            unsigned u = __bfloat16_as_ushort(__float2bfloat16_rn((sx[0] + (c0 - mb) * sw) * rinv));
            u = (u & 0x8000u) ? (~u & 0xffffu) : (u | 0x8000u);
            u = (u << 16) | (0xffffu - (unsigned)(b * 16 + rr * 4 + aw));
            u = __reduce_max_sync(0xffffffffu, u);
            if (lane == 0) { *reinterpret_cast<unsigned*>(smem + OFF_XB + aw * 4) = u; mbar_arrive(BAR(B_LST)); }
            if (mt == 0) PROF_T(2);
            uint4 f[4];
            if (aw < 2) {
                const int t = SREC(aw * 128 + lane);
                GATHER(at(g_stat, (g * 256 + aw * 128 + lane) * 16), 4, f[i].z == ep);
#pragma unroll
                for (int i = 0; i < 4; i++) {
                    *reinterpret_cast<uint32_t*>(smem + OFF_RSTD + (POS(t) + i * 32) * 4) = f[i].y;
                    *reinterpret_cast<uint16_t*>(smem + OFF_MEAN + (POS(t) + i * 32) * 2) = (uint16_t)(f[i].x >> 16);
                }
            } else {
                const int e2 = (aw - 2) * 32 + lane;
                GATHER(at(g_rs, (grp * 64 + e2) * 16), 1, f[i].y == ep && f[i].w == ep);
#pragma unroll
                for (int i = 0; i < 2; i++) {
                    const float v = __uint_as_float(i ? f[0].z : f[0].x);
                    const float hi = rbf(v), mid = rbf(v - hi), lo = v - hi - mid;
                    *reinterpret_cast<uint4*>(smem + OFF_RS + (e2 * 2 + i) * 16) = make_uint4(pack_bf(hi, mid), pack_bf(lo, 0.f), 0, 0);
                }
            }
            fence_async_smem();
            __syncwarp();
            if (lane == 0) mbar_arrive(BAR(B_STATS));
            if (mt == 127) PROF_T(9);
        }
        const bool moe = pr < 28 || pr >= 36;
        const int pair = pr < 28 ? pr : pr - 8;
        if (moe) {
            const uint64_t pol = policy_evict_first();
            const __nv_bfloat16* wp = at((aw & 1) ? P.wu : P.wg, ((c * 512 + (aw >> 1) * 256 + (lane >> 3) * 8) * F_ + pair * 64 + (lane & 7) * 8) * 2);
            uint4 b0[8], b1[8];
#define FILL(buf, str) do { _Pragma("unroll") for (int q = 0; q < 8; q++) buf[q] = ldg_stream(wp + q * (str), pol); } while (0)
#define PAUSE() do { if (mbar_test(BAR(B_QUIET), 0)) mbar_wait_sleep(BAR(B_GO), 0); } while (0)
            FILL(b0, F_);
            mbar_wait(BAR(B_SEL), 0);
            uint4 xn;
            {
                const int sel = ~*reinterpret_cast<volatile unsigned*>(smem + OFF_SEL) & (S_ - 1);
                xn = __ldg(reinterpret_cast<const uint4*>(at(P.x, (sel * D_ + c * 512 + (aw >> 1) * 256 + (lane & 7) * 32 + (lane >> 3) * 8) * 2)));
                uint4 f[1];
                GATHER(at(g_stat, SREC(sel) * 16), 1, f[i].z == ep);
                wp += 32 * F_; FILL(b1, F_); wp -= 32 * F_;
                PAUSE();
                const float m = __uint_as_float(f[0].x), ri = __uint_as_float(f[0].y);
                xn = make_uint4(norm2(xn.x, m, ri), norm2(xn.y, m, ri), norm2(xn.z, m, ri), norm2(xn.w, m, ri));
            }
            float ag[8];
#pragma unroll
            for (int i = 0; i < 8; i++) ag[i] = 0.f;
#define ROUND(cur, nxt, rd) do { \
                PAUSE(); \
                if (lane == 0) TRACE(192 + aw * 12 + (rd)); \
                if ((rd) == 7) wp = at(P.wd - 16 * D_, ((pair * 64 + (lane >> 4) * 8) * D_ + c * 512 + aw * 128 + (lane & 15) * 8) * 2); \
                wp = at(wp, ((rd) < 7 ? 64 * F_ : 32 * D_) + (cur[7].x & zero)); \
                if ((rd) & 7) { if ((rd) < 7) FILL(nxt, F_); else if ((rd) < 11) FILL(nxt, D_); } \
                _Pragma("unroll") for (int q = 0; q < 8; q += 2) { \
                    const uint32_t xw = __shfl_sync(0xffffffffu, q == 0 ? xn.x : q == 2 ? xn.y : q == 4 ? xn.z : xn.w, (lane & 24) | ((rd) & 7)); \
                    fma8(ag, cur[q], bf_lo(xw)); \
                    fma8(ag, cur[q + 1], bf_hi(xw)); \
                    if (q < 6) yield(ag[7], zero); \
                } } while (0)
#pragma unroll 1
            for (int rd = 0; rd < 12; rd += 2) {
                ROUND(b0, b1, rd);
                ROUND(b1, b0, rd + 1);
                if (rd == 6 || rd == 10) {
#pragma unroll
                    for (int i = 0; i < 8; i++) ag[i] += __shfl_xor_sync(0xffffffffu, ag[i], 16);
                }
                if (rd == 6) {
#pragma unroll
                    for (int i = 0; i < 8; i++) ag[i] += __shfl_xor_sync(0xffffffffu, ag[i], 8);
                    if (lane < 8) {
                        const uint32_t dst = mapa(sb + OFF_XB + (c * 4 + aw) * 128 + (lane & 3) * 32, lane >> 2), pb = mapa(BAR(B_PEER), lane >> 2);
                        st_async4(dst, __float_as_uint(ag[0]), __float_as_uint(ag[1]), __float_as_uint(ag[2]), __float_as_uint(ag[3]), pb);
                        st_async4(dst + 16, __float_as_uint(ag[4]), __float_as_uint(ag[5]), __float_as_uint(ag[6]), __float_as_uint(ag[7]), pb);
                    }
                    __syncwarp();
                    wp += 16 * D_; FILL(b1, D_); wp -= 16 * D_;
                    if (aw == 3) {
                        mbar_wait_cluster(BAR(B_PEER), 0);
                        const float* ps = reinterpret_cast<const float*>(smem + OFF_XB) + lane;
                        const float go = (ps[0] + ps[64]) + (ps[128] + ps[192]), uo = (ps[32] + ps[96]) + (ps[160] + ps[224]);
                        const float h = rbf(silu_f(rbf(go))) * rbf(uo), ho = __shfl_xor_sync(0xffffffffu, h, 1);
                        asm volatile("st.async.weak.shared::cluster.mbarrier::complete_tx::bytes.b32 [%0], %1, [%2];"
                                     ::"r"(mapa(sb + OFF_H + c * 64 + (lane >> 1) * 4, lane & 1)), "r"((lane & 1) ? pack_bf(ho, h) : pack_bf(h, ho)),
                                       "r"(mapa(BAR(B_H), lane & 1)) : "memory");
                    }
                    mbar_wait_cluster(BAR(B_H), 0);
                    xn = *reinterpret_cast<const uint4*>(smem + OFF_H + (lane & 3) * 32 + (lane >> 4) * 16);
#pragma unroll
                    for (int i = 0; i < 8; i++) ag[i] = 0.f;
                    if (mt == 0) PROF_T(10);
                }
            }
            const int hi = lane >> 4;
            st_relaxed128(at(g_part, pair * 4096 + (c * 8 + aw * 2 + ((lane >> 3) & 1)) * 256 + hi * 128 + (lane & 7) * 16),
                          make_uint4((__float_as_uint(hi ? ag[4] : ag[0]) & ~15u) | (ep & 15u), __float_as_uint(hi ? ag[5] : ag[1]),
                                     __float_as_uint(hi ? ag[6] : ag[2]), __float_as_uint(hi ? ag[7] : ag[3])));
            if (mt == 0) PROF_T(11);
        } else {
            mbar_wait_sleep(BAR(B_SEL), 0);
        }
        const int sel = ~*reinterpret_cast<volatile unsigned*>(smem + OFF_SEL) & (S_ - 1);
        if ((sel >> 8) == g) {
            const int col = (lane & 7) * 8 + ((lane >> 3) & 1) * 4;
            const uint2 xv = __ldg(reinterpret_cast<const uint2*>(at(P.x, (sel * D_ + grp * 64 + col) * 2)));
            uint4 f[1];
            GATHER(at(g_stat, SREC(sel) * 16), 1, f[i].z == ep);
            const uint4 rec = f[0];
            const uint4* src = at(g_part, (aw * 14 + (lane >> 4)) * 4096 + grp * 256 + (lane & 15) * 16);
            if (!moe) {
                int n = 0;
                while (((ld_relaxed(src) ^ ep) & 15u) != 0 && ++n < SPIN_LIMIT) __nanosleep(500);
            }
            uint4 t[7];
            int n = 0;
            bool ok;
            do {
                ok = true;
#pragma unroll
                for (int u = 0; u < 7; u++) { t[u] = ld_relaxed128(src + u * 512); ok = ok && ((t[u].x ^ ep) & 15u) == 0; }
            } while (!__all_sync(0xffffffffu, ok) && ++n < SPIN_LIMIT);
            float4 a = make_float4(0.f, 0.f, 0.f, 0.f);
#pragma unroll
            for (int u = 0; u < 7; u++) {
                a.x += __uint_as_float(t[u].x & ~15u); a.y += __uint_as_float(t[u].y); a.z += __uint_as_float(t[u].z); a.w += __uint_as_float(t[u].w);
            }
            a.x += __shfl_xor_sync(0xffffffffu, a.x, 16); a.y += __shfl_xor_sync(0xffffffffu, a.y, 16);
            a.z += __shfl_xor_sync(0xffffffffu, a.z, 16); a.w += __shfl_xor_sync(0xffffffffu, a.w, 16);
            float4* park = reinterpret_cast<float4*>(smem + OFF_XB) + (lane & 15);
            if (lane < 16) park[aw * 16] = a;
            named_bar<4, 128>();
            if (aw == 0) {
                const float4 p1 = park[16], p2 = park[32], p3 = park[48];
                a.x = (a.x + p1.x) + (p2.x + p3.x); a.y = (a.y + p1.y) + (p2.y + p3.y);
                a.z = (a.z + p1.z) + (p2.z + p3.z); a.w = (a.w + p1.w) + (p2.w + p3.w);
                unsigned u = *reinterpret_cast<volatile unsigned*>(smem + OFF_SEL) >> 16;
                u = (u & 0x8000u) ? (u & 0x7fffu) : (~u & 0xffffu);
                const float sg = rbf(__fdividef(1.0f, 1.0f + __expf(-__uint_as_float(u << 16))));
                const float m = __uint_as_float(rec.x), ri = __uint_as_float(rec.y);
                const uint32_t n0 = norm2(xv.x, m, ri), n1 = norm2(xv.y, m, ri);
                uint2 o;
                o.x = silu2(pack_bf(bf_lo(n0) + rbf(rbf(a.x) * sg), bf_hi(n0) + rbf(rbf(a.y) * sg)));
                o.y = silu2(pack_bf(bf_lo(n1) + rbf(rbf(a.z) * sg), bf_hi(n1) + rbf(rbf(a.w) * sg)));
                if (lane < 16) *reinterpret_cast<uint2*>(smem + OFF_H + col * 2) = o;
                __syncwarp();
                if (lane == 0) { mbar_arrive(BAR(B_UPD)); PROF_T(12); }
            }
        }
    } else if (warp < 8) {
        asm volatile("setmaxnreg.inc.sync.aligned.u32 %0;" ::"n"(CONS_REGS));
        CLUSTER_WAIT();
        const int wg = warp >> 2, wq = warp & 3;
        const int wt = tid & 127;
        float acc[128];
        const uint32_t fL = BAR(B_FL + 4 * wg), eL = BAR(B_EL + 4 * wg);
        const uint32_t dL = desc_lo(SB0 + OFF_L, 16) + wg * 4096;
        constexpr uint32_t dS = desc_lo(SB0 + OFF_S, 16);
        constexpr uint32_t SL = SLOT >> 4;
#define RELEASE(ls, ss) do { if (wt == 0) { mbar_arrive(eL + 8u * (ls)); mbar_arrive(BAR(B_ES + (ss))); } } while (0)
#define WAIT_FULL(ls, lph, ss, sph) do { mbar_wait(BAR(B_FS + (ss)), sph); mbar_wait(fL + 8u * (ls), lph); } while (0)
#define TURN() do { if (wg) named_bar<6, 256>(); else named_bar<5, 256>(); } while (0)
#define PASS() do { if (wg) named_arrive<5, 256>(); else named_arrive<6, 256>(); } while (0)
#define WG_BAR() do { if (wg) named_bar<2, 128>(); else named_bar<1, 128>(); } while (0)
        if (wg == 1) PASS();

#define MMA1_H(O, s, first) do { _Pragma("unroll") for (int kk = 0; kk < 4; kk++) \
            wgmma128<O, 0>(acc, dL + (s) * SL + kk * 2 + (O) * 8, dS + DSLOT(s) * SL + kk * 2, !((first) && kk == 0)); } while (0)
#define WAIT1(s, ph) WAIT_FULL(s, ph, DSLOT(s), ph)
#define PROBE(ls, lph, ss, sph) (mbar_test(BAR(B_FS + (ss)), sph) & mbar_test(fL + 8u * (ls), lph))
#define REL1(s) RELEASE(s, DSLOT(s))
#pragma unroll 1
        for (int it = 0; it < 12; it++) {
            const int s = it & 3;
            const bool ok = PROBE(s, (it >> 2) & 1, DSLOT(s), (it >> 2) & 1);
            if (it) { wg_wait<0>(); REL1((s + 3) & 3); }
            if (!ok) WAIT1(s, (it >> 2) & 1);
            TURN();
            wg_fence(); MMA1_H(0, s, it == 0); MMA1_H(64, s, it == 0); wg_commit();
            PASS();
            if (it == 0 && tid == 0) PROF_T(16);
        }
        TS(12);
        float rs[4] = {};
        uint32_t nm[8] = {};
#define GET_STATS() do { mbar_wait(BAR(B_STATS), 0); \
            const int p0 = POS(wg * 128 + wq * 16 + (lane >> 2));                   \
            const uint32_t msk = (lane & 3) == 0 ? 0xffffffffu : (lane & 3) == 1 ? 0x0000ffffu : 0u; \
            _Pragma("unroll") for (int i = 0; i < 4; i++) { \
                const int p = p0 + (i & 1) * 2 + (i >> 1) * 64; \
                rs[i] = *reinterpret_cast<const float*>(smem + OFF_RSTD + p * 4); \
                const uint32_t m = *reinterpret_cast<const uint16_t*>(smem + OFF_MEAN + p * 2) ^ 0x8000u; \
                nm[i + (i & 2)] = (m | (m << 16)) & msk; \
            } } while (0)
        const bool early = wg || __all_sync(0xffffffffu, mbar_test(BAR(B_STATS), 0));
        if (early && !wg) GET_STATS();
        WAIT1(0, 1);
        TS(13);
        wg_wait<0>(); REL1(3);
        if (wg) GET_STATS();
        TS(14);
        TURN();
        wg_fence();
        MMA1_H(0, 0, false);
        if (tid == 0) { mbar_arrive(BAR(B_QUIET)); PROF_T(15); }
        WAIT1(1, 1); wg_fence(); MMA1_H(0, 1, false);
        WAIT1(2, 1); wg_fence(); MMA1_H(0, 2, false); wg_commit();
        if (!early) GET_STATS();
        asm volatile("" : "+r"(nm[0]), "+r"(nm[1]), "+r"(nm[2]), "+r"(nm[3]), "+r"(nm[4]), "+r"(nm[5]), "+r"(nm[6]), "+r"(nm[7])::"memory");
        wg_fence();
        wgmma128_rs<64>(acc, nm + 4, (SB0 + OFF_RS) >> 4);
        wgmma128_rs<0>(acc, nm, (SB0 + OFF_RS) >> 4);
        WAIT1(3, 1); wg_fence(); MMA1_H(0, 3, false); wg_commit();
        PASS();
        const int mrow = wq * 16 + ((lane >> 3) & 1) * 8 + (lane & 7);
#define EPI1(O, slot, FREE) do { const uint32_t dst = sb + OFF_S + (slot) * SLOT + mrow * 128; \
            uint32_t pk[32]; \
            _Pragma("unroll") for (int i = 0; i < 32; i += 4) { \
                _Pragma("unroll") for (int k = 0; k < 4; k++) \
                    pk[i + k] = pack_bf(acc[(O) + 2 * (i + k)] * rs[(O) / 32 + (k & 1)], acc[(O) + 2 * (i + k) + 1] * rs[(O) / 32 + (k & 1)]); \
                if (i == EF) { FREE; } \
                if (i >= EF) { _Pragma("unroll") for (int v = (i == EF ? 0 : i); v <= i; v += 4) \
                    stmatrix4(dst + ((v >> 4) ^ c ^ 1) * 8192 + ((((v >> 1) & 7) + (lane >> 4)) ^ (lane & 7)) * 16, pk[v], pk[v + 1], pk[v + 2], pk[v + 3]); } } \
            WG_BAR(); \
            if (wt == 0) mbar_arrive(BAR(B_FS + (slot))); } while (0)
        TS(15);
        wg_wait<0>();
        fence_regs64<0>(acc);
        TS(16);
        {
            constexpr int EF = 0;
            EPI1(0, wg, if (wg) mbar_wait(BAR(B_FS), 0));
        }
        TS(17);
        TURN();
        wg_fence();
        MMA1_H(64, 0, false); wg_commit();
        MMA1_H(64, 1, false); wg_commit();
        MMA1_H(64, 2, false); wg_commit();
        wg_wait<2>(); REL1(0);
        MMA1_H(64, 3, false); wg_commit();
        PASS();
        TS(18);
        wg_wait<2>(); REL1(1);
        mbar_wait(BAR(B_FS), 0); mbar_wait(BAR(B_FS + 1), 0); fence_async_smem();
        wg_wait<1>(); REL1(2);
        wg_wait<0>(); REL1(3);
        fence_regs64<64>(acc);
        TS(19);
        {
            constexpr int EF = 16;
            EPI1(64, 2 + wg, mbar_wait(BAR(B_ES + 2 + wg), 1));
        }
        TS(20);

        float ac2[128];
#define MMA2_H(O, ls, ss, first) do { _Pragma("unroll") for (int kk = 0; kk < 4; kk++) \
            wgmma128<O, 1>(ac2, dS + (ss) * SL + kk * 128 + (O) * 8, dL + (ls) * SL + kk * 2, !((first) && kk == 0)); } while (0)
#define WAIT2(j) WAIT_FULL((j) & 3, ((j) >> 2) & 1, PSLOT(j), PPAR(j))
#define MMA2(j) do { wg_fence(); MMA2_H(0, (j) & 3, PSLOT(j), (j) == 0); MMA2_H(64, (j) & 3, PSLOT(j), (j) == 0); wg_commit(); } while (0)
#define REL2(j) RELEASE((j) & 3, PSLOT(j))
        WAIT2(0); TURN(); MMA2(0);
        WAIT2(1); MMA2(1); PASS();
        TS(21);
        wg_wait<1>(); REL2(0);
        mbar_wait(BAR(B_FS + 2), 0); mbar_wait(BAR(B_FS + 3), 0); fence_async_smem();
        TS(22);
        {
            uint32_t l2 = 2, s2 = 2, sp = 1, lph = 0, sph = 0;
#pragma unroll 1
            for (int j = 2; j < XJ; j += 2) {
#pragma unroll
                for (int h = 0; h < 2; h++) {
                    const bool ok = PROBE(l2 + h, lph, s2 + h, sph);
                    wg_wait<0>(); RELEASE(h ? l2 : 3 - l2, h ? s2 : sp);
                    if (!ok) WAIT_FULL(l2 + h, lph, s2 + h, sph);
                    TURN();
                    wg_fence(); MMA2_H(0, l2 + h, s2 + h, false); MMA2_H(64, l2 + h, s2 + h, false); wg_commit();
                    PASS();
                    if (h == (GOJ & 1) && j == (GOJ & ~1) && wt == 0) { mbar_arrive(BAR(B_GO)); if (wg == 0) PROF_T(19); }
                }
                sp = s2 + 1; s2 = 2 * l2; sph = lph; l2 ^= 2;
                lph ^= l2 == 0;
            }
        }
        if (tid == 0) PROF_T(20);
        uint32_t gt[32];
        const uint32_t xrow = sb + OFF_S + 2 * SLOT + wg * 8192 + ((lane >> 4) * 8 + (lane & 7)) * 128 + (((2 * wq + ((lane >> 3) & 1)) ^ (lane & 7)) << 4);
        const uint32_t gsign = c ? 0x80008000u : 0u;
#define XOFF(v) (((v) >> 2) * SLOT + ((v) & 3) * 2048)
        mbar_wait(BAR(B_SEL), 0);
        const int sel = ~*reinterpret_cast<volatile unsigned*>(smem + OFF_SEL) & (S_ - 1);
        bool own = (sel >> 7) == 2 * g + wg;
#define PATCH() do { own = false; \
            const uint32_t v0 = *reinterpret_cast<const uint16_t*>(smem + OFF_H + (wq * 16 + (lane >> 2)) * 2) ^ gsign; \
            const uint32_t v1 = *reinterpret_cast<const uint16_t*>(smem + OFF_H + (wq * 16 + (lane >> 2)) * 2 + 16) ^ gsign; \
            const uint32_t pick = (lane & 3) != ((sel >> 1) & 3) ? 0x3210u : (sel & 1) ? 0x5410u : 0x3254u; \
            _Pragma("unroll") for (int i = 0; i < 16; i++) { \
                const uint32_t m = ((sel >> 3) & 15) == i ? pick : 0x3210u; \
                gt[2 * i] = __byte_perm(gt[2 * i], v0, m); \
                gt[2 * i + 1] = __byte_perm(gt[2 * i + 1], v1, m); \
            } } while (0)
#pragma unroll
        for (int u = 0; u < 8; u++) {
            WAIT2(XJ + u); wg_wait<0>(); REL2(XJ + u - 1); TURN(); MMA2(XJ + u); PASS();
            uint32_t* o = &gt[4 * u];
            if (!(u & 3)) mbar_wait(BAR(B_FS + 2 + (u >> 2)), 1);
            ldmatrix4t(xrow + XOFF(u), o[0], o[1], o[2], o[3]);
            const float4 r4 = *reinterpret_cast<const float4*>(smem + OFF_RSTD + (wg * 128 + u * 16 + (lane & 3) * 4) * 4);
            const uint2 m2 = *reinterpret_cast<const uint2*>(smem + OFF_MEAN + (wg * 128 + u * 16 + (lane & 3) * 4) * 2);
            o[0] = gate2(o[0], m2.x, r4.x, r4.y) ^ gsign;
            o[1] = gate2(o[1], m2.x, r4.x, r4.y) ^ gsign;
            o[2] = gate2(o[2], m2.y, r4.z, r4.w) ^ gsign;
            o[3] = gate2(o[3], m2.y, r4.z, r4.w) ^ gsign;
            asm volatile("st.shared.v2.u32 [%0], {%1,%2};" ::"r"(sb + OFF_SEL + 16), "r"(o[0] ^ o[1]), "r"(o[2] ^ o[3]) : "memory");
        }
        if (tid == 0) PROF_T(21);
        WAIT2(28);
        wg_wait<0>(); REL2(27);
        if (own) {
            const uint32_t t0 = clock32();
            bool ok;
            while (!(ok = mbar_test(BAR(B_UPD), 0)) && clock32() - t0 < wg * 1400u) __nanosleep(50);
            if (__all_sync(0xffffffffu, ok)) PATCH();
        }
        TS(0);
        TURN();
        wg_fence(); MMA2_H(0, 0, PSLOT(28), false); wg_commit();
        if (wg == 0) { wg_fence(); MMA2_H(64, 0, PSLOT(28), false); wg_commit(); }
        WAIT2(29); wg_fence(); MMA2_H(0, 1, PSLOT(29), false); wg_commit();
        WAIT2(30); wg_fence(); MMA2_H(0, 2, PSLOT(30), false); wg_commit();
        wg_wait<2>();
        if (tid == 0) mbar_arrive_cluster(mapa(BAR(B_RDY), c ^ 1));
        WAIT2(31); wg_fence(); MMA2_H(0, 3, PSLOT(31), false); wg_commit();
        TS(1);
#define KEEP(i) wgmma128<64, 1>(ac2, dS + PSLOT(29 + ((i) >> 2)) * SL + ((i) & 3) * 128 + 512, dL + (1 + ((i) >> 2)) * SL + ((i) & 3) * 2, 1)
        wg_fence();
#pragma unroll
        for (int i = 0; i < KQ; i++) KEEP(i);
        wg_commit();
        mbar_wait(BAR(B_RDY + wg), 0);
        wg_wait<1>();
        fence_regs64<0>(ac2);
        TS(2);
        wg_fence();
        {
            const uint32_t dst = mapa(sb + OFF_L + wg * SLOT + wt * 16, c ^ 1), rb = mapa(BAR(B_RECV + 2 * wg), c ^ 1);
#pragma unroll
            for (int v = 0; v < 8; v++) {
                if (KQ + v < 12) KEEP(KQ + v);
                if (KQ + v == 11) { wg_commit(); if (wg == 0) PASS(); }
                st_async4(dst + v * 2048, pack_bf(ac2[8 * v + 0], ac2[8 * v + 1]), pack_bf(ac2[8 * v + 2], ac2[8 * v + 3]),
                          pack_bf(ac2[8 * v + 4], ac2[8 * v + 5]), pack_bf(ac2[8 * v + 6], ac2[8 * v + 7]), rb + (v >> 2) * 8);
            }
        }
        if (wg == 1) { wg_fence(); MMA2_H(64, 0, PSLOT(28), false); wg_commit(); }
        TS(3);
        uint32_t xr[32];
#define LDX(v) ldmatrix4t(xrow + XOFF(v), xr[4 * (v)], xr[4 * (v) + 1], xr[4 * (v) + 2], xr[4 * (v) + 3])
#pragma unroll
        for (int v = 0; v < XE; v++) LDX(v);
        if (wg == 0) {
            wg_wait<0>();
            if (wt == 0) mbar_arrive_cluster(mapa(BAR(B_RDY + 1), c ^ 1));
        }
        TS(4);
        if (own) { mbar_wait(BAR(B_UPD), 0); PATCH(); }
        TS(5);
        uint4 rv[8];
#define FETCH(v0) do { if ((v0) == 0 || (v0) == 4) mbar_wait_cluster(BAR(B_RECV + 2 * wg + (v0) / 4), 0); \
            _Pragma("unroll") for (int v = (v0); v < (v0) + 2; v++) { \
                asm volatile("ld.shared.v4.u32 {%0,%1,%2,%3}, [%4];" : "=r"(rv[v].x), "=r"(rv[v].y), "=r"(rv[v].z), "=r"(rv[v].w) \
                             : "r"(sb + OFF_L + wg * SLOT + v * 2048 + wt * 16) : "memory"); \
                if (v >= XE) LDX(v); } } while (0)
        FETCH(0);
        TS(6);
        wg_wait<0>();
        fence_regs64<64>(ac2);
        TS(7);
#pragma unroll
        for (int v0 = 0; v0 < 8; v0 += 2) {
#pragma unroll
            for (int v = v0; v < v0 + 2; v++) {
                const float* a = &ac2[64 + 8 * v];
                stmatrix4t(xrow + XOFF(v),
                           bfma2(bsub2(pack_bf(a[0], a[1]), rv[v].x), gt[4 * v + 0], xr[4 * v + 0]),
                           bfma2(bsub2(pack_bf(a[2], a[3]), rv[v].y), gt[4 * v + 1], xr[4 * v + 1]),
                           bfma2(bsub2(pack_bf(a[4], a[5]), rv[v].z), gt[4 * v + 2], xr[4 * v + 2]),
                           bfma2(bsub2(pack_bf(a[6], a[7]), rv[v].w), gt[4 * v + 3], xr[4 * v + 3]));
            }
            WG_BAR();
            if (wt == 0) mbar_arrive(eL + 4 * v0);
            if (v0 + 2 < 8) FETCH(v0 + 2);
            if (v0 == 0) TS(8);
        }
        TS(9);
    } else {
        asm volatile("setmaxnreg.dec.sync.aligned.u32 %0;" ::"n"(PROD_REGS));
#define XROWS(k) do { mbar_expect_tx(XBAR(k), 8192); bulk_g2s(sb + OFF_S + (k) * 8192, at(P.x, (b * 16 + (k) * 4) * D_ * 2), 8192, XBAR(k)); } while (0)
        if (warp == 12) {
            if (elect_one()) {
                const CUtensorMap* tmD = c ? &tm_dim : &tm_dre;
#pragma unroll 1
                for (int it = 1; it < 4; it++) {
                    while (clock32() - (uint32_t)tstart < LDEL + (it - 1) * LGAP) {}
                    LOAD0(it);
                    if (it >= X0) XROWS(it - X0);
                }
            }
            __syncwarp();
        }
        CLUSTER_WAIT();
        if (warp == 12) {
            if (elect_one()) {
                const CUtensorMap* tmD = c ? &tm_dim : &tm_dre;
#pragma unroll 1
                for (int it = 4; it < 16; it++) {
                    const int s = DSLOT(it);
                    mbar_wait(BAR(B_ES + s), ((it >> 2) & 1) ^ 1);
                    TRACE(it);
                    mbar_expect_tx(BAR(B_FS + s), SLOT);
                    tma_2d(sb + OFF_S + s * SLOT, tmD, it * 64, r * 128, BAR(B_FS + s));
                    if (it < 4 + X0) XROWS(it - X0);
                }
                const unsigned ep = load_epoch(b), e8 = ep & 0xffu;
                const uint8_t* abg = at(AB, grp * 32 * SLOT);
                const unsigned long long* fl = at(g_flag, grp * 128);
                unsigned long long rdy = ld_acquire64(fl);
                mbar_wait(BAR(B_SRD), 0);
                st_release8(at(g_flag, grp * 128 + g), e8);
                PROF_T(7);
                int j = 4;
#pragma unroll 1
                for (int cl = 0; cl < 4; cl++) {
                    if (cl) rdy = ld_acquire64(++fl);
                    fence_async_global();
#pragma unroll 1
                    for (int n = 1; n < 8; n++, j++) {
                        const int q = BLK(n), s = (j & 1) + ((j & 2) ? 0 : 4);
                        mbar_wait(BAR(B_ES + s), ((j >> 2) ^ (j >> 1)) & 1);
                        if (j == 7) mbar_wait(BAR(B_SRD + 1), 0);
                        if (((unsigned)(rdy >> (8 * q)) & 0xffu) != e8) {
                            int m = 0;
                            do { rdy = ld_acquire64(fl); } while (((unsigned)(rdy >> (8 * q)) & 0xffu) != e8 && ++m < SPIN_LIMIT);
                            fence_async_global();
                        }
                        TRACE(16 + j);
                        mbar_expect_tx(BAR(B_FS + s), SLOT);
                        bulk_g2s(sb + OFF_S + s * SLOT, at(abg, (4 * q + KO(cl)) * SLOT), SLOT, BAR(B_FS + s));
                    }
                }
                *at(g_epoch, b * 4) = ep;
            }
        } else if (warp < 15) {
            if (elect_one()) {
                const int w = warp - 13, row0 = g * 256 + w * 128;
                const CUtensorMap* tmC = c ? &tm_cim : &tm_cre;
                const uint32_t fb = BAR(B_FL + 4 * w), eb = BAR(B_EL + 4 * w), dst = sb + OFF_L + w * 4 * SLOT;
                [[maybe_unused]] unsigned long long mk = 0, mg = 0;
                int n = 0, cl = 0;
#pragma unroll 1
                for (int it = 4; it < 48; it++) {
                    const int s = it & 3;
                    mbar_wait(eb + 8 * s, ((it >> 2) & 1) ^ 1);
                    TRACE(64 + w * 64 + it - 4);
                    MARK(it);
                    mbar_expect_tx(fb + 8 * s, SLOT);
                    tma_2d(dst + s * SLOT, it < 16 ? &tm_x : tmC, (it < 16 ? it : 4 * (n ? BLK(n) : g) + KO(cl)) * 64, row0, fb + 8 * s);
                    if (it == PTJ) prefetch_tmap(w ? &tm_x64 : tmC);
                    if (it == PTJ && w) prefetch_tmap(&tm_out);
                    if (it >= 16) {
                        if (it == 19) { n = 1; cl = 0; } else if (it < 19) cl++; else if (++n == 8) { n = 1; cl++; }
                    }
                }
#pragma unroll 1
                for (int h = 0; h < 4; h++) {
                    mbar_wait(eb + 8 * h, 1);
                    fence_async_smem();
                    tma_2d_store(&tm_out, grp * 64, row0 + h * 32, sb + OFF_S + (2 + (h >> 1)) * SLOT + w * 8192 + (h & 1) * 4096);
                    bulk_commit();
                }
                FINISH(w);
            }
        } else {
            const unsigned ep = load_epoch(b);
            uint4 f[4];
            {
                sleep_until((uint32_t)tstart + 6000);
                const uint4* keys = at(reinterpret_cast<const uint4*>(g_key), lane * 16);
                bool mine = false;
                int n = 0;
                do {
                    f[0] = ld_relaxed128(keys); f[1] = ld_relaxed128(keys + 32);
                    if (__all_sync(0xffffffffu, f[0].y == ep && f[0].w == ep && f[1].y == ep && f[1].w == ep)) break;
                    if (!mine) {
                        mbar_wait(BAR(B_LST), 0);
                        const uint4 k = *reinterpret_cast<const uint4*>(smem + OFF_XB);
                        if (lane == 0) st_relaxed64(at(g_key, b * 8), ((unsigned long long)ep << 32) | max(max(k.x, k.y), max(k.z, k.w)));
                        mine = true;
                    }
                    __nanosleep(GSL);
                } while (++n < SPIN_LIMIT);
                const unsigned key = __reduce_max_sync(0xffffffffu, max(max(f[0].x, f[0].z), max(f[1].x, f[1].z)));
                if (lane == 0) { *reinterpret_cast<unsigned*>(smem + OFF_SEL) = key; mbar_arrive(BAR(B_SEL)); PROF_T(8); }
            }
            if (elect_one()) {
#pragma unroll 1
                for (int cl = 0; cl < 4; cl++) {
                    uint8_t* dst = at(AB, (grp * 32 + 4 * g + KO(cl)) * SLOT);
                    const uint32_t src = sb + OFF_S + cl * SLOT, chunk = cl ? 1024 : SLOT;
                    mbar_wait(BAR(B_FS + cl), 0);
                    fence_async_smem();
                    if (cl == 0) PROF_T(3);
                    uint32_t t0 = clock32() + (cl == 1 ? PDEL : 0);
#pragma unroll 1
                    for (uint32_t o = 0; o < SLOT; o += chunk) {
                        sleep_until(t0);
                        bulk_s2g(dst + o, src + o, chunk);
                        bulk_commit();
                        t0 += cl == 1 ? PGAP1 : cl == 2 ? PGAP2 : PGAP3;
                    }
                    bulk_wait<0>();
                    fence_async_global();
                    TRACE(252 + cl);
                    if (cl < 2) mbar_arrive(BAR(B_SRD + cl));
                    else {
                        mbar_wait(BAR(B_ES + cl), 0);
                        mbar_expect_tx(BAR(B_FS + cl), SLOT);
                        tma_2d(src, &tm_x64, grp * 64, g * 256 + (cl - 2) * 64, BAR(B_FS + cl));
                        tma_2d(src + 8192, &tm_x64, grp * 64, g * 256 + (cl - 2) * 64 + 128, BAR(B_FS + cl));
                    }
                    if (cl) st_release8(at(g_flag, grp * 128 + cl * 8 + g), ep & 0xffu);
                    if (cl == 1) PROF_T(5);
                    if (cl == 3) PROF_T(4);
                }
            }
        }
    }
}

typedef CUresult (*EncodeFn)(CUtensorMap*, CUtensorMapDataType, cuuint32_t, void*, const cuuint64_t*, const cuuint64_t*,
                             const cuuint32_t*, const cuuint32_t*, CUtensorMapInterleave, CUtensorMapSwizzle,
                             CUtensorMapL2promotion, CUtensorMapFloatOOBfill);

void make_map(EncodeFn fn, CUtensorMap* tm, const void* p, uint64_t rows, uint64_t cols, uint32_t box_rows) {
    cuuint64_t dims[2] = {cols, rows};
    cuuint64_t strides[1] = {cols * 2};
    cuuint32_t box[2] = {64, box_rows};
    cuuint32_t es[2] = {1, 1};
    fn(tm, CU_TENSOR_MAP_DATA_TYPE_BFLOAT16, 2, const_cast<void*>(p), dims, strides, box, es, CU_TENSOR_MAP_INTERLEAVE_NONE,
       CU_TENSOR_MAP_SWIZZLE_128B, CU_TENSOR_MAP_L2_PROMOTION_L2_128B, CU_TENSOR_MAP_FLOAT_OOB_FILL_NONE);
}

}

extern "C" void kernel_launch(void* const* d_in, const int* in_sizes, int n_in, void* d_out, int out_size) {
    (void)in_sizes; (void)n_in; (void)out_size;
    static EncodeFn fn = nullptr;
    if (!fn) {
        void* p = nullptr;
        cudaDriverEntryPointQueryResult q;
        cudaGetDriverEntryPoint("cuTensorMapEncodeTiled", &p, cudaEnableDefault, &q);
        fn = (EncodeFn)p;
        cudaFuncSetAttribute(fnet_fused_kernel, cudaFuncAttributeMaxDynamicSharedMemorySize, SMEM_BYTES);
    }
    CUtensorMap tx, tdre, tdim, tcre, tcim, tout, tx64;
    make_map(fn, &tx, d_in[0], S_, D_, 128);
    make_map(fn, &tcre, d_in[1], S_, S_, 128);
    make_map(fn, &tcim, d_in[2], S_, S_, 128);
    make_map(fn, &tdre, d_in[3], D_, D_, 128);
    make_map(fn, &tdim, d_in[4], D_, D_, 128);
    make_map(fn, &tx64, d_in[0], S_, D_, 64);
    make_map(fn, &tout, d_out, S_, D_, 32);
    Params P;
    P.x = (const __nv_bfloat16*)d_in[0];
    P.dre = (const __nv_bfloat16*)d_in[3];
    P.dim = (const __nv_bfloat16*)d_in[4];
    P.wr = (const __nv_bfloat16*)d_in[6];
    P.wg = (const __nv_bfloat16*)d_in[7];
    P.wu = (const __nv_bfloat16*)d_in[8];
    P.wd = (const __nv_bfloat16*)d_in[9];
    P.zero = 0;
    fnet_fused_kernel<<<NCTA, NTHREADS, SMEM_BYTES, cudaStreamPerThread>>>(tx, tdre, tdim, tcre, tcim, tout, tx64, P);
}
```

```cpp
#include <cuda_runtime.h>
#include <cuda_bf16.h>
#include <cuda.h>
#include <stdint.h>

#define GSL 200
#define SLEEP_NS 200
#define PDEL 1000
#define PGAP1 200
#define PGAP2 200
#define PGAP3 240
#define GOJ 2
#define LDEL 1300
#define LGAP 750
#define PTJ 10
#define X0 2
#define KQ 5
#define XE 2
#define PROD_REGS 32
#define CONS_REGS 184

namespace {

constexpr int S_ = 2048, D_ = 1024, F_ = 3584;
constexpr int NCTA = 128;
constexpr int XJ = 20;
constexpr uint32_t SLOT = 16384;
constexpr uint32_t OFF_L = 0;
constexpr uint32_t OFF_S = 8 * SLOT;
constexpr uint32_t OFF_RS = OFF_S + SLOT;
constexpr uint32_t OFF_BAR = 14 * SLOT;
constexpr uint32_t OFF_SEL = OFF_BAR + 360;
constexpr uint32_t OFF_RSTD = OFF_BAR + 384;
constexpr uint32_t OFF_MEAN = OFF_RSTD + 1024;
constexpr uint32_t OFF_XB = OFF_MEAN + 512;
constexpr uint32_t OFF_H = OFF_XB + 1024;
constexpr uint32_t SMEM_BYTES = OFF_H + 128;
constexpr uint32_t SB0 = 1024;
constexpr int NTHREADS = 512;
static_assert(SMEM_BYTES <= 232448, "smem");

enum { B_FS = 0, B_ES = 6, B_FL = 12, B_EL = 20, B_SRD = 28, B_RECV = 30  , B_RDY = 34, B_STATS = 36, B_LST = 37, B_UPD = 38,
       B_QUIET = 39, B_GO = 40, B_PEER = 41, B_SEL = 42, B_H = 43, B_COUNT = 44 };
static_assert(B_COUNT * 8 <= 360, "barriers");

__device__ __align__(1024) uint8_t g_ab[16u * 32u * SLOT];
__device__ __align__(128) uint4 g_part[56 * (D_ / 4)];
__device__ __align__(128) uint4 g_stat[S_];
__device__ __align__(128) uint4 g_rs[D_];
__device__ __align__(128) unsigned long long g_key[NCTA];
__device__ __align__(128) unsigned long long g_flag[16 * 16];
__device__ __align__(128) unsigned g_epoch[NCTA];
#define PROF_T(i) do {} while (0)
#define TRACE(i) do {} while (0)
#define PROF_G(i) do {} while (0)
#define TS(i) do {} while (0)
#define FINISH(wg) bulk_wait_read<0>()

#define MARK(it) do {} while (0)

__device__ __forceinline__ uint32_t smem_u32(const void* p) { return (uint32_t)__cvta_generic_to_shared(p); }
__device__ __forceinline__ void mbar_init(uint32_t bar, uint32_t cnt) {
    asm volatile("mbarrier.init.shared::cta.b64 [%0], %1;" ::"r"(bar), "r"(cnt) : "memory");
}
__device__ __forceinline__ bool mbar_try(uint32_t bar, uint32_t parity) {
    uint32_t ok;
    asm volatile("{\n.reg .pred p;\nmbarrier.try_wait.parity.shared::cta.b64 p, [%1], %2;\nselp.u32 %0, 1, 0, p;\n}"
                 : "=r"(ok) : "r"(bar), "r"(parity) : "memory");
    return ok;
}
__device__ __forceinline__ bool mbar_test(uint32_t bar, uint32_t parity) {
    uint32_t ok;
    asm volatile("{\n.reg .pred p;\nmbarrier.test_wait.parity.shared::cta.b64 p, [%1], %2;\nselp.u32 %0, 1, 0, p;\n}"
                 : "=r"(ok) : "r"(bar), "r"(parity) : "memory");
    return ok;
}
__device__ __forceinline__ bool mbar_try_cluster(uint32_t bar, uint32_t parity) {
    uint32_t ok;
    asm volatile("{\n.reg .pred p;\nmbarrier.try_wait.parity.acquire.cluster.shared::cta.b64 p, [%1], %2;\nselp.u32 %0, 1, 0, p;\n}"
                 : "=r"(ok) : "r"(bar), "r"(parity) : "memory");
    return ok;
}
constexpr int SPIN_LIMIT = 1 << 20;
__device__ __forceinline__ void mbar_wait(uint32_t bar, uint32_t parity) {
    if (mbar_try(bar, parity)) return;
    int n = 0;
    while (!mbar_try(bar, parity) && ++n < SPIN_LIMIT) {}
}
__device__ __forceinline__ void mbar_wait_cluster(uint32_t bar, uint32_t parity) {
    int n = 0;
    while (!mbar_try_cluster(bar, parity) && ++n < SPIN_LIMIT) {}
}
__device__ __forceinline__ void mbar_wait_sleep(uint32_t bar, uint32_t parity) {
    int n = 0;
    while (!mbar_try(bar, parity) && ++n < SPIN_LIMIT) __nanosleep(SLEEP_NS);
}
__device__ __forceinline__ void mbar_arrive(uint32_t bar) {
    asm volatile("mbarrier.arrive.shared::cta.b64 _, [%0];" ::"r"(bar) : "memory");
}
__device__ __forceinline__ void mbar_arrive_cluster(uint32_t cluster_bar) {
    asm volatile("mbarrier.arrive.shared::cluster.b64 _, [%0];" ::"r"(cluster_bar) : "memory");
}
__device__ __forceinline__ void mbar_expect_tx(uint32_t bar, uint32_t bytes) {
    asm volatile("mbarrier.arrive.expect_tx.shared::cta.b64 _, [%0], %1;" ::"r"(bar), "r"(bytes) : "memory");
}
__device__ __forceinline__ bool elect_one() {
    uint32_t p;
    asm volatile("{\n.reg .pred p;\nelect.sync _|p, 0xffffffff;\nselp.u32 %0, 1, 0, p;\n}" : "=r"(p));
    return p;
}
__device__ __forceinline__ uint32_t mapa(uint32_t addr, uint32_t rank) {
    uint32_t r;
    asm("mapa.shared::cluster.u32 %0, %1, %2;" : "=r"(r) : "r"(addr), "r"(rank));
    return r;
}
__device__ __forceinline__ uint32_t clock32() { uint32_t t; asm volatile("mov.u32 %0, %%clock;" : "=r"(t)); return t; }
__device__ __forceinline__ void sleep_until(uint32_t t) {
    int n = 0;
    while ((int)(clock32() - t) < 0 && ++n < SPIN_LIMIT) __nanosleep(20);
}
__device__ __forceinline__ void yield(float last, uint32_t zero) {
    asm volatile("nanosleep.u32 %0;" ::"r"(__float_as_uint(last) & zero));
}
template <typename T> __device__ __forceinline__ T* at(T* p, uint32_t bytes) {
    asm("" : "+r"(bytes));
    return reinterpret_cast<T*>(reinterpret_cast<uintptr_t>(p) + bytes);
}
__device__ __forceinline__ void tma_2d(uint32_t dst, const CUtensorMap* tm, int c0, int c1, uint32_t bar) {
    asm volatile("cp.async.bulk.tensor.2d.shared::cluster.global.mbarrier::complete_tx::bytes [%0], [%1, {%3, %4}], [%2];"
                 ::"r"(dst), "l"(tm), "r"(bar), "r"(c0), "r"(c1) : "memory");
}
__device__ __forceinline__ void tma_2d_prefetch(const CUtensorMap* tm, int c0, int c1) {
    asm volatile("cp.async.bulk.prefetch.tensor.2d.L2.global [%0, {%1, %2}];" ::"l"(tm), "r"(c0), "r"(c1) : "memory");
}
__device__ __forceinline__ void tma_2d_store(const CUtensorMap* tm, int c0, int c1, uint32_t src) {
    asm volatile("cp.async.bulk.tensor.2d.global.shared::cta.bulk_group [%0, {%2, %3}], [%1];"
                 ::"l"(tm), "r"(src), "r"(c0), "r"(c1) : "memory");
}
__device__ __forceinline__ void bulk_g2s(uint32_t dst, const void* src, uint32_t bytes, uint32_t bar) {
    asm volatile("cp.async.bulk.shared::cluster.global.mbarrier::complete_tx::bytes [%0], [%1], %2, [%3];"
                 ::"r"(dst), "l"(src), "r"(bytes), "r"(bar) : "memory");
}
__device__ __forceinline__ void bulk_s2g(void* dst, uint32_t src, uint32_t bytes) {
    asm volatile("cp.async.bulk.global.shared::cta.bulk_group [%0], [%1], %2;" ::"l"(dst), "r"(src), "r"(bytes) : "memory");
}
__device__ __forceinline__ void st_async4(uint32_t dst, uint32_t a, uint32_t b, uint32_t c, uint32_t d, uint32_t bar) {
    asm volatile("st.async.weak.shared::cluster.mbarrier::complete_tx::bytes.v4.b32 [%0], {%1,%2,%3,%4}, [%5];"
                 ::"r"(dst), "r"(a), "r"(b), "r"(c), "r"(d), "r"(bar) : "memory");
}
__device__ __forceinline__ void bulk_commit() { asm volatile("cp.async.bulk.commit_group;" ::: "memory"); }
template <int N> __device__ __forceinline__ void bulk_wait_read() { asm volatile("cp.async.bulk.wait_group.read %0;" ::"n"(N) : "memory"); }
template <int N> __device__ __forceinline__ void bulk_wait() { asm volatile("cp.async.bulk.wait_group %0;" ::"n"(N) : "memory"); }
__device__ __forceinline__ void fence_async_smem() { asm volatile("fence.proxy.async.shared::cta;" ::: "memory"); }
__device__ __forceinline__ void fence_async_global() { asm volatile("fence.proxy.async.global;" ::: "memory"); }
__device__ __forceinline__ void prefetch_tmap(const CUtensorMap* tm) {
    asm volatile("prefetch.tensormap [%0];" ::"l"(tm) : "memory");
}
__device__ __forceinline__ unsigned long long ld_acquire64(const unsigned long long* p) {
    unsigned long long v; asm volatile("ld.acquire.gpu.global.u64 %0, [%1];" : "=l"(v) : "l"(p) : "memory"); return v;
}
__device__ __forceinline__ unsigned load_epoch(int b) {
    unsigned v; asm volatile("ld.global.u32 %0, [%1];" : "=r"(v) : "l"(at(g_epoch, b * 4)) : "memory"); return v + 1;
}
__device__ __forceinline__ unsigned ld_relaxed(const void* p) {
    unsigned v; asm volatile("ld.relaxed.gpu.global.u32 %0, [%1];" : "=r"(v) : "l"(p) : "memory"); return v;
}
__device__ __forceinline__ uint4 ld_relaxed128(const uint4* p) {
    uint4 v;
    asm volatile("{\n.reg .b128 t;\n.reg .b64 lo, hi;\nld.relaxed.gpu.global.b128 t, [%4];\nmov.b128 {lo, hi}, t;\n"
                 "mov.b64 {%0, %1}, lo;\nmov.b64 {%2, %3}, hi;\n}"
                 : "=r"(v.x), "=r"(v.y), "=r"(v.z), "=r"(v.w) : "l"(p) : "memory");
    return v;
}
__device__ __forceinline__ void st_relaxed128(uint4* p, const uint4& v) {
    asm volatile("{\n.reg .b128 t;\n.reg .b64 lo, hi;\nmov.b64 lo, {%1, %2};\nmov.b64 hi, {%3, %4};\nmov.b128 t, {lo, hi};\n"
                 "st.relaxed.gpu.global.b128 [%0], t;\n}"
                 ::"l"(p), "r"(v.x), "r"(v.y), "r"(v.z), "r"(v.w) : "memory");
}
__device__ __forceinline__ void st_relaxed64(unsigned long long* p, unsigned long long v) {
    asm volatile("st.relaxed.gpu.global.u64 [%0], %1;" ::"l"(p), "l"(v) : "memory");
}
__device__ __forceinline__ void st_release8(void* p, unsigned v) {
    asm volatile("st.release.gpu.global.u8 [%0], %1;" ::"l"(p), "r"(v) : "memory");
}
__device__ __forceinline__ uint64_t policy_evict_first() {
    uint64_t pol;
    asm("createpolicy.fractional.L2::evict_first.b64 %0, 1.0;" : "=l"(pol));
    return pol;
}
__device__ __forceinline__ uint4 ldg_stream(const void* p, uint64_t pol) {
    uint4 v;
    asm volatile("ld.global.nc.L1::no_allocate.L2::cache_hint.v4.u32 {%0,%1,%2,%3}, [%4], %5;"
                 : "=r"(v.x), "=r"(v.y), "=r"(v.z), "=r"(v.w) : "l"(p), "l"(pol));
    return v;
}
template <int ID, int N> __device__ __forceinline__ void named_arrive() { asm volatile("bar.arrive %0, %1;" ::"n"(ID), "n"(N) : "memory"); }
template <int ID, int N> __device__ __forceinline__ void named_bar() { asm volatile("bar.sync %0, %1;" ::"n"(ID), "n"(N) : "memory"); }

__device__ __forceinline__ float bf_lo(uint32_t u) { return __uint_as_float(u << 16); }
__device__ __forceinline__ float bf_hi(uint32_t u) { return __uint_as_float(u & 0xffff0000u); }
__device__ __forceinline__ uint32_t pack_bf(float lo, float hi) {
    uint32_t r; asm("cvt.rn.bf16x2.f32 %0, %1, %2;" : "=r"(r) : "f"(hi), "f"(lo)); return r;
}
__device__ __forceinline__ float rbf(float v) { return __uint_as_float(pack_bf(0.f, v)); }
__device__ __forceinline__ float sqrt_f(float v) { float r; asm("sqrt.approx.f32 %0, %1;" : "=f"(r) : "f"(v)); return r; }
__device__ __forceinline__ float rcp_f(float v) { float r; asm("rcp.approx.f32 %0, %1;" : "=f"(r) : "f"(v)); return r; }
__device__ __forceinline__ float silu_f(float z) { return __fdividef(z, 1.0f + __expf(-z)); }
__device__ __forceinline__ uint32_t bsub2(uint32_t a, uint32_t b) {
    uint32_t r; asm("sub.rn.bf16x2 %0, %1, %2;" : "=r"(r) : "r"(a), "r"(b)); return r;
}
__device__ __forceinline__ uint32_t bfma2(uint32_t a, uint32_t b, uint32_t c) {
    uint32_t r; asm("fma.rn.bf16x2 %0, %1, %2, %3;" : "=r"(r) : "r"(a), "r"(b), "r"(c)); return r;
}
__device__ __forceinline__ uint32_t norm2(uint32_t xv, float m, float rinv) {
    uint32_t t = pack_bf(bf_lo(xv) - m, bf_hi(xv) - m);
    return pack_bf(bf_lo(t) * rinv, bf_hi(t) * rinv);
}
__device__ __forceinline__ float gate1(float z) {
    float t;
    const float h = 0.5f * z;
    asm("tanh.approx.f32 %0, %1;" : "=f"(t) : "f"(h));
    return fmaf(h, t, h);
}
__device__ __forceinline__ uint32_t gate2(uint32_t xv, uint32_t mean2, float r0, float r1) {
    const uint32_t t = bsub2(xv, mean2);
    return pack_bf(gate1(bf_lo(t) * r0), gate1(bf_hi(t) * r1));
}
__device__ __forceinline__ uint32_t silu2(uint32_t z) { return pack_bf(silu_f(bf_lo(z)), silu_f(bf_hi(z))); }

__device__ __forceinline__ void stmatrix4(uint32_t addr, uint32_t r0, uint32_t r1, uint32_t r2, uint32_t r3) {
    asm volatile("stmatrix.sync.aligned.m8n8.x4.shared.b16 [%0], {%1,%2,%3,%4};"
                 ::"r"(addr), "r"(r0), "r"(r1), "r"(r2), "r"(r3));
}
__device__ __forceinline__ void stmatrix4t(uint32_t addr, uint32_t r0, uint32_t r1, uint32_t r2, uint32_t r3) {
    asm volatile("stmatrix.sync.aligned.m8n8.x4.trans.shared.b16 [%0], {%1,%2,%3,%4};"
                 ::"r"(addr), "r"(r0), "r"(r1), "r"(r2), "r"(r3));
}
__device__ __forceinline__ void ldmatrix4t(uint32_t addr, uint32_t& r0, uint32_t& r1, uint32_t& r2, uint32_t& r3) {
    asm volatile("ldmatrix.sync.aligned.m8n8.x4.trans.shared.b16 {%0,%1,%2,%3}, [%4];"
                 : "=r"(r0), "=r"(r1), "=r"(r2), "=r"(r3) : "r"(addr));
}

__device__ __forceinline__ void wg_fence() { asm volatile("wgmma.fence.sync.aligned;" ::: "memory"); }
__device__ __forceinline__ void wg_commit() { asm volatile("wgmma.commit_group.sync.aligned;" ::: "memory"); }
template <int N> __device__ __forceinline__ void wg_wait() { asm volatile("wgmma.wait_group.sync.aligned %0;" ::"n"(N) : "memory"); }

__host__ __device__ constexpr uint32_t desc_lo(uint32_t addr, uint32_t lbo) { return ((addr & 0x3FFFF) >> 4) | ((lbo >> 4) << 16); }
#define DESC_HI "0x40000040"

#define R8(a, o) "+f"(a[(o) + 0]), "+f"(a[(o) + 1]), "+f"(a[(o) + 2]), "+f"(a[(o) + 3]), \
                 "+f"(a[(o) + 4]), "+f"(a[(o) + 5]), "+f"(a[(o) + 6]), "+f"(a[(o) + 7])
#define R64(a, o) R8(a, (o) + 0), R8(a, (o) + 8), R8(a, (o) + 16), R8(a, (o) + 24), \
                  R8(a, (o) + 32), R8(a, (o) + 40), R8(a, (o) + 48), R8(a, (o) + 56)

template <int O, int TA>
__device__ __forceinline__ void wgmma128(float (&a)[128], uint32_t da, uint32_t db, int scale_d) {
    asm volatile(
        "{\n.reg .pred p;\n.reg .b64 da, db;\nsetp.ne.b32 p, %66, 0;\n"
        "mov.b64 da, {%64, " DESC_HI "};\nmov.b64 db, {%65, " DESC_HI "};\n"
        "wgmma.mma_async.sync.aligned.m64n128k16.f32.bf16.bf16 "
        "{%0,%1,%2,%3,%4,%5,%6,%7,%8,%9,%10,%11,%12,%13,%14,%15,"
        "%16,%17,%18,%19,%20,%21,%22,%23,%24,%25,%26,%27,%28,%29,%30,%31,"
        "%32,%33,%34,%35,%36,%37,%38,%39,%40,%41,%42,%43,%44,%45,%46,%47,"
        "%48,%49,%50,%51,%52,%53,%54,%55,%56,%57,%58,%59,%60,%61,%62,%63},"
        "da, db, p, 1, 1, %67, 0;\n}"
        : R64(a, O)
        : "r"(da), "r"(db), "r"(scale_d), "n"(TA));
}
template <int O>
__device__ __forceinline__ void wgmma128_rs(float (&a)[128], const uint32_t* f, uint32_t db) {
    asm volatile(
        "{\n.reg .b64 db;\nmov.b64 db, {%68, 8};\n"
        "wgmma.mma_async.sync.aligned.m64n128k16.f32.bf16.bf16 "
        "{%0,%1,%2,%3,%4,%5,%6,%7,%8,%9,%10,%11,%12,%13,%14,%15,"
        "%16,%17,%18,%19,%20,%21,%22,%23,%24,%25,%26,%27,%28,%29,%30,%31,"
        "%32,%33,%34,%35,%36,%37,%38,%39,%40,%41,%42,%43,%44,%45,%46,%47,"
        "%48,%49,%50,%51,%52,%53,%54,%55,%56,%57,%58,%59,%60,%61,%62,%63},"
        "{%64, %65, %66, %67}, db, 1, 1, 1, 0;\n}"
        : R64(a, O)
        : "r"(f[0]), "r"(f[1]), "r"(f[2]), "r"(f[3]), "r"(db));
}
template <int O>
__device__ __forceinline__ void fence_regs64(float (&a)[128]) {
    asm volatile("" : R64(a, O)::"memory");
}

struct Params {
    const __nv_bfloat16* x;
    const __nv_bfloat16* dre;
    const __nv_bfloat16* dim;
    const __nv_bfloat16* wr;
    const __nv_bfloat16* wg;
    const __nv_bfloat16* wu;
    const __nv_bfloat16* wd;
    uint32_t zero;
#define AB g_ab
};

__device__ __forceinline__ float warp_sum(float v) {
#pragma unroll
    for (int o = 16; o; o >>= 1) v += __shfl_xor_sync(0xffffffffu, v, o);
    return v;
}
__device__ __forceinline__ void fma8(float* acc, const uint4& w, float s) {
    acc[0] += s * bf_lo(w.x); acc[1] += s * bf_hi(w.x); acc[2] += s * bf_lo(w.y); acc[3] += s * bf_hi(w.y);
    acc[4] += s * bf_lo(w.z); acc[5] += s * bf_hi(w.z); acc[6] += s * bf_lo(w.w); acc[7] += s * bf_hi(w.w);
}
__device__ __forceinline__ int POS(int t) { return (t & ~15) | ((t & 6) << 1) | ((t & 8) >> 2) | (t & 1); }
__host__ __device__ constexpr int PSLOT(int j) { return j < 4 ? j : (j & 1) + ((j & 2) ? 0 : 4); }
__host__ __device__ constexpr int PPAR(int j) { return j < 4 ? 0 : ((j >> 2) ^ (j >> 1) ^ 1) & 1; }
__host__ __device__ constexpr int DSLOT(int it) { return (it & 3) + 2; }
__device__ __forceinline__ int SREC(int t) { return (t & ~15) | ((t & 3) << 2) | ((t >> 2) & 3); }
__device__ __forceinline__ int KO(int cl) { return ((cl & 1) << 1) | (cl >> 1); }

__global__ void __cluster_dims__(2, 1, 1) __launch_bounds__(NTHREADS, 1)
fnet_fused_kernel(const __grid_constant__ CUtensorMap tm_x, const __grid_constant__ CUtensorMap tm_dre,
                  const __grid_constant__ CUtensorMap tm_dim, const __grid_constant__ CUtensorMap tm_cre,
                  const __grid_constant__ CUtensorMap tm_cim, const __grid_constant__ CUtensorMap tm_out,
                  const __grid_constant__ CUtensorMap tm_x64,
                  const Params P) {
    extern __shared__ __align__(1024) uint8_t smem[];
    const unsigned long long tstart = clock64();
    const uint32_t sb = smem_u32(smem);
    const int tid = threadIdx.x, lane = tid & 31;
    const int warp = __shfl_sync(0xffffffffu, tid >> 5, 0);
    const int pr = blockIdx.x >> 1, p7 = ((pr - 36) * 37) >> 8;
    const int c = blockIdx.x & 1;
    const int gi = pr < 4 ? 7 : pr < 36 ? 2 * ((pr - 4) & 7) + (((pr - 4) >> 2) & 1) : 2 * (pr - 36 - 7 * p7) + 1 + (pr - 36 - 7 * p7 > 2);
    const int g = gi & 7;
    const int r = (gi >> 3) * 4 + (pr < 4 ? pr : pr < 36 ? (pr - 4) >> 3 : p7);
#define BLK(n) ((n) - ((n) <= g))
    const int grp = 2 * r + c;
    const int b = g * 16 + grp;
    const uint32_t bar0 = sb + OFF_BAR;
    const uint32_t zero = P.zero;
#define BAR(i) (bar0 + 8u * (i))
#define XBAR(i) (sb + OFF_XB + 64 + 8u * (i))
#define CLUSTER_ARRIVE() asm volatile("barrier.cluster.arrive.relaxed.aligned;" ::: "memory")
#define CLUSTER_WAIT() asm volatile("barrier.cluster.wait.aligned;" ::: "memory")
    if ((sb & 0xffffffu) != SB0) return;

#define LOAD0(it) do { \
            mbar_expect_tx(BAR(B_FS + DSLOT(it)), SLOT); tma_2d(sb + OFF_S + DSLOT(it) * SLOT, tmD, (it) * 64, r * 128, BAR(B_FS + DSLOT(it))); \
            mbar_expect_tx(BAR(B_FL + (it)), SLOT); tma_2d(sb + OFF_L + (it) * SLOT, &tm_x, (it) * 64, g * 256, BAR(B_FL + (it))); \
            mbar_expect_tx(BAR(B_FL + 4 + (it)), SLOT); tma_2d(sb + OFF_L + (4 + (it)) * SLOT, &tm_x, (it) * 64, g * 256 + 128, BAR(B_FL + 4 + (it))); \
        } while (0)
    if (warp == 13) {
        if (elect_one()) {
            const CUtensorMap* tmD = c ? &tm_dim : &tm_dre;
            prefetch_tmap(&tm_x);
            mbar_init(BAR(B_FS + 2), 1); mbar_init(BAR(B_FL), 1); mbar_init(BAR(B_FL + 4), 1);
            asm volatile("fence.mbarrier_init.release.cluster;" ::: "memory");
            LOAD0(0);
        }
        __syncwarp();
    }
    if (warp == 12) {
        if (elect_one()) {
#pragma unroll
            for (int i = 1; i < 4; i++) { mbar_init(BAR(B_FS + 2 + i), 1); mbar_init(BAR(B_FL + i), 1); mbar_init(BAR(B_FL + 4 + i), 1); }
#pragma unroll
            for (int i = 0; i < 4; i++) mbar_init(XBAR(i), 1);
            asm volatile("fence.mbarrier_init.release.cluster;" ::: "memory");
        }
        __syncwarp();
    }
    if (warp == 14) {
        if (elect_one()) {
#pragma unroll
            for (int i = 0; i < 8; i++) { mbar_init(BAR(B_EL + i), 1); mbar_init(XBAR(4 + i), 1); if (i < 6) mbar_init(BAR(B_ES + i), 2); }
            asm volatile("fence.mbarrier_init.release.cluster;" ::: "memory");
        }
        __syncwarp();
    }
    if (warp == 15) {
        if (elect_one()) {
            mbar_init(BAR(B_FS), 1); mbar_init(BAR(B_FS + 1), 1);
#pragma unroll
            for (int i = B_SRD; i < B_COUNT; i++) mbar_init(BAR(i), i == B_GO ? 2 : i == B_STATS || i == B_LST ? 4 : 1);
#pragma unroll
            for (int i = 0; i < 4; i++) mbar_expect_tx(BAR(B_RECV + i), SLOT / 2);
            mbar_expect_tx(BAR(B_PEER), 1024); mbar_expect_tx(BAR(B_H), 128);
            asm volatile("fence.mbarrier_init.release.cluster;" ::: "memory");
        }
        __syncwarp();
    }
    CLUSTER_ARRIVE();

#define GATHER(ptr, cnt, valid) do { int n = 0; bool ok; do { ok = true; \
                _Pragma("unroll") for (int i = 0; i < (cnt); i++) { f[i] = ld_relaxed128((ptr) + i * 32); ok = ok && (valid); } \
                if (__all_sync(0xffffffffu, ok)) break; \
                __nanosleep(GSL); \
            } while (++n < SPIN_LIMIT); } while (0)
    if (warp >= 8 && warp < 12) {
        asm volatile("setmaxnreg.dec.sync.aligned.u32 %0;" ::"n"(512 - PROD_REGS - 2 * CONS_REGS));
        const int aw = warp - 8, mt = tid - 256;
        unsigned ep;
        {
            const uint8_t* rp = smem + OFF_S + aw * 2048 + lane * 16;
            const __nv_bfloat16* dp = at(c ? P.dim : P.dre, (r * 128 + g * 16 + aw * 4) * D_ * 2);
            float wf[32], sw = 0.f;
#pragma unroll
            for (int i = 0; i < 4; i++) {
                const uint4 w = __ldg(reinterpret_cast<const uint4*>(at(P.wr, lane * 16) + i * 256));
                const uint32_t wv[4] = {w.x, w.y, w.z, w.w};
#pragma unroll
                for (int e = 0; e < 4; e++) { wf[8 * i + 2 * e] = bf_lo(wv[e]); wf[8 * i + 2 * e + 1] = bf_hi(wv[e]); sw = (sw + bf_lo(wv[e])) + bf_hi(wv[e]); }
            }
            ep = load_epoch(b);
            sw = warp_sum(sw);
            CLUSTER_WAIT();
            float x0[4] = {}, s1[4] = {}, s2[4] = {}, sx[4] = {}, sd[4] = {};
#define PUSH(a, v) do { a[0] = a[1]; a[1] = a[2]; a[2] = a[3]; a[3] = v; } while (0)
#pragma unroll 1
            for (int k = 0; k < 4; k++) {
                mbar_wait(XBAR(k), 0);
                uint4 v[4];
#pragma unroll
                for (int i = 0; i < 4; i++) v[i] = *reinterpret_cast<const uint4*>(rp + k * 8192 + i * 512);
                uint32_t sh = v[0].x << 16;
                float a1s = 0.f, a2s = 0.f, axs = 0.f;
#pragma unroll
                for (int i = 0; i < 4; i++) {
                    sh = __shfl_sync(0xffffffffu, sh | (__float_as_uint(axs) & zero), 0);
                    const uint32_t xv[4] = {v[i].x, v[i].y, v[i].z, v[i].w};
#pragma unroll
                    for (int e = 0; e < 4; e++) {
                        const float a0 = bf_lo(xv[e]) - __uint_as_float(sh), a1 = bf_hi(xv[e]) - __uint_as_float(sh);
                        a1s += a0 + a1;
                        a2s = fmaf(a0, a0, fmaf(a1, a1, a2s));
                        axs = fmaf(a0, wf[8 * i + 2 * e], fmaf(a1, wf[8 * i + 2 * e + 1], axs));
                    }
                }
                PUSH(x0, __uint_as_float(sh)); PUSH(s1, a1s); PUSH(s2, a2s); PUSH(sx, axs);
                fence_async_smem();
                __syncwarp();
                if (elect_one()) {
                    const uint32_t db = XBAR(k == 3 ? 8 + aw : 4 + aw);
                    if (k == 0 || k == 3) mbar_expect_tx(db, k ? 2048 : 6144);
                    bulk_g2s(sb + OFF_S + k * 8192 + aw * 2048, dp + k * D_, 2048, db);
                }
            }
#define FOLD4(a) do { const bool u16 = lane & 16, u8 = lane & 8; \
                float p0 = (u16 ? a[2] : a[0]) + __shfl_xor_sync(0xffffffffu, u16 ? a[0] : a[2], 16); \
                float p1 = (u16 ? a[3] : a[1]) + __shfl_xor_sync(0xffffffffu, u16 ? a[1] : a[3], 16); \
                a[0] = (u8 ? p1 : p0) + __shfl_xor_sync(0xffffffffu, u8 ? p0 : p1, 8); \
                _Pragma("unroll") for (int o = 4; o; o >>= 1) a[0] += __shfl_xor_sync(0xffffffffu, a[0], o); } while (0)
#pragma unroll 1
            for (int k = 0; k < 4; k++) {
                mbar_wait(XBAR(k == 3 ? 8 + aw : 4 + aw), 0);
                float run = 0.f;
#pragma unroll
                for (int i = 0; i < 4; i++) {
                    const uint4 v = *reinterpret_cast<const uint4*>(rp + k * 8192 + i * 512);
                    const uint32_t dv[4] = {v.x, v.y, v.z, v.w};
#pragma unroll
                    for (int e = 0; e < 4; e++) run += bf_lo(dv[e]) + bf_hi(dv[e]);
                }
                PUSH(sd, run);
            }
            named_bar<4, 128>();
            if (mt < 12) asm volatile("mbarrier.inval.shared::cta.b64 [%0];" ::"r"(XBAR(mt)) : "memory");
            FOLD4(sd); FOLD4(s1); FOLD4(s2); FOLD4(sx);
            const float nb = __shfl_down_sync(0xffffffffu, sd[0], 8);
            if ((lane & 15) == 0)
                st_relaxed128(at(g_rs, (grp * 64 + g * 8 + aw * 2 + (lane >> 4)) * 16), make_uint4(__float_as_uint(sd[0]), ep, __float_as_uint(nb), ep));
            if (mt == 0) PROF_T(6);
            const int rr = lane >> 3;
            const float c0 = rr == 0 ? x0[0] : rr == 1 ? x0[1] : rr == 2 ? x0[2] : x0[3];
            const float dm = s1[0] * (1.0f / D_);
            const float mb = rbf(c0 + dm);
            const float rinv = rcp_f(rbf(sqrt_f(rbf(rbf(fmaxf(s2[0] * (1.0f / D_) - dm * dm, 0.f)) + 1e-5f))));
            if ((lane & 7) == 0) st_relaxed128(at(g_stat, (b * 16 + aw * 4 + rr) * 16), make_uint4(__float_as_uint(mb), __float_as_uint(rinv), ep, 0));
            unsigned u = __bfloat16_as_ushort(__float2bfloat16_rn((sx[0] + (c0 - mb) * sw) * rinv));
            u = (u & 0x8000u) ? (~u & 0xffffu) : (u | 0x8000u);
            u = (u << 16) | (0xffffu - (unsigned)(b * 16 + rr * 4 + aw));
            u = __reduce_max_sync(0xffffffffu, u);
            if (lane == 0) { *reinterpret_cast<unsigned*>(smem + OFF_XB + aw * 4) = u; mbar_arrive(BAR(B_LST)); }
            if (mt == 0) PROF_T(2);
            uint4 f[4];
            if (aw < 2) {
                const int t = SREC(aw * 128 + lane);
                GATHER(at(g_stat, (g * 256 + aw * 128 + lane) * 16), 4, f[i].z == ep);
#pragma unroll
                for (int i = 0; i < 4; i++) {
                    *reinterpret_cast<uint32_t*>(smem + OFF_RSTD + (POS(t) + i * 32) * 4) = f[i].y;
                    *reinterpret_cast<uint16_t*>(smem + OFF_MEAN + (POS(t) + i * 32) * 2) = (uint16_t)(f[i].x >> 16);
                }
            } else {
                const int e2 = (aw - 2) * 32 + lane;
                GATHER(at(g_rs, (grp * 64 + e2) * 16), 1, f[i].y == ep && f[i].w == ep);
#pragma unroll
                for (int i = 0; i < 2; i++) {
                    const float v = __uint_as_float(i ? f[0].z : f[0].x);
                    const float hi = rbf(v), mid = rbf(v - hi), lo = v - hi - mid;
                    *reinterpret_cast<uint4*>(smem + OFF_RS + (e2 * 2 + i) * 16) = make_uint4(pack_bf(hi, mid), pack_bf(lo, 0.f), 0, 0);
                }
            }
            fence_async_smem();
            __syncwarp();
            if (lane == 0) mbar_arrive(BAR(B_STATS));
            if (mt == 127) PROF_T(9);
        }
        const bool moe = pr < 28 || pr >= 36;
        const int pair = pr < 28 ? pr : pr - 8;
        if (moe) {
            const uint64_t pol = policy_evict_first();
            const __nv_bfloat16* wp = at((aw & 1) ? P.wu : P.wg, ((c * 512 + (aw >> 1) * 256 + (lane >> 3) * 8) * F_ + pair * 64 + (lane & 7) * 8) * 2);
            uint4 b0[8], b1[8];
#define FILL(buf, str) do { _Pragma("unroll") for (int q = 0; q < 8; q++) buf[q] = ldg_stream(wp + q * (str), pol); } while (0)
#define PAUSE() do { if (mbar_test(BAR(B_QUIET), 0)) mbar_wait_sleep(BAR(B_GO), 0); } while (0)
            FILL(b0, F_);
            mbar_wait(BAR(B_SEL), 0);
            uint4 xn;
            {
                const int sel = ~*reinterpret_cast<volatile unsigned*>(smem + OFF_SEL) & (S_ - 1);
                xn = __ldg(reinterpret_cast<const uint4*>(at(P.x, (sel * D_ + c * 512 + (aw >> 1) * 256 + (lane & 7) * 32 + (lane >> 3) * 8) * 2)));
                uint4 f[1];
                GATHER(at(g_stat, SREC(sel) * 16), 1, f[i].z == ep);
                wp += 32 * F_; FILL(b1, F_); wp -= 32 * F_;
                PAUSE();
                const float m = __uint_as_float(f[0].x), ri = __uint_as_float(f[0].y);
                xn = make_uint4(norm2(xn.x, m, ri), norm2(xn.y, m, ri), norm2(xn.z, m, ri), norm2(xn.w, m, ri));
            }
            float ag[8];
#pragma unroll
            for (int i = 0; i < 8; i++) ag[i] = 0.f;
#define ROUND(cur, nxt, rd) do { \
                PAUSE(); \
                if (lane == 0) TRACE(192 + aw * 12 + (rd)); \
                if ((rd) == 7) wp = at(P.wd - 16 * D_, ((pair * 64 + (lane >> 4) * 8) * D_ + c * 512 + aw * 128 + (lane & 15) * 8) * 2); \
                wp = at(wp, ((rd) < 7 ? 64 * F_ : 32 * D_) + (cur[7].x & zero)); \
                if ((rd) & 7) { if ((rd) < 7) FILL(nxt, F_); else if ((rd) < 11) FILL(nxt, D_); } \
                _Pragma("unroll") for (int q = 0; q < 8; q += 2) { \
                    const uint32_t xw = __shfl_sync(0xffffffffu, q == 0 ? xn.x : q == 2 ? xn.y : q == 4 ? xn.z : xn.w, (lane & 24) | ((rd) & 7)); \
                    fma8(ag, cur[q], bf_lo(xw)); \
                    fma8(ag, cur[q + 1], bf_hi(xw)); \
                    if (q < 6) yield(ag[7], zero); \
                } } while (0)
#pragma unroll 1
            for (int rd = 0; rd < 12; rd += 2) {
                ROUND(b0, b1, rd);
                ROUND(b1, b0, rd + 1);
                if (rd == 6 || rd == 10) {
#pragma unroll
                    for (int i = 0; i < 8; i++) ag[i] += __shfl_xor_sync(0xffffffffu, ag[i], 16);
                }
                if (rd == 6) {
#pragma unroll
                    for (int i = 0; i < 8; i++) ag[i] += __shfl_xor_sync(0xffffffffu, ag[i], 8);
                    if (lane < 8) {
                        const uint32_t dst = mapa(sb + OFF_XB + (c * 4 + aw) * 128 + (lane & 3) * 32, lane >> 2), pb = mapa(BAR(B_PEER), lane >> 2);
                        st_async4(dst, __float_as_uint(ag[0]), __float_as_uint(ag[1]), __float_as_uint(ag[2]), __float_as_uint(ag[3]), pb);
                        st_async4(dst + 16, __float_as_uint(ag[4]), __float_as_uint(ag[5]), __float_as_uint(ag[6]), __float_as_uint(ag[7]), pb);
                    }
                    __syncwarp();
                    wp += 16 * D_; FILL(b1, D_); wp -= 16 * D_;
                    if (aw == 3) {
                        mbar_wait_cluster(BAR(B_PEER), 0);
                        const float* ps = reinterpret_cast<const float*>(smem + OFF_XB) + lane;
                        const float go = (ps[0] + ps[64]) + (ps[128] + ps[192]), uo = (ps[32] + ps[96]) + (ps[160] + ps[224]);
                        const float h = rbf(silu_f(rbf(go))) * rbf(uo), ho = __shfl_xor_sync(0xffffffffu, h, 1);
                        asm volatile("st.async.weak.shared::cluster.mbarrier::complete_tx::bytes.b32 [%0], %1, [%2];"
                                     ::"r"(mapa(sb + OFF_H + c * 64 + (lane >> 1) * 4, lane & 1)), "r"((lane & 1) ? pack_bf(ho, h) : pack_bf(h, ho)),
                                       "r"(mapa(BAR(B_H), lane & 1)) : "memory");
                    }
                    mbar_wait_cluster(BAR(B_H), 0);
                    xn = *reinterpret_cast<const uint4*>(smem + OFF_H + (lane & 3) * 32 + (lane >> 4) * 16);
#pragma unroll
                    for (int i = 0; i < 8; i++) ag[i] = 0.f;
                    if (mt == 0) PROF_T(10);
                }
            }
            const int hi = lane >> 4;
            st_relaxed128(at(g_part, pair * 4096 + (c * 8 + aw * 2 + ((lane >> 3) & 1)) * 256 + hi * 128 + (lane & 7) * 16),
                          make_uint4((__float_as_uint(hi ? ag[4] : ag[0]) & ~15u) | (ep & 15u), __float_as_uint(hi ? ag[5] : ag[1]),
                                     __float_as_uint(hi ? ag[6] : ag[2]), __float_as_uint(hi ? ag[7] : ag[3])));
            if (mt == 0) PROF_T(11);
        } else {
            mbar_wait_sleep(BAR(B_SEL), 0);
        }
        const int sel = ~*reinterpret_cast<volatile unsigned*>(smem + OFF_SEL) & (S_ - 1);
        if ((sel >> 8) == g) {
            const int col = (lane & 7) * 8 + ((lane >> 3) & 1) * 4;
            const uint2 xv = __ldg(reinterpret_cast<const uint2*>(at(P.x, (sel * D_ + grp * 64 + col) * 2)));
            uint4 f[1];
            GATHER(at(g_stat, SREC(sel) * 16), 1, f[i].z == ep);
            const uint4 rec = f[0];
            const uint4* src = at(g_part, (aw * 14 + (lane >> 4)) * 4096 + grp * 256 + (lane & 15) * 16);
            if (!moe) {
                int n = 0;
                while (((ld_relaxed(src) ^ ep) & 15u) != 0 && ++n < SPIN_LIMIT) __nanosleep(500);
            }
            uint4 t[7];
            int n = 0;
            bool ok;
            do {
                ok = true;
#pragma unroll
                for (int u = 0; u < 7; u++) { t[u] = ld_relaxed128(src + u * 512); ok = ok && ((t[u].x ^ ep) & 15u) == 0; }
            } while (!__all_sync(0xffffffffu, ok) && ++n < SPIN_LIMIT);
            float4 a = make_float4(0.f, 0.f, 0.f, 0.f);
#pragma unroll
            for (int u = 0; u < 7; u++) {
                a.x += __uint_as_float(t[u].x & ~15u); a.y += __uint_as_float(t[u].y); a.z += __uint_as_float(t[u].z); a.w += __uint_as_float(t[u].w);
            }
            a.x += __shfl_xor_sync(0xffffffffu, a.x, 16); a.y += __shfl_xor_sync(0xffffffffu, a.y, 16);
            a.z += __shfl_xor_sync(0xffffffffu, a.z, 16); a.w += __shfl_xor_sync(0xffffffffu, a.w, 16);
            float4* park = reinterpret_cast<float4*>(smem + OFF_XB) + (lane & 15);
            if (lane < 16) park[aw * 16] = a;
            named_bar<4, 128>();
            if (aw == 0) {
                const float4 p1 = park[16], p2 = park[32], p3 = park[48];
                a.x = (a.x + p1.x) + (p2.x + p3.x); a.y = (a.y + p1.y) + (p2.y + p3.y);
                a.z = (a.z + p1.z) + (p2.z + p3.z); a.w = (a.w + p1.w) + (p2.w + p3.w);
                unsigned u = *reinterpret_cast<volatile unsigned*>(smem + OFF_SEL) >> 16;
                u = (u & 0x8000u) ? (u & 0x7fffu) : (~u & 0xffffu);
                const float sg = rbf(__fdividef(1.0f, 1.0f + __expf(-__uint_as_float(u << 16))));
                const float m = __uint_as_float(rec.x), ri = __uint_as_float(rec.y);
                const uint32_t n0 = norm2(xv.x, m, ri), n1 = norm2(xv.y, m, ri);
                uint2 o;
                o.x = silu2(pack_bf(bf_lo(n0) + rbf(rbf(a.x) * sg), bf_hi(n0) + rbf(rbf(a.y) * sg)));
                o.y = silu2(pack_bf(bf_lo(n1) + rbf(rbf(a.z) * sg), bf_hi(n1) + rbf(rbf(a.w) * sg)));
                if (lane < 16) *reinterpret_cast<uint2*>(smem + OFF_H + col * 2) = o;
                __syncwarp();
                if (lane == 0) { mbar_arrive(BAR(B_UPD)); PROF_T(12); }
            }
        }
    } else if (warp < 8) {
        asm volatile("setmaxnreg.inc.sync.aligned.u32 %0;" ::"n"(CONS_REGS));
        CLUSTER_WAIT();
        const int wg = warp >> 2, wq = warp & 3;
        const int wt = tid & 127;
        float acc[128];
        const uint32_t fL = BAR(B_FL + 4 * wg), eL = BAR(B_EL + 4 * wg);
        const uint32_t dL = desc_lo(SB0 + OFF_L, 16) + wg * 4096;
        constexpr uint32_t dS = desc_lo(SB0 + OFF_S, 16);
        constexpr uint32_t SL = SLOT >> 4;
#define RELEASE(ls, ss) do { if (wt == 0) { mbar_arrive(eL + 8u * (ls)); mbar_arrive(BAR(B_ES + (ss))); } } while (0)
#define WAIT_FULL(ls, lph, ss, sph) do { mbar_wait(BAR(B_FS + (ss)), sph); mbar_wait(fL + 8u * (ls), lph); } while (0)
#define TURN() do { if (wg) named_bar<6, 256>(); else named_bar<5, 256>(); } while (0)
#define PASS() do { if (wg) named_arrive<5, 256>(); else named_arrive<6, 256>(); } while (0)
#define WG_BAR() do { if (wg) named_bar<2, 128>(); else named_bar<1, 128>(); } while (0)
        if (wg == 1) PASS();

#define MMA1_H(O, s, first) do { _Pragma("unroll") for (int kk = 0; kk < 4; kk++) \
            wgmma128<O, 0>(acc, dL + (s) * SL + kk * 2 + (O) * 8, dS + DSLOT(s) * SL + kk * 2, !((first) && kk == 0)); } while (0)
#define WAIT1(s, ph) WAIT_FULL(s, ph, DSLOT(s), ph)
#define PROBE(ls, lph, ss, sph) (mbar_test(BAR(B_FS + (ss)), sph) & mbar_test(fL + 8u * (ls), lph))
#define REL1(s) RELEASE(s, DSLOT(s))
#pragma unroll 1
        for (int it = 0; it < 12; it++) {
            const int s = it & 3;
            const bool ok = PROBE(s, (it >> 2) & 1, DSLOT(s), (it >> 2) & 1);
            if (it) { wg_wait<0>(); REL1((s + 3) & 3); }
            if (!ok) WAIT1(s, (it >> 2) & 1);
            TURN();
            wg_fence(); MMA1_H(0, s, it == 0); MMA1_H(64, s, it == 0); wg_commit();
            PASS();
            if (it == 0 && tid == 0) PROF_T(16);
        }
        TS(12);
        float rs[4] = {};
        uint32_t nm[8] = {};
#define GET_STATS() do { mbar_wait(BAR(B_STATS), 0); \
            const int p0 = POS(wg * 128 + wq * 16 + (lane >> 2));                   \
            const uint32_t msk = (lane & 3) == 0 ? 0xffffffffu : (lane & 3) == 1 ? 0x0000ffffu : 0u; \
            _Pragma("unroll") for (int i = 0; i < 4; i++) { \
                const int p = p0 + (i & 1) * 2 + (i >> 1) * 64; \
                rs[i] = *reinterpret_cast<const float*>(smem + OFF_RSTD + p * 4); \
                const uint32_t m = *reinterpret_cast<const uint16_t*>(smem + OFF_MEAN + p * 2) ^ 0x8000u; \
                nm[i + (i & 2)] = (m | (m << 16)) & msk; \
            } } while (0)
        const bool early = wg || __all_sync(0xffffffffu, mbar_test(BAR(B_STATS), 0));
        if (early && !wg) GET_STATS();
        WAIT1(0, 1);
        TS(13);
        wg_wait<0>(); REL1(3);
        if (wg) GET_STATS();
        TS(14);
        TURN();
        wg_fence();
        MMA1_H(0, 0, false);
        if (tid == 0) { mbar_arrive(BAR(B_QUIET)); PROF_T(15); }
        WAIT1(1, 1); wg_fence(); MMA1_H(0, 1, false);
        WAIT1(2, 1); wg_fence(); MMA1_H(0, 2, false); wg_commit();
        if (!early) GET_STATS();
        asm volatile("" : "+r"(nm[0]), "+r"(nm[1]), "+r"(nm[2]), "+r"(nm[3]), "+r"(nm[4]), "+r"(nm[5]), "+r"(nm[6]), "+r"(nm[7])::"memory");
        wg_fence();
        wgmma128_rs<64>(acc, nm + 4, (SB0 + OFF_RS) >> 4);
        wgmma128_rs<0>(acc, nm, (SB0 + OFF_RS) >> 4);
        WAIT1(3, 1); wg_fence(); MMA1_H(0, 3, false); wg_commit();
        PASS();
        const int mrow = wq * 16 + ((lane >> 3) & 1) * 8 + (lane & 7);
#define EPI1(O, slot, FREE) do { const uint32_t dst = sb + OFF_S + (slot) * SLOT + mrow * 128; \
            uint32_t pk[32]; \
            _Pragma("unroll") for (int i = 0; i < 32; i += 4) { \
                _Pragma("unroll") for (int k = 0; k < 4; k++) \
                    pk[i + k] = pack_bf(acc[(O) + 2 * (i + k)] * rs[(O) / 32 + (k & 1)], acc[(O) + 2 * (i + k) + 1] * rs[(O) / 32 + (k & 1)]); \
                if (i == EF) { FREE; } \
                if (i >= EF) { _Pragma("unroll") for (int v = (i == EF ? 0 : i); v <= i; v += 4) \
                    stmatrix4(dst + ((v >> 4) ^ c ^ 1) * 8192 + ((((v >> 1) & 7) + (lane >> 4)) ^ (lane & 7)) * 16, pk[v], pk[v + 1], pk[v + 2], pk[v + 3]); } } \
            WG_BAR(); \
            if (wt == 0) mbar_arrive(BAR(B_FS + (slot))); } while (0)
        TS(15);
        wg_wait<0>();
        fence_regs64<0>(acc);
        TS(16);
        {
            constexpr int EF = 0;
            EPI1(0, wg, if (wg) mbar_wait(BAR(B_FS), 0));
        }
        TS(17);
        TURN();
        wg_fence();
        MMA1_H(64, 0, false); wg_commit();
        MMA1_H(64, 1, false); wg_commit();
        MMA1_H(64, 2, false); wg_commit();
        wg_wait<2>(); REL1(0);
        MMA1_H(64, 3, false); wg_commit();
        PASS();
        TS(18);
        wg_wait<2>(); REL1(1);
        mbar_wait(BAR(B_FS), 0); mbar_wait(BAR(B_FS + 1), 0); fence_async_smem();
        wg_wait<1>(); REL1(2);
        wg_wait<0>(); REL1(3);
        fence_regs64<64>(acc);
        TS(19);
        {
            constexpr int EF = 16;
            EPI1(64, 2 + wg, mbar_wait(BAR(B_ES + 2 + wg), 1));
        }
        TS(20);

        float ac2[128];
#define MMA2_H(O, ls, ss, first) do { _Pragma("unroll") for (int kk = 0; kk < 4; kk++) \
            wgmma128<O, 1>(ac2, dS + (ss) * SL + kk * 128 + (O) * 8, dL + (ls) * SL + kk * 2, !((first) && kk == 0)); } while (0)
#define WAIT2(j) WAIT_FULL((j) & 3, ((j) >> 2) & 1, PSLOT(j), PPAR(j))
#define MMA2(j) do { wg_fence(); MMA2_H(0, (j) & 3, PSLOT(j), (j) == 0); MMA2_H(64, (j) & 3, PSLOT(j), (j) == 0); wg_commit(); } while (0)
#define REL2(j) RELEASE((j) & 3, PSLOT(j))
        WAIT2(0); TURN(); MMA2(0);
        WAIT2(1); MMA2(1); PASS();
        TS(21);
        wg_wait<1>(); REL2(0);
        mbar_wait(BAR(B_FS + 2), 0); mbar_wait(BAR(B_FS + 3), 0); fence_async_smem();
        TS(22);
        {
            uint32_t l2 = 2, s2 = 2, sp = 1, lph = 0, sph = 0;
#pragma unroll 1
            for (int j = 2; j < XJ; j += 2) {
#pragma unroll
                for (int h = 0; h < 2; h++) {
                    const bool ok = PROBE(l2 + h, lph, s2 + h, sph);
                    wg_wait<0>(); RELEASE(h ? l2 : 3 - l2, h ? s2 : sp);
                    if (!ok) WAIT_FULL(l2 + h, lph, s2 + h, sph);
                    TURN();
                    wg_fence(); MMA2_H(0, l2 + h, s2 + h, false); MMA2_H(64, l2 + h, s2 + h, false); wg_commit();
                    PASS();
                    if (h == (GOJ & 1) && j == (GOJ & ~1) && wt == 0) { mbar_arrive(BAR(B_GO)); if (wg == 0) PROF_T(19); }
                }
                sp = s2 + 1; s2 = 2 * l2; sph = lph; l2 ^= 2;
                lph ^= l2 == 0;
            }
        }
        if (tid == 0) PROF_T(20);
        uint32_t gt[32];
        const uint32_t xrow = sb + OFF_S + 2 * SLOT + wg * 8192 + ((lane >> 4) * 8 + (lane & 7)) * 128 + (((2 * wq + ((lane >> 3) & 1)) ^ (lane & 7)) << 4);
        const uint32_t gsign = c ? 0x80008000u : 0u;
#define XOFF(v) (((v) >> 2) * SLOT + ((v) & 3) * 2048)
        mbar_wait(BAR(B_SEL), 0);
        const int sel = ~*reinterpret_cast<volatile unsigned*>(smem + OFF_SEL) & (S_ - 1);
        bool own = (sel >> 7) == 2 * g + wg;
#define PATCH() do { own = false; \
            const uint32_t v0 = *reinterpret_cast<const uint16_t*>(smem + OFF_H + (wq * 16 + (lane >> 2)) * 2) ^ gsign; \
            const uint32_t v1 = *reinterpret_cast<const uint16_t*>(smem + OFF_H + (wq * 16 + (lane >> 2)) * 2 + 16) ^ gsign; \
            const uint32_t pick = (lane & 3) != ((sel >> 1) & 3) ? 0x3210u : (sel & 1) ? 0x5410u : 0x3254u; \
            _Pragma("unroll") for (int i = 0; i < 16; i++) { \
                const uint32_t m = ((sel >> 3) & 15) == i ? pick : 0x3210u; \
                gt[2 * i] = __byte_perm(gt[2 * i], v0, m); \
                gt[2 * i + 1] = __byte_perm(gt[2 * i + 1], v1, m); \
            } } while (0)
#pragma unroll
        for (int u = 0; u < 8; u++) {
            if (u) { WAIT2(XJ + u - 1); wg_wait<0>(); REL2(XJ + u - 2); TURN(); MMA2(XJ + u - 1); PASS(); }
            uint32_t* o = &gt[4 * u];
            if (!(u & 3)) mbar_wait(BAR(B_FS + 2 + (u >> 2)), 1);
            ldmatrix4t(xrow + XOFF(u), o[0], o[1], o[2], o[3]);
            const float4 r4 = *reinterpret_cast<const float4*>(smem + OFF_RSTD + (wg * 128 + u * 16 + (lane & 3) * 4) * 4);
            const uint2 m2 = *reinterpret_cast<const uint2*>(smem + OFF_MEAN + (wg * 128 + u * 16 + (lane & 3) * 4) * 2);
            o[0] = gate2(o[0], m2.x, r4.x, r4.y) ^ gsign;
            o[1] = gate2(o[1], m2.x, r4.x, r4.y) ^ gsign;
            o[2] = gate2(o[2], m2.y, r4.z, r4.w) ^ gsign;
            o[3] = gate2(o[3], m2.y, r4.z, r4.w) ^ gsign;
            asm volatile("st.shared.v2.u32 [%0], {%1,%2};" ::"r"(sb + OFF_SEL + 16), "r"(o[0] ^ o[1]), "r"(o[2] ^ o[3]) : "memory");
        }
        if (tid == 0) PROF_T(21);
        WAIT2(27);
        wg_wait<0>(); REL2(26);
        if (own) {
            const uint32_t t0 = clock32();
            bool ok;
            while (!(ok = mbar_test(BAR(B_UPD), 0)) && clock32() - t0 < wg * 1900u) __nanosleep(50);
            if (__all_sync(0xffffffffu, ok)) PATCH();
        }
        TS(0);
        TURN();
        MMA2(27);
        WAIT2(28); wg_fence(); MMA2_H(0, 0, PSLOT(28), false); wg_commit();
        if (wg == 0) { wg_fence(); MMA2_H(64, 0, PSLOT(28), false); wg_commit(); }
        constexpr uint32_t dL0 = desc_lo(SB0 + OFF_L, 16);
        const uint32_t ct[3] = {wg ? 3u : 1u, wg ? 1u : 2u, wg ? 2u : 5u};
#define TMMA(O, i) wgmma128<O, 1>(ac2, ((i) < 8 ? dS + PSLOT(29 + ((i) >> 2)) * SL : dL0 + 6 * SL) + ((i) & 3) * 128 + (O) * 8, \
                                  dL0 + ct[(i) >> 2] * SL + ((i) & 3) * 2, 1)
#define KEEP(i) TMMA(64, i)
#pragma unroll
        for (int k = 0; k < 3; k++) {
            if (k < 2) mbar_wait(BAR(B_FS + PSLOT(29 + k)), PPAR(29 + k)); else mbar_wait(BAR(B_FL + 6), 1);
            mbar_wait(BAR(B_FL + ct[k]), k == 0 || wg == 0);
            wg_fence();
#pragma unroll
            for (int i = 4 * k; i < 4 * k + 4; i++) TMMA(0, i);
            wg_commit();
            if (k < 2) wg_wait<2>();
            if (k == 0 && tid == 0) mbar_arrive(BAR(B_EL + 3));
            if (k == 1 && tid == 0) mbar_arrive_cluster(mapa(BAR(B_RDY), c ^ 1));
        }
        TS(1);
        wg_fence();
#pragma unroll
        for (int i = 0; i < KQ; i++) KEEP(i);
        wg_commit();
        mbar_wait(BAR(B_RDY + wg), 0);
        wg_wait<1>();
        fence_regs64<0>(ac2);
        TS(2);
        wg_fence();
        {
            const uint32_t dst = mapa(sb + OFF_L + wg * 5 * SLOT + wt * 16, c ^ 1), rb = mapa(BAR(B_RECV + 2 * wg), c ^ 1);
#pragma unroll
            for (int v = 0; v < 8; v++) {
                if (KQ + v < 12) KEEP(KQ + v);
                if (KQ + v == 7) wg_commit();
                if (KQ + v == 11) { wg_commit(); if (wg == 0) PASS(); }
                st_async4(dst + v * 2048, pack_bf(ac2[8 * v + 0], ac2[8 * v + 1]), pack_bf(ac2[8 * v + 2], ac2[8 * v + 3]),
                          pack_bf(ac2[8 * v + 4], ac2[8 * v + 5]), pack_bf(ac2[8 * v + 6], ac2[8 * v + 7]), rb + (v >> 2) * 8);
            }
        }
        if (wg == 1) { wg_fence(); MMA2_H(64, 0, PSLOT(28), false); wg_commit(); }
        TS(3);
        uint32_t xr[32];
#define LDX(v) ldmatrix4t(xrow + XOFF(v), xr[4 * (v)], xr[4 * (v) + 1], xr[4 * (v) + 2], xr[4 * (v) + 3])
        if (wg == 0) {
            wg_wait<2>();
            if (wt == 0) mbar_arrive(BAR(B_EL + 1));
            wg_wait<1>();
            if (wt == 0) mbar_arrive(BAR(B_EL + 2));
        }
#pragma unroll
        for (int v = 0; v < XE; v++) LDX(v);
        if (wg == 0) {
            wg_wait<0>();
            if (wt == 0) mbar_arrive_cluster(mapa(BAR(B_RDY + 1), c ^ 1));
        }
        TS(4);
        if (own) { mbar_wait(BAR(B_UPD), 0); PATCH(); }
        TS(5);
        uint4 rv[8];
#define FETCH(v0) do { if ((v0) == 0 || (v0) == 4) mbar_wait_cluster(BAR(B_RECV + 2 * wg + (v0) / 4), 0); \
            _Pragma("unroll") for (int v = (v0); v < (v0) + 2; v++) { \
                asm volatile("ld.shared.v4.u32 {%0,%1,%2,%3}, [%4];" : "=r"(rv[v].x), "=r"(rv[v].y), "=r"(rv[v].z), "=r"(rv[v].w) \
                             : "r"(sb + OFF_L + wg * 5 * SLOT + v * 2048 + wt * 16) : "memory"); \
                if (v >= XE) LDX(v); } } while (0)
        FETCH(0);
        TS(6);
        wg_wait<0>();
        fence_regs64<64>(ac2);
        TS(7);
#pragma unroll
        for (int v0 = 0; v0 < 8; v0 += 2) {
#pragma unroll
            for (int v = v0; v < v0 + 2; v++) {
                const float* a = &ac2[64 + 8 * v];
                stmatrix4t(xrow + XOFF(v),
                           bfma2(bsub2(pack_bf(a[0], a[1]), rv[v].x), gt[4 * v + 0], xr[4 * v + 0]),
                           bfma2(bsub2(pack_bf(a[2], a[3]), rv[v].y), gt[4 * v + 1], xr[4 * v + 1]),
                           bfma2(bsub2(pack_bf(a[4], a[5]), rv[v].z), gt[4 * v + 2], xr[4 * v + 2]),
                           bfma2(bsub2(pack_bf(a[6], a[7]), rv[v].w), gt[4 * v + 3], xr[4 * v + 3]));
            }
            WG_BAR();
            if (wt == 0) mbar_arrive(eL + 4 * v0);
            if (v0 + 2 < 8) FETCH(v0 + 2);
            if (v0 == 0) TS(8);
        }
        TS(9);
    } else {
        asm volatile("setmaxnreg.dec.sync.aligned.u32 %0;" ::"n"(PROD_REGS));
#define XROWS(k) do { mbar_expect_tx(XBAR(k), 8192); bulk_g2s(sb + OFF_S + (k) * 8192, at(P.x, (b * 16 + (k) * 4) * D_ * 2), 8192, XBAR(k)); } while (0)
        if (warp == 12) {
            if (elect_one()) {
                const CUtensorMap* tmD = c ? &tm_dim : &tm_dre;
#pragma unroll 1
                for (int it = 1; it < 4; it++) {
                    while (clock32() - (uint32_t)tstart < LDEL + (it - 1) * LGAP) {}
                    LOAD0(it);
                    if (it >= X0) XROWS(it - X0);
                }
            }
            __syncwarp();
        }
        CLUSTER_WAIT();
        if (warp == 12) {
            if (elect_one()) {
                const CUtensorMap* tmD = c ? &tm_dim : &tm_dre;
#pragma unroll 1
                for (int it = 4; it < 16; it++) {
                    const int s = DSLOT(it);
                    mbar_wait(BAR(B_ES + s), ((it >> 2) & 1) ^ 1);
                    TRACE(it);
                    mbar_expect_tx(BAR(B_FS + s), SLOT);
                    tma_2d(sb + OFF_S + s * SLOT, tmD, it * 64, r * 128, BAR(B_FS + s));
                    if (it < 4 + X0) XROWS(it - X0);
                }
                const unsigned ep = load_epoch(b), e8 = ep & 0xffu;
                const uint8_t* abg = at(AB, grp * 32 * SLOT);
                const unsigned long long* fl = at(g_flag, grp * 128);
                unsigned long long rdy = ld_acquire64(fl);
                mbar_wait(BAR(B_SRD), 0);
                st_release8(at(g_flag, grp * 128 + g), e8);
                PROF_T(7);
                int j = 4;
#pragma unroll 1
                for (int cl = 0; cl < 4; cl++) {
                    if (cl) rdy = ld_acquire64(++fl);
                    fence_async_global();
#pragma unroll 1
                    for (int n = 1; n < 8; n++, j++) {
                        const int q = BLK(n), s = (j & 1) + ((j & 2) ? 0 : 4);
                        const uint32_t fb = BAR(j == 31 ? B_FL + 6 : B_FS + s);
                        if (j == 31) mbar_wait(BAR(B_EL + 6), 0); else mbar_wait(BAR(B_ES + s), ((j >> 2) ^ (j >> 1)) & 1);
                        if (j == 7) mbar_wait(BAR(B_SRD + 1), 0);
                        if (((unsigned)(rdy >> (8 * q)) & 0xffu) != e8) {
                            int m = 0;
                            do { rdy = ld_acquire64(fl); } while (((unsigned)(rdy >> (8 * q)) & 0xffu) != e8 && ++m < SPIN_LIMIT);
                            fence_async_global();
                        }
                        TRACE(16 + j);
                        mbar_expect_tx(fb, SLOT);
                        bulk_g2s(sb + (j == 31 ? OFF_L + 6 * SLOT : OFF_S + s * SLOT), at(abg, (4 * q + KO(cl)) * SLOT), SLOT, fb);
                    }
                }
                *at(g_epoch, b * 4) = ep;
            }
        } else if (warp < 15) {
            if (elect_one()) {
                const int w = warp - 13, row0 = g * 256 + w * 128;
                const CUtensorMap* tmC = c ? &tm_cim : &tm_cre;
                const uint32_t fb = BAR(B_FL + 4 * w), eb = BAR(B_EL + 4 * w), dst = sb + OFF_L + w * 4 * SLOT;
                [[maybe_unused]] unsigned long long mk = 0, mg = 0;
                int n = 0, cl = 0;
#pragma unroll 1
                for (int it = 4; it < 47 - 2 * w; it++) {
                    const int s = it & 3;
                    mbar_wait(eb + 8 * s, ((it >> 2) & 1) ^ 1);
                    TRACE(64 + w * 64 + it - 4);
                    MARK(it);
                    mbar_expect_tx(fb + 8 * s, SLOT);
                    tma_2d(dst + s * SLOT, it < 16 ? &tm_x : tmC, (it < 16 ? it : 4 * (n ? BLK(n) : g) + KO(cl)) * 64, row0, fb + 8 * s);
                    if (it == PTJ) prefetch_tmap(w ? &tm_x64 : tmC);
                    if (it == PTJ && w) prefetch_tmap(&tm_out);
                    if (it >= 16) {
                        if (it == 19) { n = 1; cl = 0; } else if (it < 19) cl++; else if (++n == 8) { n = 1; cl++; }
                    }
                }
#pragma unroll 1
                for (int i = 2 * w; i < 3; i++) {
                    const int s = w ? 1 : i ? i : 3;
                    mbar_wait(eb + 8 * s, w == 0 && i);
                    mbar_expect_tx(fb + 8 * s, SLOT);
                    tma_2d(dst + s * SLOT, tmC, (4 * BLK(5 + i) + 3) * 64, row0 ^ 128, fb + 8 * s);
                }
                if (w && (r & 3) < 2) tma_2d_prefetch(tmC, (4 * BLK(6 + (r & 1)) + 3) * 64, row0);
#pragma unroll 1
                for (int h = 0; h < 4; h++) {
                    mbar_wait(eb + 8 * h, ((w ? 7 : 9) >> h) & 1);
                    fence_async_smem();
                    tma_2d_store(&tm_out, grp * 64, row0 + h * 32, sb + OFF_S + (2 + (h >> 1)) * SLOT + w * 8192 + (h & 1) * 4096);
                    bulk_commit();
                }
                FINISH(w);
            }
        } else {
            const unsigned ep = load_epoch(b);
            uint4 f[4];
            {
                sleep_until((uint32_t)tstart + 6000);
                const uint4* keys = at(reinterpret_cast<const uint4*>(g_key), lane * 16);
                bool mine = false;
                int n = 0;
                do {
                    f[0] = ld_relaxed128(keys); f[1] = ld_relaxed128(keys + 32);
                    if (__all_sync(0xffffffffu, f[0].y == ep && f[0].w == ep && f[1].y == ep && f[1].w == ep)) break;
                    if (!mine) {
                        mbar_wait(BAR(B_LST), 0);
                        const uint4 k = *reinterpret_cast<const uint4*>(smem + OFF_XB);
                        if (lane == 0) st_relaxed64(at(g_key, b * 8), ((unsigned long long)ep << 32) | max(max(k.x, k.y), max(k.z, k.w)));
                        mine = true;
                    }
                    __nanosleep(GSL);
                } while (++n < SPIN_LIMIT);
                const unsigned key = __reduce_max_sync(0xffffffffu, max(max(f[0].x, f[0].z), max(f[1].x, f[1].z)));
                if (lane == 0) { *reinterpret_cast<unsigned*>(smem + OFF_SEL) = key; mbar_arrive(BAR(B_SEL)); PROF_T(8); }
            }
            if (elect_one()) {
#pragma unroll 1
                for (int cl = 0; cl < 4; cl++) {
                    uint8_t* dst = at(AB, (grp * 32 + 4 * g + KO(cl)) * SLOT);
                    const uint32_t src = sb + OFF_S + cl * SLOT, chunk = cl ? 1024 : SLOT;
                    mbar_wait(BAR(B_FS + cl), 0);
                    fence_async_smem();
                    if (cl == 0) PROF_T(3);
                    uint32_t t0 = clock32() + (cl == 1 ? PDEL : 0);
#pragma unroll 1
                    for (uint32_t o = 0; o < SLOT; o += chunk) {
                        sleep_until(t0);
                        bulk_s2g(dst + o, src + o, chunk);
                        bulk_commit();
                        t0 += cl == 1 ? PGAP1 : cl == 2 ? PGAP2 : PGAP3;
                    }
                    bulk_wait<0>();
                    fence_async_global();
                    TRACE(252 + cl);
                    if (cl < 2) mbar_arrive(BAR(B_SRD + cl));
                    else {
                        mbar_wait(BAR(B_ES + cl), 0);
                        mbar_expect_tx(BAR(B_FS + cl), SLOT);
                        tma_2d(src, &tm_x64, grp * 64, g * 256 + (cl - 2) * 64, BAR(B_FS + cl));
                        tma_2d(src + 8192, &tm_x64, grp * 64, g * 256 + (cl - 2) * 64 + 128, BAR(B_FS + cl));
                    }
                    if (cl) st_release8(at(g_flag, grp * 128 + cl * 8 + g), ep & 0xffu);
                    if (cl == 1) PROF_T(5);
                    if (cl == 3) PROF_T(4);
                }
            }
        }
    }
}

typedef CUresult (*EncodeFn)(CUtensorMap*, CUtensorMapDataType, cuuint32_t, void*, const cuuint64_t*, const cuuint64_t*,
                             const cuuint32_t*, const cuuint32_t*, CUtensorMapInterleave, CUtensorMapSwizzle,
                             CUtensorMapL2promotion, CUtensorMapFloatOOBfill);

void make_map(EncodeFn fn, CUtensorMap* tm, const void* p, uint64_t rows, uint64_t cols, uint32_t box_rows) {
    cuuint64_t dims[2] = {cols, rows};
    cuuint64_t strides[1] = {cols * 2};
    cuuint32_t box[2] = {64, box_rows};
    cuuint32_t es[2] = {1, 1};
    fn(tm, CU_TENSOR_MAP_DATA_TYPE_BFLOAT16, 2, const_cast<void*>(p), dims, strides, box, es, CU_TENSOR_MAP_INTERLEAVE_NONE,
       CU_TENSOR_MAP_SWIZZLE_128B, CU_TENSOR_MAP_L2_PROMOTION_L2_128B, CU_TENSOR_MAP_FLOAT_OOB_FILL_NONE);
}

}

extern "C" void kernel_launch(void* const* d_in, const int* in_sizes, int n_in, void* d_out, int out_size) {
    (void)in_sizes; (void)n_in; (void)out_size;
    static EncodeFn fn = nullptr;
    if (!fn) {
        void* p = nullptr;
        cudaDriverEntryPointQueryResult q;
        cudaGetDriverEntryPoint("cuTensorMapEncodeTiled", &p, cudaEnableDefault, &q);
        fn = (EncodeFn)p;
        cudaFuncSetAttribute(fnet_fused_kernel, cudaFuncAttributeMaxDynamicSharedMemorySize, SMEM_BYTES);
    }
    CUtensorMap tx, tdre, tdim, tcre, tcim, tout, tx64;
    make_map(fn, &tx, d_in[0], S_, D_, 128);
    make_map(fn, &tcre, d_in[1], S_, S_, 128);
    make_map(fn, &tcim, d_in[2], S_, S_, 128);
    make_map(fn, &tdre, d_in[3], D_, D_, 128);
    make_map(fn, &tdim, d_in[4], D_, D_, 128);
    make_map(fn, &tx64, d_in[0], S_, D_, 64);
    make_map(fn, &tout, d_out, S_, D_, 32);
    Params P;
    P.x = (const __nv_bfloat16*)d_in[0];
    P.dre = (const __nv_bfloat16*)d_in[3];
    P.dim = (const __nv_bfloat16*)d_in[4];
    P.wr = (const __nv_bfloat16*)d_in[6];
    P.wg = (const __nv_bfloat16*)d_in[7];
    P.wu = (const __nv_bfloat16*)d_in[8];
    P.wd = (const __nv_bfloat16*)d_in[9];
    P.zero = 0;
    fnet_fused_kernel<<<NCTA, NTHREADS, SMEM_BYTES, cudaStreamPerThread>>>(tx, tdre, tdim, tcre, tcim, tout, tx64, P);
}
```

```cpp
#include <cuda_runtime.h>
#include <cuda_bf16.h>
#include <cuda.h>
#include <stdint.h>

#define GSL 200
#define SLEEP_NS 200
#define PDEL 1000
#define PGAP1 200
#define PGAP2 200
#define PGAP3 240
#define GOJ 2
#define LDEL 1400
#define LGAP 750
#define PTJ 10
#define X0 2
#define KQ 5
#define XE 2
#define PROD_REGS 32
#define CONS_REGS 184

namespace {

constexpr int S_ = 2048, D_ = 1024, F_ = 3584;
constexpr int NCTA = 128;
constexpr int XJ = 20;
constexpr uint32_t SLOT = 16384;
constexpr uint32_t OFF_L = 0;
constexpr uint32_t OFF_S = 8 * SLOT;
constexpr uint32_t OFF_RS = OFF_S + SLOT;
constexpr uint32_t OFF_BAR = 14 * SLOT;
constexpr uint32_t OFF_SEL = OFF_BAR + 360;
constexpr uint32_t OFF_RSTD = OFF_BAR + 384;
constexpr uint32_t OFF_MEAN = OFF_RSTD + 1024;
constexpr uint32_t OFF_XB = OFF_MEAN + 512;
constexpr uint32_t OFF_H = OFF_XB + 1024;
constexpr uint32_t SMEM_BYTES = OFF_H + 128;
constexpr uint32_t SB0 = 1024;
constexpr int NTHREADS = 512;
static_assert(SMEM_BYTES <= 232448, "smem");

enum { B_FS = 0, B_ES = 6, B_FL = 12, B_EL = 20, B_SRD = 28, B_RECV = 30  , B_RDY = 34, B_STATS = 36, B_LST = 37, B_UPD = 38,
       B_QUIET = 39, B_GO = 40, B_PEER = 41, B_SEL = 42, B_H = 43, B_COUNT = 44 };
static_assert(B_COUNT * 8 <= 360, "barriers");

__device__ __align__(1024) uint8_t g_ab[16u * 32u * SLOT];
__device__ __align__(128) uint4 g_part[56 * (D_ / 4)];
__device__ __align__(128) uint4 g_stat[S_];
__device__ __align__(128) uint4 g_rs[D_];
__device__ __align__(128) unsigned long long g_key[NCTA];
__device__ __align__(128) unsigned long long g_flag[16 * 16];
__device__ __align__(128) unsigned g_epoch[NCTA];
#define PROF_T(i) do {} while (0)
#define TRACE(i) do {} while (0)
#define PROF_G(i) do {} while (0)
#define TS(i) do {} while (0)
#define FINISH(wg) bulk_wait_read<0>()

#define MARK(it) do {} while (0)

__device__ __forceinline__ uint32_t smem_u32(const void* p) { return (uint32_t)__cvta_generic_to_shared(p); }
__device__ __forceinline__ void mbar_init(uint32_t bar, uint32_t cnt) {
    asm volatile("mbarrier.init.shared::cta.b64 [%0], %1;" ::"r"(bar), "r"(cnt) : "memory");
}
__device__ __forceinline__ bool mbar_try(uint32_t bar, uint32_t parity) {
    uint32_t ok;
    asm volatile("{\n.reg .pred p;\nmbarrier.try_wait.parity.shared::cta.b64 p, [%1], %2;\nselp.u32 %0, 1, 0, p;\n}"
                 : "=r"(ok) : "r"(bar), "r"(parity) : "memory");
    return ok;
}
__device__ __forceinline__ bool mbar_test(uint32_t bar, uint32_t parity) {
    uint32_t ok;
    asm volatile("{\n.reg .pred p;\nmbarrier.test_wait.parity.shared::cta.b64 p, [%1], %2;\nselp.u32 %0, 1, 0, p;\n}"
                 : "=r"(ok) : "r"(bar), "r"(parity) : "memory");
    return ok;
}
__device__ __forceinline__ bool mbar_try_cluster(uint32_t bar, uint32_t parity) {
    uint32_t ok;
    asm volatile("{\n.reg .pred p;\nmbarrier.try_wait.parity.acquire.cluster.shared::cta.b64 p, [%1], %2;\nselp.u32 %0, 1, 0, p;\n}"
                 : "=r"(ok) : "r"(bar), "r"(parity) : "memory");
    return ok;
}
constexpr int SPIN_LIMIT = 1 << 20;
__device__ __forceinline__ void mbar_wait(uint32_t bar, uint32_t parity) {
    if (mbar_try(bar, parity)) return;
    int n = 0;
    while (!mbar_try(bar, parity) && ++n < SPIN_LIMIT) {}
}
__device__ __forceinline__ void mbar_wait_cluster(uint32_t bar, uint32_t parity) {
    int n = 0;
    while (!mbar_try_cluster(bar, parity) && ++n < SPIN_LIMIT) {}
}
__device__ __forceinline__ void mbar_wait_sleep(uint32_t bar, uint32_t parity) {
    int n = 0;
    while (!mbar_try(bar, parity) && ++n < SPIN_LIMIT) __nanosleep(SLEEP_NS);
}
__device__ __forceinline__ void mbar_arrive(uint32_t bar) {
    asm volatile("mbarrier.arrive.shared::cta.b64 _, [%0];" ::"r"(bar) : "memory");
}
__device__ __forceinline__ void mbar_arrive_cluster(uint32_t cluster_bar) {
    asm volatile("mbarrier.arrive.shared::cluster.b64 _, [%0];" ::"r"(cluster_bar) : "memory");
}
__device__ __forceinline__ void mbar_expect_tx(uint32_t bar, uint32_t bytes) {
    asm volatile("mbarrier.arrive.expect_tx.shared::cta.b64 _, [%0], %1;" ::"r"(bar), "r"(bytes) : "memory");
}
__device__ __forceinline__ bool elect_one() {
    uint32_t p;
    asm volatile("{\n.reg .pred p;\nelect.sync _|p, 0xffffffff;\nselp.u32 %0, 1, 0, p;\n}" : "=r"(p));
    return p;
}
__device__ __forceinline__ uint32_t mapa(uint32_t addr, uint32_t rank) {
    uint32_t r;
    asm("mapa.shared::cluster.u32 %0, %1, %2;" : "=r"(r) : "r"(addr), "r"(rank));
    return r;
}
__device__ __forceinline__ uint32_t clock32() { uint32_t t; asm volatile("mov.u32 %0, %%clock;" : "=r"(t)); return t; }
__device__ __forceinline__ void sleep_until(uint32_t t) {
    int n = 0;
    while ((int)(clock32() - t) < 0 && ++n < SPIN_LIMIT) __nanosleep(20);
}
__device__ __forceinline__ void yield(float last, uint32_t zero) {
    asm volatile("nanosleep.u32 %0;" ::"r"(__float_as_uint(last) & zero));
}
template <typename T> __device__ __forceinline__ T* at(T* p, uint32_t bytes) {
    asm("" : "+r"(bytes));
    return reinterpret_cast<T*>(reinterpret_cast<uintptr_t>(p) + bytes);
}
__device__ __forceinline__ void tma_2d(uint32_t dst, const CUtensorMap* tm, int c0, int c1, uint32_t bar) {
    asm volatile("cp.async.bulk.tensor.2d.shared::cluster.global.mbarrier::complete_tx::bytes [%0], [%1, {%3, %4}], [%2];"
                 ::"r"(dst), "l"(tm), "r"(bar), "r"(c0), "r"(c1) : "memory");
}
__device__ __forceinline__ void tma_2d_prefetch(const CUtensorMap* tm, int c0, int c1) {
    asm volatile("cp.async.bulk.prefetch.tensor.2d.L2.global [%0, {%1, %2}];" ::"l"(tm), "r"(c0), "r"(c1) : "memory");
}
__device__ __forceinline__ void tma_2d_store(const CUtensorMap* tm, int c0, int c1, uint32_t src) {
    asm volatile("cp.async.bulk.tensor.2d.global.shared::cta.bulk_group [%0, {%2, %3}], [%1];"
                 ::"l"(tm), "r"(src), "r"(c0), "r"(c1) : "memory");
}
__device__ __forceinline__ void bulk_g2s(uint32_t dst, const void* src, uint32_t bytes, uint32_t bar) {
    asm volatile("cp.async.bulk.shared::cluster.global.mbarrier::complete_tx::bytes [%0], [%1], %2, [%3];"
                 ::"r"(dst), "l"(src), "r"(bytes), "r"(bar) : "memory");
}
__device__ __forceinline__ void bulk_s2g(void* dst, uint32_t src, uint32_t bytes) {
    asm volatile("cp.async.bulk.global.shared::cta.bulk_group [%0], [%1], %2;" ::"l"(dst), "r"(src), "r"(bytes) : "memory");
}
__device__ __forceinline__ void st_async4(uint32_t dst, uint32_t a, uint32_t b, uint32_t c, uint32_t d, uint32_t bar) {
    asm volatile("st.async.weak.shared::cluster.mbarrier::complete_tx::bytes.v4.b32 [%0], {%1,%2,%3,%4}, [%5];"
                 ::"r"(dst), "r"(a), "r"(b), "r"(c), "r"(d), "r"(bar) : "memory");
}
__device__ __forceinline__ void bulk_commit() { asm volatile("cp.async.bulk.commit_group;" ::: "memory"); }
template <int N> __device__ __forceinline__ void bulk_wait_read() { asm volatile("cp.async.bulk.wait_group.read %0;" ::"n"(N) : "memory"); }
template <int N> __device__ __forceinline__ void bulk_wait() { asm volatile("cp.async.bulk.wait_group %0;" ::"n"(N) : "memory"); }
__device__ __forceinline__ void fence_async_smem() { asm volatile("fence.proxy.async.shared::cta;" ::: "memory"); }
__device__ __forceinline__ void fence_async_global() { asm volatile("fence.proxy.async.global;" ::: "memory"); }
__device__ __forceinline__ void prefetch_tmap(const CUtensorMap* tm) {
    asm volatile("prefetch.tensormap [%0];" ::"l"(tm) : "memory");
}
__device__ __forceinline__ unsigned long long ld_acquire64(const unsigned long long* p) {
    unsigned long long v; asm volatile("ld.acquire.gpu.global.u64 %0, [%1];" : "=l"(v) : "l"(p) : "memory"); return v;
}
__device__ __forceinline__ unsigned load_epoch(int b) {
    unsigned v; asm volatile("ld.global.u32 %0, [%1];" : "=r"(v) : "l"(at(g_epoch, b * 4)) : "memory"); return v + 1;
}
__device__ __forceinline__ unsigned ld_relaxed(const void* p) {
    unsigned v; asm volatile("ld.relaxed.gpu.global.u32 %0, [%1];" : "=r"(v) : "l"(p) : "memory"); return v;
}
__device__ __forceinline__ uint4 ld_relaxed128(const uint4* p) {
    uint4 v;
    asm volatile("{\n.reg .b128 t;\n.reg .b64 lo, hi;\nld.relaxed.gpu.global.b128 t, [%4];\nmov.b128 {lo, hi}, t;\n"
                 "mov.b64 {%0, %1}, lo;\nmov.b64 {%2, %3}, hi;\n}"
                 : "=r"(v.x), "=r"(v.y), "=r"(v.z), "=r"(v.w) : "l"(p) : "memory");
    return v;
}
__device__ __forceinline__ void st_relaxed128(uint4* p, const uint4& v) {
    asm volatile("{\n.reg .b128 t;\n.reg .b64 lo, hi;\nmov.b64 lo, {%1, %2};\nmov.b64 hi, {%3, %4};\nmov.b128 t, {lo, hi};\n"
                 "st.relaxed.gpu.global.b128 [%0], t;\n}"
                 ::"l"(p), "r"(v.x), "r"(v.y), "r"(v.z), "r"(v.w) : "memory");
}
__device__ __forceinline__ void st_relaxed64(unsigned long long* p, unsigned long long v) {
    asm volatile("st.relaxed.gpu.global.u64 [%0], %1;" ::"l"(p), "l"(v) : "memory");
}
__device__ __forceinline__ void st_release8(void* p, unsigned v) {
    asm volatile("st.release.gpu.global.u8 [%0], %1;" ::"l"(p), "r"(v) : "memory");
}
__device__ __forceinline__ uint64_t policy_evict_first() {
    uint64_t pol;
    asm("createpolicy.fractional.L2::evict_first.b64 %0, 1.0;" : "=l"(pol));
    return pol;
}
__device__ __forceinline__ uint4 ldg_stream(const void* p, uint64_t pol) {
    uint4 v;
    asm volatile("ld.global.nc.L1::no_allocate.L2::cache_hint.v4.u32 {%0,%1,%2,%3}, [%4], %5;"
                 : "=r"(v.x), "=r"(v.y), "=r"(v.z), "=r"(v.w) : "l"(p), "l"(pol));
    return v;
}
__device__ __forceinline__ uint4 ldg_stream_ord(const void* p, uint64_t pol) {
    uint4 v;
    asm volatile("ld.relaxed.gpu.global.L1::no_allocate.L2::cache_hint.v4.u32 {%0,%1,%2,%3}, [%4], %5;"
                 : "=r"(v.x), "=r"(v.y), "=r"(v.z), "=r"(v.w) : "l"(p), "l"(pol) : "memory");
    return v;
}
template <int ID, int N> __device__ __forceinline__ void named_arrive() { asm volatile("bar.arrive %0, %1;" ::"n"(ID), "n"(N) : "memory"); }
template <int ID, int N> __device__ __forceinline__ void named_bar() { asm volatile("bar.sync %0, %1;" ::"n"(ID), "n"(N) : "memory"); }

__device__ __forceinline__ float bf_lo(uint32_t u) { return __uint_as_float(u << 16); }
__device__ __forceinline__ float bf_hi(uint32_t u) { return __uint_as_float(u & 0xffff0000u); }
__device__ __forceinline__ uint32_t pack_bf(float lo, float hi) {
    uint32_t r; asm("cvt.rn.bf16x2.f32 %0, %1, %2;" : "=r"(r) : "f"(hi), "f"(lo)); return r;
}
__device__ __forceinline__ float rbf(float v) { return __uint_as_float(pack_bf(0.f, v)); }
__device__ __forceinline__ float sqrt_f(float v) { float r; asm("sqrt.approx.f32 %0, %1;" : "=f"(r) : "f"(v)); return r; }
__device__ __forceinline__ float rcp_f(float v) { float r; asm("rcp.approx.f32 %0, %1;" : "=f"(r) : "f"(v)); return r; }
__device__ __forceinline__ float silu_f(float z) { return __fdividef(z, 1.0f + __expf(-z)); }
__device__ __forceinline__ uint32_t bsub2(uint32_t a, uint32_t b) {
    uint32_t r; asm("sub.rn.bf16x2 %0, %1, %2;" : "=r"(r) : "r"(a), "r"(b)); return r;
}
__device__ __forceinline__ uint32_t bfma2(uint32_t a, uint32_t b, uint32_t c) {
    uint32_t r; asm("fma.rn.bf16x2 %0, %1, %2, %3;" : "=r"(r) : "r"(a), "r"(b), "r"(c)); return r;
}
__device__ __forceinline__ uint32_t norm2(uint32_t xv, float m, float rinv) {
    uint32_t t = pack_bf(bf_lo(xv) - m, bf_hi(xv) - m);
    return pack_bf(bf_lo(t) * rinv, bf_hi(t) * rinv);
}
__device__ __forceinline__ float gate1(float z) {
    float t;
    const float h = 0.5f * z;
    asm("tanh.approx.f32 %0, %1;" : "=f"(t) : "f"(h));
    return fmaf(h, t, h);
}
__device__ __forceinline__ uint32_t gate2(uint32_t xv, uint32_t mean2, float r0, float r1) {
    const uint32_t t = bsub2(xv, mean2);
    return pack_bf(gate1(bf_lo(t) * r0), gate1(bf_hi(t) * r1));
}
__device__ __forceinline__ uint32_t silu2(uint32_t z) { return pack_bf(silu_f(bf_lo(z)), silu_f(bf_hi(z))); }

__device__ __forceinline__ void stmatrix4(uint32_t addr, uint32_t r0, uint32_t r1, uint32_t r2, uint32_t r3) {
    asm volatile("stmatrix.sync.aligned.m8n8.x4.shared.b16 [%0], {%1,%2,%3,%4};"
                 ::"r"(addr), "r"(r0), "r"(r1), "r"(r2), "r"(r3));
}
__device__ __forceinline__ void stmatrix4t(uint32_t addr, uint32_t r0, uint32_t r1, uint32_t r2, uint32_t r3) {
    asm volatile("stmatrix.sync.aligned.m8n8.x4.trans.shared.b16 [%0], {%1,%2,%3,%4};"
                 ::"r"(addr), "r"(r0), "r"(r1), "r"(r2), "r"(r3));
}
__device__ __forceinline__ void ldmatrix4t(uint32_t addr, uint32_t& r0, uint32_t& r1, uint32_t& r2, uint32_t& r3) {
    asm volatile("ldmatrix.sync.aligned.m8n8.x4.trans.shared.b16 {%0,%1,%2,%3}, [%4];"
                 : "=r"(r0), "=r"(r1), "=r"(r2), "=r"(r3) : "r"(addr));
}

__device__ __forceinline__ void wg_fence() { asm volatile("wgmma.fence.sync.aligned;" ::: "memory"); }
__device__ __forceinline__ void wg_commit() { asm volatile("wgmma.commit_group.sync.aligned;" ::: "memory"); }
template <int N> __device__ __forceinline__ void wg_wait() { asm volatile("wgmma.wait_group.sync.aligned %0;" ::"n"(N) : "memory"); }

__host__ __device__ constexpr uint32_t desc_lo(uint32_t addr, uint32_t lbo) { return ((addr & 0x3FFFF) >> 4) | ((lbo >> 4) << 16); }
#define DESC_HI "0x40000040"

#define R8(a, o) "+f"(a[(o) + 0]), "+f"(a[(o) + 1]), "+f"(a[(o) + 2]), "+f"(a[(o) + 3]), \
                 "+f"(a[(o) + 4]), "+f"(a[(o) + 5]), "+f"(a[(o) + 6]), "+f"(a[(o) + 7])
#define R64(a, o) R8(a, (o) + 0), R8(a, (o) + 8), R8(a, (o) + 16), R8(a, (o) + 24), \
                  R8(a, (o) + 32), R8(a, (o) + 40), R8(a, (o) + 48), R8(a, (o) + 56)

template <int O, int TA>
__device__ __forceinline__ void wgmma128(float (&a)[128], uint32_t da, uint32_t db, int scale_d) {
    asm volatile(
        "{\n.reg .pred p;\n.reg .b64 da, db;\nsetp.ne.b32 p, %66, 0;\n"
        "mov.b64 da, {%64, " DESC_HI "};\nmov.b64 db, {%65, " DESC_HI "};\n"
        "wgmma.mma_async.sync.aligned.m64n128k16.f32.bf16.bf16 "
        "{%0,%1,%2,%3,%4,%5,%6,%7,%8,%9,%10,%11,%12,%13,%14,%15,"
        "%16,%17,%18,%19,%20,%21,%22,%23,%24,%25,%26,%27,%28,%29,%30,%31,"
        "%32,%33,%34,%35,%36,%37,%38,%39,%40,%41,%42,%43,%44,%45,%46,%47,"
        "%48,%49,%50,%51,%52,%53,%54,%55,%56,%57,%58,%59,%60,%61,%62,%63},"
        "da, db, p, 1, 1, %67, 0;\n}"
        : R64(a, O)
        : "r"(da), "r"(db), "r"(scale_d), "n"(TA));
}
template <int O>
__device__ __forceinline__ void wgmma128_rs(float (&a)[128], const uint32_t* f, uint32_t db) {
    asm volatile(
        "{\n.reg .b64 db;\nmov.b64 db, {%68, 8};\n"
        "wgmma.mma_async.sync.aligned.m64n128k16.f32.bf16.bf16 "
        "{%0,%1,%2,%3,%4,%5,%6,%7,%8,%9,%10,%11,%12,%13,%14,%15,"
        "%16,%17,%18,%19,%20,%21,%22,%23,%24,%25,%26,%27,%28,%29,%30,%31,"
        "%32,%33,%34,%35,%36,%37,%38,%39,%40,%41,%42,%43,%44,%45,%46,%47,"
        "%48,%49,%50,%51,%52,%53,%54,%55,%56,%57,%58,%59,%60,%61,%62,%63},"
        "{%64, %65, %66, %67}, db, 1, 1, 1, 0;\n}"
        : R64(a, O)
        : "r"(f[0]), "r"(f[1]), "r"(f[2]), "r"(f[3]), "r"(db));
}
template <int O>
__device__ __forceinline__ void fence_regs64(float (&a)[128]) {
    asm volatile("" : R64(a, O)::"memory");
}

struct Params {
    const __nv_bfloat16* x;
    const __nv_bfloat16* dre;
    const __nv_bfloat16* dim;
    const __nv_bfloat16* wr;
    const __nv_bfloat16* wg;
    const __nv_bfloat16* wu;
    const __nv_bfloat16* wd;
    uint32_t zero;
#define AB g_ab
};

__device__ __forceinline__ float warp_sum(float v) {
#pragma unroll
    for (int o = 16; o; o >>= 1) v += __shfl_xor_sync(0xffffffffu, v, o);
    return v;
}
__device__ __forceinline__ void fma8(float* acc, const uint4& w, float s) {
    acc[0] += s * bf_lo(w.x); acc[1] += s * bf_hi(w.x); acc[2] += s * bf_lo(w.y); acc[3] += s * bf_hi(w.y);
    acc[4] += s * bf_lo(w.z); acc[5] += s * bf_hi(w.z); acc[6] += s * bf_lo(w.w); acc[7] += s * bf_hi(w.w);
}
__device__ __forceinline__ int POS(int t) { return (t & ~15) | ((t & 6) << 1) | ((t & 8) >> 2) | (t & 1); }
__host__ __device__ constexpr int PSLOT(int j) { return j < 4 ? j : (j & 1) + ((j & 2) ? 0 : 4); }
__host__ __device__ constexpr int PPAR(int j) { return j < 4 ? 0 : ((j >> 2) ^ (j >> 1) ^ 1) & 1; }
__host__ __device__ constexpr int DSLOT(int it) { return (it & 3) + 2; }
__device__ __forceinline__ int SREC(int t) { return (t & ~15) | ((t & 3) << 2) | ((t >> 2) & 3); }
__device__ __forceinline__ int KO(int cl) { return ((cl & 1) << 1) | (cl >> 1); }

__global__ void __cluster_dims__(2, 1, 1) __launch_bounds__(NTHREADS, 1)
fnet_fused_kernel(const __grid_constant__ CUtensorMap tm_x, const __grid_constant__ CUtensorMap tm_dre,
                  const __grid_constant__ CUtensorMap tm_dim, const __grid_constant__ CUtensorMap tm_cre,
                  const __grid_constant__ CUtensorMap tm_cim, const __grid_constant__ CUtensorMap tm_out,
                  const __grid_constant__ CUtensorMap tm_x64,
                  const Params P) {
    extern __shared__ __align__(1024) uint8_t smem[];
    const unsigned long long tstart = clock64();
    const uint32_t sb = smem_u32(smem);
    const int tid = threadIdx.x, lane = tid & 31;
    const int warp = __shfl_sync(0xffffffffu, tid >> 5, 0);
    const int pr = blockIdx.x >> 1, p7 = ((pr - 36) * 37) >> 8;
    const int c = blockIdx.x & 1;
    const int gi = pr < 4 ? 7 : pr < 36 ? 2 * ((pr - 4) & 7) + (((pr - 4) >> 2) & 1) : 2 * (pr - 36 - 7 * p7) + 1 + (pr - 36 - 7 * p7 > 2);
    const int g = gi & 7;
    const int r = (gi >> 3) * 4 + (pr < 4 ? pr : pr < 36 ? (pr - 4) >> 3 : p7);
#define BLK(n) ((n) - ((n) <= g))
    const int grp = 2 * r + c;
    const int b = g * 16 + grp;
    const uint32_t bar0 = sb + OFF_BAR;
    const uint32_t zero = P.zero;
#define BAR(i) (bar0 + 8u * (i))
#define XBAR(i) (sb + OFF_XB + 64 + 8u * (i))
#define CLUSTER_ARRIVE() asm volatile("barrier.cluster.arrive.relaxed.aligned;" ::: "memory")
#define CLUSTER_WAIT() asm volatile("barrier.cluster.wait.aligned;" ::: "memory")
    if ((sb & 0xffffffu) != SB0) return;

#define LOAD0(it) do { \
            mbar_expect_tx(BAR(B_FS + DSLOT(it)), SLOT); tma_2d(sb + OFF_S + DSLOT(it) * SLOT, tmD, (it) * 64, r * 128, BAR(B_FS + DSLOT(it))); \
            mbar_expect_tx(BAR(B_FL + (it)), SLOT); tma_2d(sb + OFF_L + (it) * SLOT, &tm_x, (it) * 64, g * 256, BAR(B_FL + (it))); \
            mbar_expect_tx(BAR(B_FL + 4 + (it)), SLOT); tma_2d(sb + OFF_L + (4 + (it)) * SLOT, &tm_x, (it) * 64, g * 256 + 128, BAR(B_FL + 4 + (it))); \
        } while (0)
    if (warp == 13) {
        if (elect_one()) {
            const CUtensorMap* tmD = c ? &tm_dim : &tm_dre;
            prefetch_tmap(&tm_x);
            mbar_init(BAR(B_FS + 2), 1); mbar_init(BAR(B_FL), 1); mbar_init(BAR(B_FL + 4), 1);
            asm volatile("fence.mbarrier_init.release.cluster;" ::: "memory");
            LOAD0(0);
        }
        __syncwarp();
    }
    if (warp == 12) {
        if (elect_one()) {
#pragma unroll
            for (int i = 1; i < 4; i++) { mbar_init(BAR(B_FS + 2 + i), 1); mbar_init(BAR(B_FL + i), 1); mbar_init(BAR(B_FL + 4 + i), 1); }
#pragma unroll
            for (int i = 0; i < 4; i++) mbar_init(XBAR(i), 1);
            asm volatile("fence.mbarrier_init.release.cluster;" ::: "memory");
        }
        __syncwarp();
    }
    if (warp == 14) {
        if (elect_one()) {
#pragma unroll
            for (int i = 0; i < 8; i++) { mbar_init(BAR(B_EL + i), 1); mbar_init(XBAR(4 + i), 1); if (i < 6) mbar_init(BAR(B_ES + i), 2); }
            asm volatile("fence.mbarrier_init.release.cluster;" ::: "memory");
        }
        __syncwarp();
    }
    if (warp == 15) {
        if (elect_one()) {
            mbar_init(BAR(B_FS), 1); mbar_init(BAR(B_FS + 1), 1);
#pragma unroll
            for (int i = B_SRD; i < B_COUNT; i++) mbar_init(BAR(i), i == B_GO ? 2 : i == B_STATS || i == B_LST ? 4 : 1);
#pragma unroll
            for (int i = 0; i < 4; i++) mbar_expect_tx(BAR(B_RECV + i), SLOT / 2);
            mbar_expect_tx(BAR(B_PEER), 1024); mbar_expect_tx(BAR(B_H), 128);
            asm volatile("fence.mbarrier_init.release.cluster;" ::: "memory");
        }
        __syncwarp();
    }
    CLUSTER_ARRIVE();

#define GATHER(ptr, cnt, valid) do { int n = 0; bool ok; _Pragma("unroll 1") do { ok = true; \
                _Pragma("unroll") for (int i = 0; i < (cnt); i++) { f[i] = ld_relaxed128((ptr) + i * 32); ok = ok && (valid); } \
                if (__all_sync(0xffffffffu, ok)) break; \
                __nanosleep(GSL); \
            } while (++n < SPIN_LIMIT); } while (0)
    if (warp >= 8 && warp < 12) {
        asm volatile("setmaxnreg.dec.sync.aligned.u32 %0;" ::"n"(512 - PROD_REGS - 2 * CONS_REGS));
        const int aw = warp - 8, mt = tid - 256;
        unsigned ep;
        {
            const uint8_t* rp = smem + OFF_S + aw * 2048 + lane * 16;
            const __nv_bfloat16* dp = at(c ? P.dim : P.dre, (r * 128 + g * 16 + aw * 4) * D_ * 2);
            float wf[32], sw = 0.f;
#pragma unroll
            for (int i = 0; i < 4; i++) {
                const uint4 w = __ldg(reinterpret_cast<const uint4*>(at(P.wr, lane * 16) + i * 256));
                const uint32_t wv[4] = {w.x, w.y, w.z, w.w};
#pragma unroll
                for (int e = 0; e < 4; e++) { wf[8 * i + 2 * e] = bf_lo(wv[e]); wf[8 * i + 2 * e + 1] = bf_hi(wv[e]); sw = (sw + bf_lo(wv[e])) + bf_hi(wv[e]); }
            }
            ep = load_epoch(b);
            sw = warp_sum(sw);
            CLUSTER_WAIT();
            float x0[4] = {}, s1[4] = {}, s2[4] = {}, sx[4] = {}, sd[4] = {};
#define PUSH(a, v) do { a[0] = a[1]; a[1] = a[2]; a[2] = a[3]; a[3] = v; } while (0)
#pragma unroll 1
            for (int k = 0; k < 4; k++) {
                mbar_wait(XBAR(k), 0);
                uint4 v[4];
#pragma unroll
                for (int i = 0; i < 4; i++) v[i] = *reinterpret_cast<const uint4*>(rp + k * 8192 + i * 512);
                uint32_t sh = v[0].x << 16;
                float a1s = 0.f, a2s = 0.f, axs = 0.f;
#pragma unroll
                for (int i = 0; i < 4; i++) {
                    sh = __shfl_sync(0xffffffffu, sh | (__float_as_uint(axs) & zero), 0);
                    const uint32_t xv[4] = {v[i].x, v[i].y, v[i].z, v[i].w};
#pragma unroll
                    for (int e = 0; e < 4; e++) {
                        const float a0 = bf_lo(xv[e]) - __uint_as_float(sh), a1 = bf_hi(xv[e]) - __uint_as_float(sh);
                        a1s += a0 + a1;
                        a2s = fmaf(a0, a0, fmaf(a1, a1, a2s));
                        axs = fmaf(a0, wf[8 * i + 2 * e], fmaf(a1, wf[8 * i + 2 * e + 1], axs));
                    }
                }
                PUSH(x0, __uint_as_float(sh)); PUSH(s1, a1s); PUSH(s2, a2s); PUSH(sx, axs);
                fence_async_smem();
                __syncwarp();
                if (elect_one()) {
                    const uint32_t db = XBAR(k == 3 ? 8 + aw : 4 + aw);
                    if (k == 0 || k == 3) mbar_expect_tx(db, k ? 2048 : 6144);
                    bulk_g2s(sb + OFF_S + k * 8192 + aw * 2048, dp + k * D_, 2048, db);
                }
            }
#define FOLD4(a) do { const bool u16 = lane & 16, u8 = lane & 8; \
                float p0 = (u16 ? a[2] : a[0]) + __shfl_xor_sync(0xffffffffu, u16 ? a[0] : a[2], 16); \
                float p1 = (u16 ? a[3] : a[1]) + __shfl_xor_sync(0xffffffffu, u16 ? a[1] : a[3], 16); \
                a[0] = (u8 ? p1 : p0) + __shfl_xor_sync(0xffffffffu, u8 ? p0 : p1, 8); \
                _Pragma("unroll") for (int o = 4; o; o >>= 1) a[0] += __shfl_xor_sync(0xffffffffu, a[0], o); } while (0)
#pragma unroll 1
            for (int k = 0; k < 4; k++) {
                mbar_wait(XBAR(k == 3 ? 8 + aw : 4 + aw), 0);
                float run = 0.f;
#pragma unroll
                for (int i = 0; i < 4; i++) {
                    const uint4 v = *reinterpret_cast<const uint4*>(rp + k * 8192 + i * 512);
                    const uint32_t dv[4] = {v.x, v.y, v.z, v.w};
#pragma unroll
                    for (int e = 0; e < 4; e++) run += bf_lo(dv[e]) + bf_hi(dv[e]);
                }
                PUSH(sd, run);
            }
            named_bar<4, 128>();
            if (mt < 12) asm volatile("mbarrier.inval.shared::cta.b64 [%0];" ::"r"(XBAR(mt)) : "memory");
            FOLD4(sd); FOLD4(s1); FOLD4(s2); FOLD4(sx);
            const float nb = __shfl_down_sync(0xffffffffu, sd[0], 8);
            if ((lane & 15) == 0)
                st_relaxed128(at(g_rs, (grp * 64 + g * 8 + aw * 2 + (lane >> 4)) * 16), make_uint4(__float_as_uint(sd[0]), ep, __float_as_uint(nb), ep));
            if (mt == 0) PROF_T(6);
            const int rr = lane >> 3;
            const float c0 = rr == 0 ? x0[0] : rr == 1 ? x0[1] : rr == 2 ? x0[2] : x0[3];
            const float dm = s1[0] * (1.0f / D_);
            const float mb = rbf(c0 + dm);
            const float rinv = rcp_f(rbf(sqrt_f(rbf(rbf(fmaxf(s2[0] * (1.0f / D_) - dm * dm, 0.f)) + 1e-5f))));
            if ((lane & 7) == 0) st_relaxed128(at(g_stat, (b * 16 + aw * 4 + rr) * 16), make_uint4(__float_as_uint(mb), __float_as_uint(rinv), ep, 0));
            unsigned u = __bfloat16_as_ushort(__float2bfloat16_rn((sx[0] + (c0 - mb) * sw) * rinv));
            u = (u & 0x8000u) ? (~u & 0xffffu) : (u | 0x8000u);
            u = (u << 16) | (0xffffu - (unsigned)(b * 16 + rr * 4 + aw));
            u = __reduce_max_sync(0xffffffffu, u);
            if (lane == 0) { *reinterpret_cast<unsigned*>(smem + OFF_XB + aw * 4) = u; mbar_arrive(BAR(B_LST)); }
            if (mt == 0) PROF_T(2);
            uint4 f[4];
            if (aw < 2) {
                const int t = SREC(aw * 128 + lane);
                GATHER(at(g_stat, (g * 256 + aw * 128 + lane) * 16), 4, f[i].z == ep);
#pragma unroll
                for (int i = 0; i < 4; i++) {
                    *reinterpret_cast<uint32_t*>(smem + OFF_RSTD + (POS(t) + i * 32) * 4) = f[i].y;
                    *reinterpret_cast<uint16_t*>(smem + OFF_MEAN + (POS(t) + i * 32) * 2) = (uint16_t)(f[i].x >> 16);
                }
            } else {
                const int e2 = (aw - 2) * 32 + lane;
                GATHER(at(g_rs, (grp * 64 + e2) * 16), 1, f[i].y == ep && f[i].w == ep);
#pragma unroll
                for (int i = 0; i < 2; i++) {
                    const float v = __uint_as_float(i ? f[0].z : f[0].x);
                    const float hi = rbf(v), mid = rbf(v - hi), lo = v - hi - mid;
                    *reinterpret_cast<uint4*>(smem + OFF_RS + (e2 * 2 + i) * 16) = make_uint4(pack_bf(hi, mid), pack_bf(lo, 0.f), 0, 0);
                }
            }
            fence_async_smem();
            __syncwarp();
            if (lane == 0) mbar_arrive(BAR(B_STATS));
            if (mt == 127) PROF_T(9);
        }
        const bool moe = pr < 28 || pr >= 36;
        const int pair = pr < 28 ? pr : pr - 8;
        if (moe) {
            const uint64_t pol = policy_evict_first();
            const __nv_bfloat16* wp = at((aw & 1) ? P.wu : P.wg, ((c * 512 + (aw >> 1) * 256 + (lane >> 3) * 8) * F_ + pair * 64 + (lane & 7) * 8) * 2);
            uint4 b0[8], b1[8];
#define FILL(buf, str) do { _Pragma("unroll") for (int q = 0; q < 8; q++) buf[q] = ldg_stream(wp + q * (str), pol); } while (0)
#define PAUSE() do { if (mbar_test(BAR(B_QUIET), 0)) mbar_wait_sleep(BAR(B_GO), 0); } while (0)
#define FILLO(buf, row) do { _Pragma("unroll") for (int q = 0; q < 8; q++) buf[q] = ldg_stream_ord(wp + ((row) + q) * F_, pol); } while (0)
            FILLO(b0, 0);
            mbar_wait(BAR(B_SEL), 0);
            uint4 xn;
            {
                const int sel = ~*reinterpret_cast<volatile unsigned*>(smem + OFF_SEL) & (S_ - 1);
                xn = __ldg(reinterpret_cast<const uint4*>(at(P.x, (sel * D_ + c * 512 + (aw >> 1) * 256 + (lane & 7) * 32 + (lane >> 3) * 8) * 2)));
                uint4 f[1];
                GATHER(at(g_stat, SREC(sel) * 16), 1, f[i].z == ep);
                FILLO(b1, 32);
                PAUSE();
                const float m = __uint_as_float(f[0].x), ri = __uint_as_float(f[0].y);
                xn = make_uint4(norm2(xn.x, m, ri), norm2(xn.y, m, ri), norm2(xn.z, m, ri), norm2(xn.w, m, ri));
            }
            float ag[8];
#pragma unroll
            for (int i = 0; i < 8; i++) ag[i] = 0.f;
#define ROUND(cur, nxt, rd) do { \
                PAUSE(); \
                if (lane == 0) TRACE(192 + aw * 12 + (rd)); \
                if ((rd) == 7) wp = at(P.wd - 16 * D_, ((pair * 64 + (lane >> 4) * 8) * D_ + c * 512 + aw * 128 + (lane & 15) * 8) * 2); \
                wp = at(wp, ((rd) < 7 ? 64 * F_ : 32 * D_) + (cur[7].x & zero)); \
                if ((rd) & 7) { if ((rd) < 7) FILL(nxt, F_); else if ((rd) < 11) FILL(nxt, D_); } \
                _Pragma("unroll") for (int q = 0; q < 8; q += 2) { \
                    const uint32_t xw = __shfl_sync(0xffffffffu, q == 0 ? xn.x : q == 2 ? xn.y : q == 4 ? xn.z : xn.w, (lane & 24) | ((rd) & 7)); \
                    fma8(ag, cur[q], bf_lo(xw)); \
                    fma8(ag, cur[q + 1], bf_hi(xw)); \
                    if (q < 6) yield(ag[7], zero); \
                } } while (0)
#pragma unroll 1
            for (int rd = 0; rd < 12; rd += 2) {
                ROUND(b0, b1, rd);
                ROUND(b1, b0, rd + 1);
                if (rd == 6 || rd == 10) {
#pragma unroll
                    for (int i = 0; i < 8; i++) ag[i] += __shfl_xor_sync(0xffffffffu, ag[i], 16);
                }
                if (rd == 6) {
#pragma unroll
                    for (int i = 0; i < 8; i++) ag[i] += __shfl_xor_sync(0xffffffffu, ag[i], 8);
                    if (lane < 8) {
                        const uint32_t dst = mapa(sb + OFF_XB + (c * 4 + aw) * 128 + (lane & 3) * 32, lane >> 2), pb = mapa(BAR(B_PEER), lane >> 2);
                        st_async4(dst, __float_as_uint(ag[0]), __float_as_uint(ag[1]), __float_as_uint(ag[2]), __float_as_uint(ag[3]), pb);
                        st_async4(dst + 16, __float_as_uint(ag[4]), __float_as_uint(ag[5]), __float_as_uint(ag[6]), __float_as_uint(ag[7]), pb);
                    }
                    __syncwarp();
                    wp += 16 * D_; FILL(b1, D_); wp -= 16 * D_;
                    if (aw == 3) {
                        mbar_wait_cluster(BAR(B_PEER), 0);
                        const float* ps = reinterpret_cast<const float*>(smem + OFF_XB) + lane;
                        const float go = (ps[0] + ps[64]) + (ps[128] + ps[192]), uo = (ps[32] + ps[96]) + (ps[160] + ps[224]);
                        const float h = rbf(silu_f(rbf(go))) * rbf(uo), ho = __shfl_xor_sync(0xffffffffu, h, 1);
                        asm volatile("st.async.weak.shared::cluster.mbarrier::complete_tx::bytes.b32 [%0], %1, [%2];"
                                     ::"r"(mapa(sb + OFF_H + c * 64 + (lane >> 1) * 4, lane & 1)), "r"((lane & 1) ? pack_bf(ho, h) : pack_bf(h, ho)),
                                       "r"(mapa(BAR(B_H), lane & 1)) : "memory");
                    }
                    mbar_wait_cluster(BAR(B_H), 0);
                    xn = *reinterpret_cast<const uint4*>(smem + OFF_H + (lane & 3) * 32 + (lane >> 4) * 16);
#pragma unroll
                    for (int i = 0; i < 8; i++) ag[i] = 0.f;
                    if (mt == 0) PROF_T(10);
                }
            }
            const int hi = lane >> 4;
            st_relaxed128(at(g_part, pair * 4096 + (c * 8 + aw * 2 + ((lane >> 3) & 1)) * 256 + hi * 128 + (lane & 7) * 16),
                          make_uint4((__float_as_uint(hi ? ag[4] : ag[0]) & ~15u) | (ep & 15u), __float_as_uint(hi ? ag[5] : ag[1]),
                                     __float_as_uint(hi ? ag[6] : ag[2]), __float_as_uint(hi ? ag[7] : ag[3])));
            if (mt == 0) PROF_T(11);
        } else {
            mbar_wait_sleep(BAR(B_SEL), 0);
        }
        const int sel = ~*reinterpret_cast<volatile unsigned*>(smem + OFF_SEL) & (S_ - 1);
        if ((sel >> 8) == g) {
            const int col = (lane & 7) * 8 + ((lane >> 3) & 1) * 4;
            const uint2 xv = __ldg(reinterpret_cast<const uint2*>(at(P.x, (sel * D_ + grp * 64 + col) * 2)));
            uint4 f[1];
            GATHER(at(g_stat, SREC(sel) * 16), 1, f[i].z == ep);
            const uint4 rec = f[0];
            const uint4* src = at(g_part, (aw * 14 + (lane >> 4)) * 4096 + grp * 256 + (lane & 15) * 16);
            if (!moe) {
                int n = 0;
                while (((ld_relaxed(src) ^ ep) & 15u) != 0 && ++n < SPIN_LIMIT) __nanosleep(500);
            }
            uint4 t[7];
            int n = 0;
            bool ok;
            do {
                ok = true;
#pragma unroll
                for (int u = 0; u < 7; u++) { t[u] = ld_relaxed128(src + u * 512); ok = ok && ((t[u].x ^ ep) & 15u) == 0; }
            } while (!__all_sync(0xffffffffu, ok) && ++n < SPIN_LIMIT);
            float4 a = make_float4(0.f, 0.f, 0.f, 0.f);
#pragma unroll
            for (int u = 0; u < 7; u++) {
                a.x += __uint_as_float(t[u].x & ~15u); a.y += __uint_as_float(t[u].y); a.z += __uint_as_float(t[u].z); a.w += __uint_as_float(t[u].w);
            }
            a.x += __shfl_xor_sync(0xffffffffu, a.x, 16); a.y += __shfl_xor_sync(0xffffffffu, a.y, 16);
            a.z += __shfl_xor_sync(0xffffffffu, a.z, 16); a.w += __shfl_xor_sync(0xffffffffu, a.w, 16);
            float4* park = reinterpret_cast<float4*>(smem + OFF_XB) + (lane & 15);
            if (lane < 16) park[aw * 16] = a;
            named_bar<4, 128>();
            if (aw == 0) {
                const float4 p1 = park[16], p2 = park[32], p3 = park[48];
                a.x = (a.x + p1.x) + (p2.x + p3.x); a.y = (a.y + p1.y) + (p2.y + p3.y);
                a.z = (a.z + p1.z) + (p2.z + p3.z); a.w = (a.w + p1.w) + (p2.w + p3.w);
                unsigned u = *reinterpret_cast<volatile unsigned*>(smem + OFF_SEL) >> 16;
                u = (u & 0x8000u) ? (u & 0x7fffu) : (~u & 0xffffu);
                const float sg = rbf(__fdividef(1.0f, 1.0f + __expf(-__uint_as_float(u << 16))));
                const float m = __uint_as_float(rec.x), ri = __uint_as_float(rec.y);
                const uint32_t n0 = norm2(xv.x, m, ri), n1 = norm2(xv.y, m, ri);
                uint2 o;
                o.x = silu2(pack_bf(bf_lo(n0) + rbf(rbf(a.x) * sg), bf_hi(n0) + rbf(rbf(a.y) * sg)));
                o.y = silu2(pack_bf(bf_lo(n1) + rbf(rbf(a.z) * sg), bf_hi(n1) + rbf(rbf(a.w) * sg)));
                if (lane < 16) *reinterpret_cast<uint2*>(smem + OFF_H + col * 2) = o;
                __syncwarp();
                if (lane == 0) { mbar_arrive(BAR(B_UPD)); PROF_T(12); }
            }
        }
    } else if (warp < 8) {
        asm volatile("setmaxnreg.inc.sync.aligned.u32 %0;" ::"n"(CONS_REGS));
        CLUSTER_WAIT();
        const int wg = warp >> 2, wq = warp & 3;
        const int wt = tid & 127;
        float acc[128];
        const uint32_t fL = BAR(B_FL + 4 * wg), eL = BAR(B_EL + 4 * wg);
        const uint32_t dL = desc_lo(SB0 + OFF_L, 16) + wg * 4096;
        constexpr uint32_t dS = desc_lo(SB0 + OFF_S, 16);
        constexpr uint32_t SL = SLOT >> 4;
#define RELEASE(ls, ss) do { if (wt == 0) { mbar_arrive(eL + 8u * (ls)); mbar_arrive(BAR(B_ES + (ss))); } } while (0)
#define WAIT_FULL(ls, lph, ss, sph) do { mbar_wait(BAR(B_FS + (ss)), sph); mbar_wait(fL + 8u * (ls), lph); } while (0)
#define TURN() do { if (wg) named_bar<6, 256>(); else named_bar<5, 256>(); } while (0)
#define PASS() do { if (wg) named_arrive<5, 256>(); else named_arrive<6, 256>(); } while (0)
#define WG_BAR() do { if (wg) named_bar<2, 128>(); else named_bar<1, 128>(); } while (0)
        if (wg == 1) PASS();

#define MMA1_H(O, s, first) do { _Pragma("unroll") for (int kk = 0; kk < 4; kk++) \
            wgmma128<O, 0>(acc, dL + (s) * SL + kk * 2 + (O) * 8, dS + DSLOT(s) * SL + kk * 2, !((first) && kk == 0)); } while (0)
#define WAIT1(s, ph) WAIT_FULL(s, ph, DSLOT(s), ph)
#define PROBE(ls, lph, ss, sph) (mbar_test(BAR(B_FS + (ss)), sph) & mbar_test(fL + 8u * (ls), lph))
#define REL1(s) RELEASE(s, DSLOT(s))
#pragma unroll 1
        for (int it = 0; it < 12; it++) {
            const int s = it & 3;
            const bool ok = PROBE(s, (it >> 2) & 1, DSLOT(s), (it >> 2) & 1);
            if (it) { wg_wait<0>(); REL1((s + 3) & 3); }
            if (!ok) WAIT1(s, (it >> 2) & 1);
            TURN();
            wg_fence(); MMA1_H(0, s, it == 0); MMA1_H(64, s, it == 0); wg_commit();
            PASS();
            if (it == 0 && tid == 0) PROF_T(16);
        }
        TS(12);
        float rs[4] = {};
        uint32_t nm[8] = {};
#define GET_STATS() do { mbar_wait(BAR(B_STATS), 0); \
            const int p0 = POS(wg * 128 + wq * 16 + (lane >> 2));                   \
            const uint32_t msk = (lane & 3) == 0 ? 0xffffffffu : (lane & 3) == 1 ? 0x0000ffffu : 0u; \
            _Pragma("unroll") for (int i = 0; i < 4; i++) { \
                const int p = p0 + (i & 1) * 2 + (i >> 1) * 64; \
                rs[i] = *reinterpret_cast<const float*>(smem + OFF_RSTD + p * 4); \
                const uint32_t m = *reinterpret_cast<const uint16_t*>(smem + OFF_MEAN + p * 2) ^ 0x8000u; \
                nm[i + (i & 2)] = (m | (m << 16)) & msk; \
            } } while (0)
        const bool early = wg || __all_sync(0xffffffffu, mbar_test(BAR(B_STATS), 0));
        if (early && !wg) GET_STATS();
        WAIT1(0, 1);
        TS(13);
        wg_wait<0>(); REL1(3);
        if (wg) GET_STATS();
        TS(14);
        TURN();
        wg_fence();
        MMA1_H(0, 0, false);
        if (tid == 0) { mbar_arrive(BAR(B_QUIET)); PROF_T(15); }
        WAIT1(1, 1); wg_fence(); MMA1_H(0, 1, false);
        WAIT1(2, 1); wg_fence(); MMA1_H(0, 2, false); wg_commit();
        if (!early) GET_STATS();
        asm volatile("" : "+r"(nm[0]), "+r"(nm[1]), "+r"(nm[2]), "+r"(nm[3]), "+r"(nm[4]), "+r"(nm[5]), "+r"(nm[6]), "+r"(nm[7])::"memory");
        wg_fence();
        wgmma128_rs<64>(acc, nm + 4, (SB0 + OFF_RS) >> 4);
        wgmma128_rs<0>(acc, nm, (SB0 + OFF_RS) >> 4);
        WAIT1(3, 1); wg_fence(); MMA1_H(0, 3, false); wg_commit();
        PASS();
        const int mrow = wq * 16 + ((lane >> 3) & 1) * 8 + (lane & 7);
#define EPI1(O, slot, FREE) do { const uint32_t dst = sb + OFF_S + (slot) * SLOT + mrow * 128; \
            uint32_t pk[32]; \
            _Pragma("unroll") for (int i = 0; i < 32; i += 4) { \
                _Pragma("unroll") for (int k = 0; k < 4; k++) \
                    pk[i + k] = pack_bf(acc[(O) + 2 * (i + k)] * rs[(O) / 32 + (k & 1)], acc[(O) + 2 * (i + k) + 1] * rs[(O) / 32 + (k & 1)]); \
                if (i == EF) { FREE; } \
                if (i >= EF) { _Pragma("unroll") for (int v = (i == EF ? 0 : i); v <= i; v += 4) \
                    stmatrix4(dst + ((v >> 4) ^ c ^ 1) * 8192 + ((((v >> 1) & 7) + (lane >> 4)) ^ (lane & 7)) * 16, pk[v], pk[v + 1], pk[v + 2], pk[v + 3]); } } \
            WG_BAR(); \
            if (wt == 0) mbar_arrive(BAR(B_FS + (slot))); } while (0)
        TS(15);
        wg_wait<0>();
        fence_regs64<0>(acc);
        TS(16);
        {
            constexpr int EF = 0;
            EPI1(0, wg, if (wg) mbar_wait(BAR(B_FS), 0));
        }
        TS(17);
        TURN();
        wg_fence();
        MMA1_H(64, 0, false); wg_commit();
        MMA1_H(64, 1, false); wg_commit();
        MMA1_H(64, 2, false); wg_commit();
        wg_wait<2>(); REL1(0);
        MMA1_H(64, 3, false); wg_commit();
        PASS();
        TS(18);
        wg_wait<2>(); REL1(1);
        mbar_wait(BAR(B_FS), 0); mbar_wait(BAR(B_FS + 1), 0); fence_async_smem();
        wg_wait<1>(); REL1(2);
        wg_wait<0>(); REL1(3);
        fence_regs64<64>(acc);
        TS(19);
        {
            constexpr int EF = 16;
            EPI1(64, 2 + wg, mbar_wait(BAR(B_ES + 2 + wg), 1));
        }
        TS(20);

        float ac2[128];
#define MMA2_H(O, ls, ss, first) do { _Pragma("unroll") for (int kk = 0; kk < 4; kk++) \
            wgmma128<O, 1>(ac2, dS + (ss) * SL + kk * 128 + (O) * 8, dL + (ls) * SL + kk * 2, !((first) && kk == 0)); } while (0)
#define WAIT2(j) WAIT_FULL((j) & 3, ((j) >> 2) & 1, PSLOT(j), PPAR(j))
#define MMA2(j) do { wg_fence(); MMA2_H(0, (j) & 3, PSLOT(j), (j) == 0); MMA2_H(64, (j) & 3, PSLOT(j), (j) == 0); wg_commit(); } while (0)
#define REL2(j) RELEASE((j) & 3, PSLOT(j))
        WAIT2(0); TURN(); MMA2(0);
        WAIT2(1); MMA2(1); PASS();
        TS(21);
        wg_wait<1>(); REL2(0);
        mbar_wait(BAR(B_FS + 2), 0); mbar_wait(BAR(B_FS + 3), 0); fence_async_smem();
        TS(22);
        {
            uint32_t l2 = 2, s2 = 2, sp = 1, lph = 0, sph = 0;
#pragma unroll 1
            for (int j = 2; j < XJ; j += 2) {
#pragma unroll
                for (int h = 0; h < 2; h++) {
                    const bool ok = PROBE(l2 + h, lph, s2 + h, sph);
                    wg_wait<0>(); RELEASE(h ? l2 : 3 - l2, h ? s2 : sp);
                    if (!ok) WAIT_FULL(l2 + h, lph, s2 + h, sph);
                    TURN();
                    wg_fence(); MMA2_H(0, l2 + h, s2 + h, false); MMA2_H(64, l2 + h, s2 + h, false); wg_commit();
                    PASS();
                    if (h == (GOJ & 1) && j == (GOJ & ~1) && wt == 0) { mbar_arrive(BAR(B_GO)); if (wg == 0) PROF_T(19); }
                }
                sp = s2 + 1; s2 = 2 * l2; sph = lph; l2 ^= 2;
                lph ^= l2 == 0;
            }
        }
        if (tid == 0) PROF_T(20);
        uint32_t gt[32];
        const uint32_t xrow = sb + OFF_S + 2 * SLOT + wg * 8192 + ((lane >> 4) * 8 + (lane & 7)) * 128 + (((2 * wq + ((lane >> 3) & 1)) ^ (lane & 7)) << 4);
        const uint32_t gsign = c ? 0x80008000u : 0u;
#define XOFF(v) (((v) >> 2) * SLOT + ((v) & 3) * 2048)
        int sel = 0;
        bool own = false;
#define PATCH() do { own = false; \
            const uint32_t v0 = *reinterpret_cast<const uint16_t*>(smem + OFF_H + (wq * 16 + (lane >> 2)) * 2) ^ gsign; \
            const uint32_t v1 = *reinterpret_cast<const uint16_t*>(smem + OFF_H + (wq * 16 + (lane >> 2)) * 2 + 16) ^ gsign; \
            const uint32_t pick = (lane & 3) != ((sel >> 1) & 3) ? 0x3210u : (sel & 1) ? 0x5410u : 0x3254u; \
            _Pragma("unroll") for (int i = 0; i < 16; i++) { \
                const uint32_t m = ((sel >> 3) & 15) == i ? pick : 0x3210u; \
                gt[2 * i] = __byte_perm(gt[2 * i], v0, m); \
                gt[2 * i + 1] = __byte_perm(gt[2 * i + 1], v1, m); \
            } } while (0)
#pragma unroll
        for (int u = 0; u < 8; u++) {
            if (u) { WAIT2(XJ + u - 1); wg_wait<0>(); REL2(XJ + u - 2); TURN(); MMA2(XJ + u - 1); PASS(); }
            uint32_t* o = &gt[4 * u];
            if (!(u & 3)) mbar_wait(BAR(B_FS + 2 + (u >> 2)), 1);
            ldmatrix4t(xrow + XOFF(u), o[0], o[1], o[2], o[3]);
            const float4 r4 = *reinterpret_cast<const float4*>(smem + OFF_RSTD + (wg * 128 + u * 16 + (lane & 3) * 4) * 4);
            const uint2 m2 = *reinterpret_cast<const uint2*>(smem + OFF_MEAN + (wg * 128 + u * 16 + (lane & 3) * 4) * 2);
            o[0] = gate2(o[0], m2.x, r4.x, r4.y) ^ gsign;
            o[1] = gate2(o[1], m2.x, r4.x, r4.y) ^ gsign;
            o[2] = gate2(o[2], m2.y, r4.z, r4.w) ^ gsign;
            o[3] = gate2(o[3], m2.y, r4.z, r4.w) ^ gsign;
            if (u == 2) {
                mbar_wait(BAR(B_SEL), 0);
                sel = ~*reinterpret_cast<volatile unsigned*>(smem + OFF_SEL) & (S_ - 1);
                own = (sel >> 7) == 2 * g + wg;
            }
            asm volatile("st.shared.v2.u32 [%0], {%1,%2};" ::"r"(sb + OFF_SEL + 16), "r"(o[0] ^ o[1]), "r"(o[2] ^ o[3]) : "memory");
        }
        if (tid == 0) PROF_T(21);
        WAIT2(27);
        wg_wait<0>(); REL2(26);
        if (own) {
            const uint32_t t0 = clock32();
            bool ok;
            while (!(ok = mbar_test(BAR(B_UPD), 0)) && clock32() - t0 < wg * 1900u) __nanosleep(50);
            if (__all_sync(0xffffffffu, ok)) PATCH();
        }
        TS(0);
        TURN();
        MMA2(27);
        WAIT2(28); wg_fence(); MMA2_H(0, 0, PSLOT(28), false); wg_commit();
        if (wg == 0) { wg_fence(); MMA2_H(64, 0, PSLOT(28), false); wg_commit(); }
        constexpr uint32_t dL0 = desc_lo(SB0 + OFF_L, 16);
        const uint32_t ct[3] = {wg ? 3u : 1u, wg ? 1u : 2u, wg ? 2u : 5u};
#define TMMA(O, i) wgmma128<O, 1>(ac2, ((i) < 8 ? dS + PSLOT(29 + ((i) >> 2)) * SL : dL0 + 6 * SL) + ((i) & 3) * 128 + (O) * 8, \
                                  dL0 + ct[(i) >> 2] * SL + ((i) & 3) * 2, 1)
#define KEEP(i) TMMA(64, i)
#pragma unroll
        for (int k = 0; k < 3; k++) {
            if (k < 2) mbar_wait(BAR(B_FS + PSLOT(29 + k)), PPAR(29 + k)); else mbar_wait(BAR(B_FL + 6), 1);
            mbar_wait(BAR(B_FL + ct[k]), k == 0 || wg == 0);
            wg_fence();
#pragma unroll
            for (int i = 4 * k; i < 4 * k + 4; i++) TMMA(0, i);
            wg_commit();
            if (k < 2) wg_wait<2>();
            if (k == 0 && tid == 0) mbar_arrive(BAR(B_EL + 3));
            if (k == 1 && tid == 0) mbar_arrive_cluster(mapa(BAR(B_RDY), c ^ 1));
        }
        TS(1);
        wg_fence();
#pragma unroll
        for (int i = 0; i < KQ; i++) KEEP(i);
        wg_commit();
        mbar_wait(BAR(B_RDY + wg), 0);
        wg_wait<1>();
        fence_regs64<0>(ac2);
        TS(2);
        wg_fence();
        {
            const uint32_t dst = mapa(sb + OFF_L + wg * 5 * SLOT + wt * 16, c ^ 1), rb = mapa(BAR(B_RECV + 2 * wg), c ^ 1);
#pragma unroll
            for (int v = 0; v < 8; v++) {
                if (KQ + v < 12) KEEP(KQ + v);
                if (KQ + v == 7) wg_commit();
                if (KQ + v == 11) { wg_commit(); if (wg == 0) PASS(); }
                st_async4(dst + v * 2048, pack_bf(ac2[8 * v + 0], ac2[8 * v + 1]), pack_bf(ac2[8 * v + 2], ac2[8 * v + 3]),
                          pack_bf(ac2[8 * v + 4], ac2[8 * v + 5]), pack_bf(ac2[8 * v + 6], ac2[8 * v + 7]), rb + (v >> 2) * 8);
            }
        }
        if (wg == 1) { wg_fence(); MMA2_H(64, 0, PSLOT(28), false); wg_commit(); }
        TS(3);
        uint32_t xr[32];
#define LDX(v) ldmatrix4t(xrow + XOFF(v), xr[4 * (v)], xr[4 * (v) + 1], xr[4 * (v) + 2], xr[4 * (v) + 3])
        if (wg == 0) {
            wg_wait<2>();
            if (wt == 0) mbar_arrive(BAR(B_EL + 1));
            wg_wait<1>();
            if (wt == 0) mbar_arrive(BAR(B_EL + 2));
        }
#pragma unroll
        for (int v = 0; v < XE; v++) LDX(v);
        if (wg == 0) {
            wg_wait<0>();
            if (wt == 0) mbar_arrive_cluster(mapa(BAR(B_RDY + 1), c ^ 1));
        }
        TS(4);
        if (own) { mbar_wait(BAR(B_UPD), 0); PATCH(); }
        TS(5);
        uint4 rv[8];
#define FETCH(v0) do { if ((v0) == 0 || (v0) == 4) mbar_wait_cluster(BAR(B_RECV + 2 * wg + (v0) / 4), 0); \
            _Pragma("unroll") for (int v = (v0); v < (v0) + 2; v++) { \
                asm volatile("ld.shared.v4.u32 {%0,%1,%2,%3}, [%4];" : "=r"(rv[v].x), "=r"(rv[v].y), "=r"(rv[v].z), "=r"(rv[v].w) \
                             : "r"(sb + OFF_L + wg * 5 * SLOT + v * 2048 + wt * 16) : "memory"); \
                if (v >= XE) LDX(v); } } while (0)
        FETCH(0);
        TS(6);
        wg_wait<0>();
        fence_regs64<64>(ac2);
        TS(7);
#pragma unroll
        for (int v0 = 0; v0 < 8; v0 += 2) {
#pragma unroll
            for (int v = v0; v < v0 + 2; v++) {
                const float* a = &ac2[64 + 8 * v];
                stmatrix4t(xrow + XOFF(v),
                           bfma2(bsub2(pack_bf(a[0], a[1]), rv[v].x), gt[4 * v + 0], xr[4 * v + 0]),
                           bfma2(bsub2(pack_bf(a[2], a[3]), rv[v].y), gt[4 * v + 1], xr[4 * v + 1]),
                           bfma2(bsub2(pack_bf(a[4], a[5]), rv[v].z), gt[4 * v + 2], xr[4 * v + 2]),
                           bfma2(bsub2(pack_bf(a[6], a[7]), rv[v].w), gt[4 * v + 3], xr[4 * v + 3]));
            }
            WG_BAR();
            if (wt == 0) mbar_arrive(eL + 4 * v0);
            if (v0 + 2 < 8) FETCH(v0 + 2);
            if (v0 == 0) TS(8);
        }
        TS(9);
    } else {
        asm volatile("setmaxnreg.dec.sync.aligned.u32 %0;" ::"n"(PROD_REGS));
#define XROWS(k) do { mbar_expect_tx(XBAR(k), 8192); bulk_g2s(sb + OFF_S + (k) * 8192, at(P.x, (b * 16 + (k) * 4) * D_ * 2), 8192, XBAR(k)); } while (0)
        if (warp == 12) {
            if (elect_one()) {
                const CUtensorMap* tmD = c ? &tm_dim : &tm_dre;
#pragma unroll 1
                for (int it = 1; it < 4; it++) {
                    while (clock32() - (uint32_t)tstart < LDEL + (it - 1) * LGAP) {}
                    LOAD0(it);
                    if (it >= X0) XROWS(it - X0);
                }
            }
            __syncwarp();
        }
        CLUSTER_WAIT();
        if (warp == 12) {
            if (elect_one()) {
                const CUtensorMap* tmD = c ? &tm_dim : &tm_dre;
#pragma unroll 1
                for (int it = 4; it < 16; it++) {
                    const int s = DSLOT(it);
                    mbar_wait(BAR(B_ES + s), ((it >> 2) & 1) ^ 1);
                    TRACE(it);
                    mbar_expect_tx(BAR(B_FS + s), SLOT);
                    tma_2d(sb + OFF_S + s * SLOT, tmD, it * 64, r * 128, BAR(B_FS + s));
                    if (it < 4 + X0) XROWS(it - X0);
                }
                const unsigned ep = load_epoch(b), e8 = ep & 0xffu;
                const uint8_t* abg = at(AB, grp * 32 * SLOT);
                const unsigned long long* fl = at(g_flag, grp * 128);
                unsigned long long rdy = ld_acquire64(fl);
                mbar_wait(BAR(B_SRD), 0);
                st_release8(at(g_flag, grp * 128 + g), e8);
                PROF_T(7);
                int j = 4;
#pragma unroll 1
                for (int cl = 0; cl < 4; cl++) {
                    if (cl) rdy = ld_acquire64(++fl);
                    fence_async_global();
#pragma unroll 1
                    for (int n = 1; n < 8; n++, j++) {
                        const int q = BLK(n), s = (j & 1) + ((j & 2) ? 0 : 4);
                        const uint32_t fb = BAR(j == 31 ? B_FL + 6 : B_FS + s);
                        if (j == 31) mbar_wait(BAR(B_EL + 6), 0); else mbar_wait(BAR(B_ES + s), ((j >> 2) ^ (j >> 1)) & 1);
                        if (j == 7) mbar_wait(BAR(B_SRD + 1), 0);
                        if (((unsigned)(rdy >> (8 * q)) & 0xffu) != e8) {
                            int m = 0;
                            do { rdy = ld_acquire64(fl); } while (((unsigned)(rdy >> (8 * q)) & 0xffu) != e8 && ++m < SPIN_LIMIT);
                            fence_async_global();
                        }
                        TRACE(16 + j);
                        mbar_expect_tx(fb, SLOT);
                        bulk_g2s(sb + (j == 31 ? OFF_L + 6 * SLOT : OFF_S + s * SLOT), at(abg, (4 * q + KO(cl)) * SLOT), SLOT, fb);
                    }
                }
                *at(g_epoch, b * 4) = ep;
            }
        } else if (warp < 15) {
            if (elect_one()) {
                const int w = warp - 13, row0 = g * 256 + w * 128;
                const CUtensorMap* tmC = c ? &tm_cim : &tm_cre;
                const uint32_t fb = BAR(B_FL + 4 * w), eb = BAR(B_EL + 4 * w), dst = sb + OFF_L + w * 4 * SLOT;
                [[maybe_unused]] unsigned long long mk = 0, mg = 0;
                int n = 0, cl = 0;
#pragma unroll 1
                for (int it = 4; it < 47 - 2 * w; it++) {
                    const int s = it & 3;
                    mbar_wait(eb + 8 * s, ((it >> 2) & 1) ^ 1);
                    TRACE(64 + w * 64 + it - 4);
                    MARK(it);
                    mbar_expect_tx(fb + 8 * s, SLOT);
                    tma_2d(dst + s * SLOT, it < 16 ? &tm_x : tmC, (it < 16 ? it : 4 * (n ? BLK(n) : g) + KO(cl)) * 64, row0, fb + 8 * s);
                    if (it == PTJ) prefetch_tmap(w ? &tm_x64 : tmC);
                    if (it == PTJ && w) prefetch_tmap(&tm_out);
                    if (it >= 16) {
                        if (it == 19) { n = 1; cl = 0; } else if (it < 19) cl++; else if (++n == 8) { n = 1; cl++; }
                    }
                }
#pragma unroll 1
                for (int i = 2 * w; i < 3; i++) {
                    const int s = w ? 1 : i ? i : 3;
                    mbar_wait(eb + 8 * s, w == 0 && i);
                    mbar_expect_tx(fb + 8 * s, SLOT);
                    tma_2d(dst + s * SLOT, tmC, (4 * BLK(5 + i) + 3) * 64, row0 ^ 128, fb + 8 * s);
                }
                if (w && (r & 3) < 2) tma_2d_prefetch(tmC, (4 * BLK(6 + (r & 1)) + 3) * 64, row0);
#pragma unroll 1
                for (int h = 0; h < 4; h++) {
                    mbar_wait(eb + 8 * h, ((w ? 7 : 9) >> h) & 1);
                    fence_async_smem();
                    tma_2d_store(&tm_out, grp * 64, row0 + h * 32, sb + OFF_S + (2 + (h >> 1)) * SLOT + w * 8192 + (h & 1) * 4096);
                    bulk_commit();
                }
                FINISH(w);
            }
        } else {
            const unsigned ep = load_epoch(b);
            uint4 f[4];
            {
                sleep_until((uint32_t)tstart + 6000);
                const uint4* keys = at(reinterpret_cast<const uint4*>(g_key), lane * 16);
                bool mine = false;
                int n = 0;
                do {
                    f[0] = ld_relaxed128(keys); f[1] = ld_relaxed128(keys + 32);
                    if (__all_sync(0xffffffffu, f[0].y == ep && f[0].w == ep && f[1].y == ep && f[1].w == ep)) break;
                    if (!mine) {
                        mbar_wait(BAR(B_LST), 0);
                        const uint4 k = *reinterpret_cast<const uint4*>(smem + OFF_XB);
                        if (lane == 0) st_relaxed64(at(g_key, b * 8), ((unsigned long long)ep << 32) | max(max(k.x, k.y), max(k.z, k.w)));
                        mine = true;
                    }
                    __nanosleep(GSL);
                } while (++n < SPIN_LIMIT);
                const unsigned key = __reduce_max_sync(0xffffffffu, max(max(f[0].x, f[0].z), max(f[1].x, f[1].z)));
                if (lane == 0) { *reinterpret_cast<unsigned*>(smem + OFF_SEL) = key; mbar_arrive(BAR(B_SEL)); PROF_T(8); }
            }
            if (elect_one()) {
#pragma unroll 1
                for (int cl = 0; cl < 4; cl++) {
                    uint8_t* dst = at(AB, (grp * 32 + 4 * g + KO(cl)) * SLOT);
                    const uint32_t src = sb + OFF_S + cl * SLOT, chunk = cl ? 1024 : SLOT;
                    mbar_wait(BAR(B_FS + cl), 0);
                    fence_async_smem();
                    if (cl == 0) PROF_T(3);
                    uint32_t t0 = clock32() + (cl == 1 ? PDEL : 0);
#pragma unroll 1
                    for (uint32_t o = 0; o < SLOT; o += chunk) {
                        sleep_until(t0);
                        bulk_s2g(dst + o, src + o, chunk);
                        bulk_commit();
                        t0 += cl == 1 ? PGAP1 : cl == 2 ? PGAP2 : PGAP3;
                    }
                    bulk_wait<0>();
                    fence_async_global();
                    TRACE(252 + cl);
                    if (cl < 2) mbar_arrive(BAR(B_SRD + cl));
                    else {
                        mbar_wait(BAR(B_ES + cl), 0);
                        mbar_expect_tx(BAR(B_FS + cl), SLOT);
                        tma_2d(src, &tm_x64, grp * 64, g * 256 + (cl - 2) * 64, BAR(B_FS + cl));
                        tma_2d(src + 8192, &tm_x64, grp * 64, g * 256 + (cl - 2) * 64 + 128, BAR(B_FS + cl));
                    }
                    if (cl) st_release8(at(g_flag, grp * 128 + cl * 8 + g), ep & 0xffu);
                    if (cl == 1) PROF_T(5);
                    if (cl == 3) PROF_T(4);
                }
            }
        }
    }
}

typedef CUresult (*EncodeFn)(CUtensorMap*, CUtensorMapDataType, cuuint32_t, void*, const cuuint64_t*, const cuuint64_t*,
                             const cuuint32_t*, const cuuint32_t*, CUtensorMapInterleave, CUtensorMapSwizzle,
                             CUtensorMapL2promotion, CUtensorMapFloatOOBfill);

void make_map(EncodeFn fn, CUtensorMap* tm, const void* p, uint64_t rows, uint64_t cols, uint32_t box_rows) {
    cuuint64_t dims[2] = {cols, rows};
    cuuint64_t strides[1] = {cols * 2};
    cuuint32_t box[2] = {64, box_rows};
    cuuint32_t es[2] = {1, 1};
    fn(tm, CU_TENSOR_MAP_DATA_TYPE_BFLOAT16, 2, const_cast<void*>(p), dims, strides, box, es, CU_TENSOR_MAP_INTERLEAVE_NONE,
       CU_TENSOR_MAP_SWIZZLE_128B, CU_TENSOR_MAP_L2_PROMOTION_L2_128B, CU_TENSOR_MAP_FLOAT_OOB_FILL_NONE);
}

}

extern "C" void kernel_launch(void* const* d_in, const int* in_sizes, int n_in, void* d_out, int out_size) {
    (void)in_sizes; (void)n_in; (void)out_size;
    static EncodeFn fn = nullptr;
    if (!fn) {
        void* p = nullptr;
        cudaDriverEntryPointQueryResult q;
        cudaGetDriverEntryPoint("cuTensorMapEncodeTiled", &p, cudaEnableDefault, &q);
        fn = (EncodeFn)p;
        cudaFuncSetAttribute(fnet_fused_kernel, cudaFuncAttributeMaxDynamicSharedMemorySize, SMEM_BYTES);
    }
    CUtensorMap tx, tdre, tdim, tcre, tcim, tout, tx64;
    make_map(fn, &tx, d_in[0], S_, D_, 128);
    make_map(fn, &tcre, d_in[1], S_, S_, 128);
    make_map(fn, &tcim, d_in[2], S_, S_, 128);
    make_map(fn, &tdre, d_in[3], D_, D_, 128);
    make_map(fn, &tdim, d_in[4], D_, D_, 128);
    make_map(fn, &tx64, d_in[0], S_, D_, 64);
    make_map(fn, &tout, d_out, S_, D_, 32);
    Params P;
    P.x = (const __nv_bfloat16*)d_in[0];
    P.dre = (const __nv_bfloat16*)d_in[3];
    P.dim = (const __nv_bfloat16*)d_in[4];
    P.wr = (const __nv_bfloat16*)d_in[6];
    P.wg = (const __nv_bfloat16*)d_in[7];
    P.wu = (const __nv_bfloat16*)d_in[8];
    P.wd = (const __nv_bfloat16*)d_in[9];
    P.zero = 0;
    fnet_fused_kernel<<<NCTA, NTHREADS, SMEM_BYTES, cudaStreamPerThread>>>(tx, tdre, tdim, tcre, tcim, tout, tx64, P);
}
```

```cpp
#include <cuda_runtime.h>
#include <cuda_bf16.h>
#include <cuda.h>
#include <stdint.h>

#define GSL 200
#define SLEEP_NS 200
#define PDEL 1000
#define PGAP1 200
#define PGAP2 200
#define PGAP3 240
#define GOJ 2
#define LDEL 1400
#define LGAP 750
#define PTJ 10
#define X0 2
#define W0 13
#define XF 0
#define KQ 5
#define XE 2
#define PROD_REGS 32
#define CONS_REGS 184

namespace {

constexpr int S_ = 2048, D_ = 1024, F_ = 3584;
constexpr int NCTA = 128;
constexpr int XJ = 20;
constexpr uint32_t SLOT = 16384;
constexpr uint32_t OFF_L = 0;
constexpr uint32_t OFF_S = 8 * SLOT;
constexpr uint32_t OFF_RS = OFF_S + SLOT;
constexpr uint32_t OFF_BAR = 14 * SLOT;
constexpr uint32_t OFF_SEL = OFF_BAR + 360;
constexpr uint32_t OFF_RSTD = OFF_BAR + 384;
constexpr uint32_t OFF_MEAN = OFF_RSTD + 1024;
constexpr uint32_t OFF_XB = OFF_MEAN + 512;
constexpr uint32_t OFF_H = OFF_XB + 1024;
constexpr uint32_t SMEM_BYTES = OFF_H + 128;
constexpr uint32_t SB0 = 1024;
constexpr int NTHREADS = 512;
static_assert(SMEM_BYTES <= 232448, "smem");

enum { B_FS = 0, B_ES = 6, B_FL = 12, B_EL = 20, B_SRD = 28, B_RECV = 30  , B_RDY = 34, B_STATS = 36, B_LST = 37, B_UPD = 38,
       B_QUIET = 39, B_GO = 40, B_PEER = 41, B_SEL = 42, B_H = 43, B_COUNT = 44 };
static_assert(B_COUNT * 8 <= 360, "barriers");

__device__ __align__(1024) uint8_t g_ab[16u * 32u * SLOT];
__device__ __align__(128) uint4 g_part[56 * (D_ / 4)];
__device__ __align__(128) uint4 g_stat[S_];
__device__ __align__(128) uint4 g_rs[D_];
__device__ __align__(128) unsigned long long g_key[NCTA];
__device__ __align__(128) unsigned long long g_flag[16 * 16];
__device__ __align__(128) unsigned g_epoch[NCTA];
#define PROF_T(i) do {} while (0)
#define TRACE(i) do {} while (0)
#define PROF_G(i) do {} while (0)
#define TS(i) do {} while (0)
#define FINISH(wg) bulk_wait_read<0>()

#define MARK(it) do {} while (0)

__device__ __forceinline__ uint32_t smem_u32(const void* p) { return (uint32_t)__cvta_generic_to_shared(p); }
__device__ __forceinline__ void mbar_init(uint32_t bar, uint32_t cnt) {
    asm volatile("mbarrier.init.shared::cta.b64 [%0], %1;" ::"r"(bar), "r"(cnt) : "memory");
}
__device__ __forceinline__ bool mbar_try(uint32_t bar, uint32_t parity) {
    uint32_t ok;
    asm volatile("{\n.reg .pred p;\nmbarrier.try_wait.parity.shared::cta.b64 p, [%1], %2;\nselp.u32 %0, 1, 0, p;\n}"
                 : "=r"(ok) : "r"(bar), "r"(parity) : "memory");
    return ok;
}
__device__ __forceinline__ bool mbar_test(uint32_t bar, uint32_t parity) {
    uint32_t ok;
    asm volatile("{\n.reg .pred p;\nmbarrier.test_wait.parity.shared::cta.b64 p, [%1], %2;\nselp.u32 %0, 1, 0, p;\n}"
                 : "=r"(ok) : "r"(bar), "r"(parity) : "memory");
    return ok;
}
__device__ __forceinline__ bool mbar_try_cluster(uint32_t bar, uint32_t parity) {
    uint32_t ok;
    asm volatile("{\n.reg .pred p;\nmbarrier.try_wait.parity.acquire.cluster.shared::cta.b64 p, [%1], %2;\nselp.u32 %0, 1, 0, p;\n}"
                 : "=r"(ok) : "r"(bar), "r"(parity) : "memory");
    return ok;
}
constexpr int SPIN_LIMIT = 1 << 20;
__device__ __forceinline__ void mbar_wait(uint32_t bar, uint32_t parity) {
    if (mbar_try(bar, parity)) return;
    int n = 0;
    while (!mbar_try(bar, parity) && ++n < SPIN_LIMIT) {}
}
__device__ __forceinline__ void mbar_wait_cluster(uint32_t bar, uint32_t parity) {
    int n = 0;
    while (!mbar_try_cluster(bar, parity) && ++n < SPIN_LIMIT) {}
}
__device__ __forceinline__ void mbar_wait_sleep(uint32_t bar, uint32_t parity) {
    int n = 0;
    while (!mbar_try(bar, parity) && ++n < SPIN_LIMIT) __nanosleep(SLEEP_NS);
}
__device__ __forceinline__ void mbar_arrive(uint32_t bar) {
    asm volatile("mbarrier.arrive.shared::cta.b64 _, [%0];" ::"r"(bar) : "memory");
}
__device__ __forceinline__ void mbar_arrive_cluster(uint32_t cluster_bar) {
    asm volatile("mbarrier.arrive.shared::cluster.b64 _, [%0];" ::"r"(cluster_bar) : "memory");
}
__device__ __forceinline__ void mbar_expect_tx(uint32_t bar, uint32_t bytes) {
    asm volatile("mbarrier.arrive.expect_tx.shared::cta.b64 _, [%0], %1;" ::"r"(bar), "r"(bytes) : "memory");
}
__device__ __forceinline__ bool elect_one() {
    uint32_t p;
    asm volatile("{\n.reg .pred p;\nelect.sync _|p, 0xffffffff;\nselp.u32 %0, 1, 0, p;\n}" : "=r"(p));
    return p;
}
__device__ __forceinline__ uint32_t mapa(uint32_t addr, uint32_t rank) {
    uint32_t r;
    asm("mapa.shared::cluster.u32 %0, %1, %2;" : "=r"(r) : "r"(addr), "r"(rank));
    return r;
}
__device__ __forceinline__ uint32_t clock32() { uint32_t t; asm volatile("mov.u32 %0, %%clock;" : "=r"(t)); return t; }
__device__ __forceinline__ void sleep_until(uint32_t t) {
    int n = 0;
    while ((int)(clock32() - t) < 0 && ++n < SPIN_LIMIT) __nanosleep(20);
}
__device__ __forceinline__ void yield(float last, uint32_t zero) {
    asm volatile("nanosleep.u32 %0;" ::"r"(__float_as_uint(last) & zero));
}
template <typename T> __device__ __forceinline__ T* at(T* p, uint32_t bytes) {
    asm("" : "+r"(bytes));
    return reinterpret_cast<T*>(reinterpret_cast<uintptr_t>(p) + bytes);
}
__device__ __forceinline__ void tma_2d(uint32_t dst, const CUtensorMap* tm, int c0, int c1, uint32_t bar) {
    asm volatile("cp.async.bulk.tensor.2d.shared::cluster.global.mbarrier::complete_tx::bytes [%0], [%1, {%3, %4}], [%2];"
                 ::"r"(dst), "l"(tm), "r"(bar), "r"(c0), "r"(c1) : "memory");
}
__device__ __forceinline__ void tma_2d_prefetch(const CUtensorMap* tm, int c0, int c1) {
    asm volatile("cp.async.bulk.prefetch.tensor.2d.L2.global [%0, {%1, %2}];" ::"l"(tm), "r"(c0), "r"(c1) : "memory");
}
__device__ __forceinline__ void tma_2d_store(const CUtensorMap* tm, int c0, int c1, uint32_t src) {
    asm volatile("cp.async.bulk.tensor.2d.global.shared::cta.bulk_group [%0, {%2, %3}], [%1];"
                 ::"l"(tm), "r"(src), "r"(c0), "r"(c1) : "memory");
}
__device__ __forceinline__ void bulk_g2s(uint32_t dst, const void* src, uint32_t bytes, uint32_t bar) {
    asm volatile("cp.async.bulk.shared::cluster.global.mbarrier::complete_tx::bytes [%0], [%1], %2, [%3];"
                 ::"r"(dst), "l"(src), "r"(bytes), "r"(bar) : "memory");
}
__device__ __forceinline__ void bulk_s2g(void* dst, uint32_t src, uint32_t bytes) {
    asm volatile("cp.async.bulk.global.shared::cta.bulk_group [%0], [%1], %2;" ::"l"(dst), "r"(src), "r"(bytes) : "memory");
}
__device__ __forceinline__ void st_async4(uint32_t dst, uint32_t a, uint32_t b, uint32_t c, uint32_t d, uint32_t bar) {
    asm volatile("st.async.weak.shared::cluster.mbarrier::complete_tx::bytes.v4.b32 [%0], {%1,%2,%3,%4}, [%5];"
                 ::"r"(dst), "r"(a), "r"(b), "r"(c), "r"(d), "r"(bar) : "memory");
}
__device__ __forceinline__ void bulk_commit() { asm volatile("cp.async.bulk.commit_group;" ::: "memory"); }
template <int N> __device__ __forceinline__ void bulk_wait_read() { asm volatile("cp.async.bulk.wait_group.read %0;" ::"n"(N) : "memory"); }
template <int N> __device__ __forceinline__ void bulk_wait() { asm volatile("cp.async.bulk.wait_group %0;" ::"n"(N) : "memory"); }
__device__ __forceinline__ void fence_async_smem() { asm volatile("fence.proxy.async.shared::cta;" ::: "memory"); }
__device__ __forceinline__ void fence_async_global() { asm volatile("fence.proxy.async.global;" ::: "memory"); }
__device__ __forceinline__ void prefetch_tmap(const CUtensorMap* tm) {
    asm volatile("prefetch.tensormap [%0];" ::"l"(tm) : "memory");
}
__device__ __forceinline__ unsigned long long ld_acquire64(const unsigned long long* p) {
    unsigned long long v; asm volatile("ld.acquire.gpu.global.u64 %0, [%1];" : "=l"(v) : "l"(p) : "memory"); return v;
}
__device__ __forceinline__ unsigned load_epoch(int b) {
    unsigned v; asm volatile("ld.global.u32 %0, [%1];" : "=r"(v) : "l"(at(g_epoch, b * 4)) : "memory"); return v + 1;
}
__device__ __forceinline__ unsigned ld_relaxed(const void* p) {
    unsigned v; asm volatile("ld.relaxed.gpu.global.u32 %0, [%1];" : "=r"(v) : "l"(p) : "memory"); return v;
}
__device__ __forceinline__ uint4 ld_relaxed128(const uint4* p) {
    uint4 v;
    asm volatile("{\n.reg .b128 t;\n.reg .b64 lo, hi;\nld.relaxed.gpu.global.b128 t, [%4];\nmov.b128 {lo, hi}, t;\n"
                 "mov.b64 {%0, %1}, lo;\nmov.b64 {%2, %3}, hi;\n}"
                 : "=r"(v.x), "=r"(v.y), "=r"(v.z), "=r"(v.w) : "l"(p) : "memory");
    return v;
}
__device__ __forceinline__ void st_relaxed128(uint4* p, const uint4& v) {
    asm volatile("{\n.reg .b128 t;\n.reg .b64 lo, hi;\nmov.b64 lo, {%1, %2};\nmov.b64 hi, {%3, %4};\nmov.b128 t, {lo, hi};\n"
                 "st.relaxed.gpu.global.b128 [%0], t;\n}"
                 ::"l"(p), "r"(v.x), "r"(v.y), "r"(v.z), "r"(v.w) : "memory");
}
__device__ __forceinline__ void st_relaxed64(unsigned long long* p, unsigned long long v) {
    asm volatile("st.relaxed.gpu.global.u64 [%0], %1;" ::"l"(p), "l"(v) : "memory");
}
__device__ __forceinline__ void st_release8(void* p, unsigned v) {
    asm volatile("st.release.gpu.global.u8 [%0], %1;" ::"l"(p), "r"(v) : "memory");
}
__device__ __forceinline__ uint64_t policy_evict_first() {
    uint64_t pol;
    asm("createpolicy.fractional.L2::evict_first.b64 %0, 1.0;" : "=l"(pol));
    return pol;
}
__device__ __forceinline__ uint4 ldg_stream(const void* p, uint64_t pol) {
    uint4 v;
    asm volatile("ld.global.nc.L1::no_allocate.L2::cache_hint.v4.u32 {%0,%1,%2,%3}, [%4], %5;"
                 : "=r"(v.x), "=r"(v.y), "=r"(v.z), "=r"(v.w) : "l"(p), "l"(pol));
    return v;
}
__device__ __forceinline__ uint4 ldg_stream_ord(const void* p, uint64_t pol) {
    uint4 v;
    asm volatile("ld.relaxed.gpu.global.L1::no_allocate.L2::cache_hint.v4.u32 {%0,%1,%2,%3}, [%4], %5;"
                 : "=r"(v.x), "=r"(v.y), "=r"(v.z), "=r"(v.w) : "l"(p), "l"(pol) : "memory");
    return v;
}
template <int ID, int N> __device__ __forceinline__ void named_arrive() { asm volatile("bar.arrive %0, %1;" ::"n"(ID), "n"(N) : "memory"); }
template <int ID, int N> __device__ __forceinline__ void named_bar() { asm volatile("bar.sync %0, %1;" ::"n"(ID), "n"(N) : "memory"); }

__device__ __forceinline__ float bf_lo(uint32_t u) { return __uint_as_float(u << 16); }
__device__ __forceinline__ float bf_hi(uint32_t u) { return __uint_as_float(u & 0xffff0000u); }
__device__ __forceinline__ uint32_t pack_bf(float lo, float hi) {
    uint32_t r; asm("cvt.rn.bf16x2.f32 %0, %1, %2;" : "=r"(r) : "f"(hi), "f"(lo)); return r;
}
__device__ __forceinline__ float rbf(float v) { return __uint_as_float(pack_bf(0.f, v)); }
__device__ __forceinline__ float sqrt_f(float v) { float r; asm("sqrt.approx.f32 %0, %1;" : "=f"(r) : "f"(v)); return r; }
__device__ __forceinline__ float rcp_f(float v) { float r; asm("rcp.approx.f32 %0, %1;" : "=f"(r) : "f"(v)); return r; }
__device__ __forceinline__ float silu_f(float z) { return __fdividef(z, 1.0f + __expf(-z)); }
__device__ __forceinline__ uint32_t bsub2(uint32_t a, uint32_t b) {
    uint32_t r; asm("sub.rn.bf16x2 %0, %1, %2;" : "=r"(r) : "r"(a), "r"(b)); return r;
}
__device__ __forceinline__ uint32_t bfma2(uint32_t a, uint32_t b, uint32_t c) {
    uint32_t r; asm("fma.rn.bf16x2 %0, %1, %2, %3;" : "=r"(r) : "r"(a), "r"(b), "r"(c)); return r;
}
__device__ __forceinline__ uint32_t norm2(uint32_t xv, float m, float rinv) {
    uint32_t t = pack_bf(bf_lo(xv) - m, bf_hi(xv) - m);
    return pack_bf(bf_lo(t) * rinv, bf_hi(t) * rinv);
}
__device__ __forceinline__ float gate1(float z) {
    float t;
    const float h = 0.5f * z;
    asm("tanh.approx.f32 %0, %1;" : "=f"(t) : "f"(h));
    return fmaf(h, t, h);
}
__device__ __forceinline__ uint32_t gate2(uint32_t xv, uint32_t mean2, float r0, float r1) {
    const uint32_t t = bsub2(xv, mean2);
    return pack_bf(gate1(bf_lo(t) * r0), gate1(bf_hi(t) * r1));
}
__device__ __forceinline__ uint32_t silu2(uint32_t z) { return pack_bf(silu_f(bf_lo(z)), silu_f(bf_hi(z))); }

__device__ __forceinline__ void stmatrix4(uint32_t addr, uint32_t r0, uint32_t r1, uint32_t r2, uint32_t r3) {
    asm volatile("stmatrix.sync.aligned.m8n8.x4.shared.b16 [%0], {%1,%2,%3,%4};"
                 ::"r"(addr), "r"(r0), "r"(r1), "r"(r2), "r"(r3));
}
__device__ __forceinline__ void stmatrix4t(uint32_t addr, uint32_t r0, uint32_t r1, uint32_t r2, uint32_t r3) {
    asm volatile("stmatrix.sync.aligned.m8n8.x4.trans.shared.b16 [%0], {%1,%2,%3,%4};"
                 ::"r"(addr), "r"(r0), "r"(r1), "r"(r2), "r"(r3));
}
__device__ __forceinline__ void ldmatrix4t(uint32_t addr, uint32_t& r0, uint32_t& r1, uint32_t& r2, uint32_t& r3) {
    asm volatile("ldmatrix.sync.aligned.m8n8.x4.trans.shared.b16 {%0,%1,%2,%3}, [%4];"
                 : "=r"(r0), "=r"(r1), "=r"(r2), "=r"(r3) : "r"(addr));
}

__device__ __forceinline__ void wg_fence() { asm volatile("wgmma.fence.sync.aligned;" ::: "memory"); }
__device__ __forceinline__ void wg_commit() { asm volatile("wgmma.commit_group.sync.aligned;" ::: "memory"); }
template <int N> __device__ __forceinline__ void wg_wait() { asm volatile("wgmma.wait_group.sync.aligned %0;" ::"n"(N) : "memory"); }

__host__ __device__ constexpr uint32_t desc_lo(uint32_t addr, uint32_t lbo) { return ((addr & 0x3FFFF) >> 4) | ((lbo >> 4) << 16); }
#define DESC_HI "0x40000040"

#define R8(a, o) "+f"(a[(o) + 0]), "+f"(a[(o) + 1]), "+f"(a[(o) + 2]), "+f"(a[(o) + 3]), \
                 "+f"(a[(o) + 4]), "+f"(a[(o) + 5]), "+f"(a[(o) + 6]), "+f"(a[(o) + 7])
#define R64(a, o) R8(a, (o) + 0), R8(a, (o) + 8), R8(a, (o) + 16), R8(a, (o) + 24), \
                  R8(a, (o) + 32), R8(a, (o) + 40), R8(a, (o) + 48), R8(a, (o) + 56)

template <int O, int TA>
__device__ __forceinline__ void wgmma128(float (&a)[128], uint32_t da, uint32_t db, int scale_d) {
    asm volatile(
        "{\n.reg .pred p;\n.reg .b64 da, db;\nsetp.ne.b32 p, %66, 0;\n"
        "mov.b64 da, {%64, " DESC_HI "};\nmov.b64 db, {%65, " DESC_HI "};\n"
        "wgmma.mma_async.sync.aligned.m64n128k16.f32.bf16.bf16 "
        "{%0,%1,%2,%3,%4,%5,%6,%7,%8,%9,%10,%11,%12,%13,%14,%15,"
        "%16,%17,%18,%19,%20,%21,%22,%23,%24,%25,%26,%27,%28,%29,%30,%31,"
        "%32,%33,%34,%35,%36,%37,%38,%39,%40,%41,%42,%43,%44,%45,%46,%47,"
        "%48,%49,%50,%51,%52,%53,%54,%55,%56,%57,%58,%59,%60,%61,%62,%63},"
        "da, db, p, 1, 1, %67, 0;\n}"
        : R64(a, O)
        : "r"(da), "r"(db), "r"(scale_d), "n"(TA));
}
template <int O>
__device__ __forceinline__ void wgmma128_rs(float (&a)[128], const uint32_t* f, uint32_t db) {
    asm volatile(
        "{\n.reg .b64 db;\nmov.b64 db, {%68, 8};\n"
        "wgmma.mma_async.sync.aligned.m64n128k16.f32.bf16.bf16 "
        "{%0,%1,%2,%3,%4,%5,%6,%7,%8,%9,%10,%11,%12,%13,%14,%15,"
        "%16,%17,%18,%19,%20,%21,%22,%23,%24,%25,%26,%27,%28,%29,%30,%31,"
        "%32,%33,%34,%35,%36,%37,%38,%39,%40,%41,%42,%43,%44,%45,%46,%47,"
        "%48,%49,%50,%51,%52,%53,%54,%55,%56,%57,%58,%59,%60,%61,%62,%63},"
        "{%64, %65, %66, %67}, db, 1, 1, 1, 0;\n}"
        : R64(a, O)
        : "r"(f[0]), "r"(f[1]), "r"(f[2]), "r"(f[3]), "r"(db));
}
template <int O>
__device__ __forceinline__ void fence_regs64(float (&a)[128]) {
    asm volatile("" : R64(a, O)::"memory");
}

struct Params {
    const __nv_bfloat16* x;
    const __nv_bfloat16* dre;
    const __nv_bfloat16* dim;
    const __nv_bfloat16* wr;
    const __nv_bfloat16* wg;
    const __nv_bfloat16* wu;
    const __nv_bfloat16* wd;
    uint32_t zero;
#define AB g_ab
};

__device__ __forceinline__ float warp_sum(float v) {
#pragma unroll
    for (int o = 16; o; o >>= 1) v += __shfl_xor_sync(0xffffffffu, v, o);
    return v;
}
__device__ __forceinline__ void fma8(float* acc, const uint4& w, float s) {
    acc[0] += s * bf_lo(w.x); acc[1] += s * bf_hi(w.x); acc[2] += s * bf_lo(w.y); acc[3] += s * bf_hi(w.y);
    acc[4] += s * bf_lo(w.z); acc[5] += s * bf_hi(w.z); acc[6] += s * bf_lo(w.w); acc[7] += s * bf_hi(w.w);
}
__device__ __forceinline__ int POS(int t) { return (t & ~15) | ((t & 6) << 1) | ((t & 8) >> 2) | (t & 1); }
__host__ __device__ constexpr int PSLOT(int j) { return j < 4 ? j : (j & 1) + ((j & 2) ? 0 : 4); }
__host__ __device__ constexpr int PPAR(int j) { return j < 4 ? 0 : ((j >> 2) ^ (j >> 1) ^ 1) & 1; }
__host__ __device__ constexpr int DSLOT(int it) { return (it & 3) + 2; }
__device__ __forceinline__ int SREC(int t) { return (t & ~15) | ((t & 3) << 2) | ((t >> 2) & 3); }
__device__ __forceinline__ int KO(int cl) { return ((cl & 1) << 1) | (cl >> 1); }

__global__ void __cluster_dims__(2, 1, 1) __launch_bounds__(NTHREADS, 1)
fnet_fused_kernel(const __grid_constant__ CUtensorMap tm_x, const __grid_constant__ CUtensorMap tm_dre,
                  const __grid_constant__ CUtensorMap tm_dim, const __grid_constant__ CUtensorMap tm_cre,
                  const __grid_constant__ CUtensorMap tm_cim, const __grid_constant__ CUtensorMap tm_out,
                  const __grid_constant__ CUtensorMap tm_x64,
                  const Params P) {
    extern __shared__ __align__(1024) uint8_t smem[];
    const unsigned long long tstart = clock64();
    const uint32_t sb = smem_u32(smem);
    const int tid = threadIdx.x, lane = tid & 31;
    if (tid == 0) { prefetch_tmap((blockIdx.x & 1) ? &tm_dim : &tm_dre); prefetch_tmap(&tm_x); }
    const int warp = __shfl_sync(0xffffffffu, tid >> 5, 0);
    const int pr = blockIdx.x >> 1, p7 = ((pr - 36) * 37) >> 8;
    const int c = blockIdx.x & 1;
    const bool upper = pr >= 36;
    const int col = upper ? pr - 36 - 7 * p7 + 8 : pr < 4 ? 15 : (pr - 4) & 7;
    const int gi = (int)(0x7eca8531fdb96420ull >> (4 * col)) & 15;
    const int g = gi & 7;
    const int r = (gi >> 3) * 4 + (upper ? p7 : pr < 4 ? pr : (pr - 4) >> 3);
#define BLK(n) ((n) - ((n) <= g))
    const int grp = 2 * r + c;
    const int b = g * 16 + grp;
    const uint32_t bar0 = sb + OFF_BAR;
    const uint32_t zero = P.zero;
#define BAR(i) (bar0 + 8u * (i))
#define XBAR(i) (sb + OFF_XB + 64 + 8u * (i))
#define CLUSTER_ARRIVE() asm volatile("barrier.cluster.arrive.relaxed.aligned;" ::: "memory")
#define CLUSTER_WAIT() asm volatile("barrier.cluster.wait.aligned;" ::: "memory")

#define LOAD0(it) do { \
            mbar_expect_tx(BAR(B_FS + DSLOT(it)), SLOT); tma_2d(sb + OFF_S + DSLOT(it) * SLOT, tmD, (it) * 64, r * 128, BAR(B_FS + DSLOT(it))); \
            mbar_expect_tx(BAR(B_FL + (it)), SLOT); tma_2d(sb + OFF_L + (it) * SLOT, &tm_x, (it) * 64, g * 256, BAR(B_FL + (it))); \
            mbar_expect_tx(BAR(B_FL + 4 + (it)), SLOT); tma_2d(sb + OFF_L + (4 + (it)) * SLOT, &tm_x, (it) * 64, g * 256 + 128, BAR(B_FL + 4 + (it))); \
        } while (0)
    if (warp == W0) {
        if (elect_one()) {
            const CUtensorMap* tmD = c ? &tm_dim : &tm_dre;
            mbar_init(BAR(B_FS + 2), 1); mbar_init(BAR(B_FL), 1); mbar_init(BAR(B_FL + 4), 1);
            asm volatile("fence.mbarrier_init.release.cluster;" ::: "memory");
            if (XF) {
                mbar_expect_tx(BAR(B_FL), SLOT); tma_2d(sb + OFF_L, &tm_x, 0, g * 256, BAR(B_FL));
                mbar_expect_tx(BAR(B_FS + 2), SLOT); tma_2d(sb + OFF_S + 2 * SLOT, tmD, 0, r * 128, BAR(B_FS + 2));
                mbar_expect_tx(BAR(B_FL + 4), SLOT); tma_2d(sb + OFF_L + 4 * SLOT, &tm_x, 0, g * 256 + 128, BAR(B_FL + 4));
            } else LOAD0(0);
        }
        __syncwarp();
    }
    if (warp == 12) {
        if (elect_one()) {
#pragma unroll
            for (int i = 1; i < 4; i++) { mbar_init(BAR(B_FS + 2 + i), 1); mbar_init(BAR(B_FL + i), 1); mbar_init(BAR(B_FL + 4 + i), 1); }
#pragma unroll
            for (int i = 0; i < 4; i++) mbar_init(XBAR(i), 1);
            asm volatile("fence.mbarrier_init.release.cluster;" ::: "memory");
        }
        __syncwarp();
    }
    if (warp == 14) {
        if (elect_one()) {
#pragma unroll
            for (int i = 0; i < 8; i++) { mbar_init(BAR(B_EL + i), 1); mbar_init(XBAR(4 + i), 1); if (i < 6) mbar_init(BAR(B_ES + i), 2); }
            asm volatile("fence.mbarrier_init.release.cluster;" ::: "memory");
        }
        __syncwarp();
    }
    if (warp == 15) {
        if (elect_one()) {
            mbar_init(BAR(B_FS), 1); mbar_init(BAR(B_FS + 1), 1);
#pragma unroll
            for (int i = B_SRD; i < B_COUNT; i++) mbar_init(BAR(i), i == B_GO ? 2 : i == B_STATS || i == B_LST ? 4 : 1);
#pragma unroll
            for (int i = 0; i < 4; i++) mbar_expect_tx(BAR(B_RECV + i), SLOT / 2);
            mbar_expect_tx(BAR(B_PEER), 1024); mbar_expect_tx(BAR(B_H), 128);
            asm volatile("fence.mbarrier_init.release.cluster;" ::: "memory");
        }
        __syncwarp();
    }
    CLUSTER_ARRIVE();
    if ((sb & 0xffffffu) != SB0) return;

#define GATHER(ptr, cnt, valid) do { int n = 0; bool ok; _Pragma("unroll 1") do { ok = true; \
                _Pragma("unroll") for (int i = 0; i < (cnt); i++) { f[i] = ld_relaxed128((ptr) + i * 32); ok = ok && (valid); } \
                if (__all_sync(0xffffffffu, ok)) break; \
                __nanosleep(GSL); \
            } while (++n < SPIN_LIMIT); } while (0)
    if (warp >= 8 && warp < 12) {
        asm volatile("setmaxnreg.dec.sync.aligned.u32 %0;" ::"n"(512 - PROD_REGS - 2 * CONS_REGS));
        const int aw = warp - 8, mt = tid - 256;
        unsigned ep;
        {
            const uint8_t* rp = smem + OFF_S + aw * 2048 + lane * 16;
            const __nv_bfloat16* dp = at(c ? P.dim : P.dre, (r * 128 + g * 16 + aw * 4) * D_ * 2);
            float wf[32], sw = 0.f;
#pragma unroll
            for (int i = 0; i < 4; i++) {
                const uint4 w = __ldg(reinterpret_cast<const uint4*>(at(P.wr, lane * 16) + i * 256));
                const uint32_t wv[4] = {w.x, w.y, w.z, w.w};
#pragma unroll
                for (int e = 0; e < 4; e++) { wf[8 * i + 2 * e] = bf_lo(wv[e]); wf[8 * i + 2 * e + 1] = bf_hi(wv[e]); sw = (sw + bf_lo(wv[e])) + bf_hi(wv[e]); }
            }
            ep = load_epoch(b);
            sw = warp_sum(sw);
            CLUSTER_WAIT();
            float x0[4] = {}, s1[4] = {}, s2[4] = {}, sx[4] = {}, sd[4] = {};
#define PUSH(a, v) do { a[0] = a[1]; a[1] = a[2]; a[2] = a[3]; a[3] = v; } while (0)
#pragma unroll 1
            for (int k = 0; k < 4; k++) {
                mbar_wait(XBAR(k), 0);
                uint4 v[4];
#pragma unroll
                for (int i = 0; i < 4; i++) v[i] = *reinterpret_cast<const uint4*>(rp + k * 8192 + i * 512);
                uint32_t sh = v[0].x << 16;
                float a1s = 0.f, a2s = 0.f, axs = 0.f;
#pragma unroll
                for (int i = 0; i < 4; i++) {
                    sh = __shfl_sync(0xffffffffu, sh | (__float_as_uint(axs) & zero), 0);
                    const uint32_t xv[4] = {v[i].x, v[i].y, v[i].z, v[i].w};
#pragma unroll
                    for (int e = 0; e < 4; e++) {
                        const float a0 = bf_lo(xv[e]) - __uint_as_float(sh), a1 = bf_hi(xv[e]) - __uint_as_float(sh);
                        a1s += a0 + a1;
                        a2s = fmaf(a0, a0, fmaf(a1, a1, a2s));
                        axs = fmaf(a0, wf[8 * i + 2 * e], fmaf(a1, wf[8 * i + 2 * e + 1], axs));
                    }
                }
                PUSH(x0, __uint_as_float(sh)); PUSH(s1, a1s); PUSH(s2, a2s); PUSH(sx, axs);
                fence_async_smem();
                __syncwarp();
                if (elect_one()) {
                    const uint32_t db = XBAR(k == 3 ? 8 + aw : 4 + aw);
                    if (k == 0 || k == 3) mbar_expect_tx(db, k ? 2048 : 6144);
                    bulk_g2s(sb + OFF_S + k * 8192 + aw * 2048, dp + k * D_, 2048, db);
                }
            }
#define FOLD4(a) do { const bool u16 = lane & 16, u8 = lane & 8; \
                float p0 = (u16 ? a[2] : a[0]) + __shfl_xor_sync(0xffffffffu, u16 ? a[0] : a[2], 16); \
                float p1 = (u16 ? a[3] : a[1]) + __shfl_xor_sync(0xffffffffu, u16 ? a[1] : a[3], 16); \
                a[0] = (u8 ? p1 : p0) + __shfl_xor_sync(0xffffffffu, u8 ? p0 : p1, 8); \
                _Pragma("unroll") for (int o = 4; o; o >>= 1) a[0] += __shfl_xor_sync(0xffffffffu, a[0], o); } while (0)
#pragma unroll 1
            for (int k = 0; k < 4; k++) {
                mbar_wait(XBAR(k == 3 ? 8 + aw : 4 + aw), 0);
                float run = 0.f;
#pragma unroll
                for (int i = 0; i < 4; i++) {
                    const uint4 v = *reinterpret_cast<const uint4*>(rp + k * 8192 + i * 512);
                    const uint32_t dv[4] = {v.x, v.y, v.z, v.w};
#pragma unroll
                    for (int e = 0; e < 4; e++) run += bf_lo(dv[e]) + bf_hi(dv[e]);
                }
                PUSH(sd, run);
            }
            named_bar<4, 128>();
            if (mt < 12) asm volatile("mbarrier.inval.shared::cta.b64 [%0];" ::"r"(XBAR(mt)) : "memory");
            FOLD4(sd); FOLD4(s1); FOLD4(s2); FOLD4(sx);
            const float nb = __shfl_down_sync(0xffffffffu, sd[0], 8);
            if ((lane & 15) == 0)
                st_relaxed128(at(g_rs, (grp * 64 + g * 8 + aw * 2 + (lane >> 4)) * 16), make_uint4(__float_as_uint(sd[0]), ep, __float_as_uint(nb), ep));
            if (mt == 0) PROF_T(6);
            const int rr = lane >> 3;
            const float c0 = rr == 0 ? x0[0] : rr == 1 ? x0[1] : rr == 2 ? x0[2] : x0[3];
            const float dm = s1[0] * (1.0f / D_);
            const float mb = rbf(c0 + dm);
            const float rinv = rcp_f(rbf(sqrt_f(rbf(rbf(fmaxf(s2[0] * (1.0f / D_) - dm * dm, 0.f)) + 1e-5f))));
            if ((lane & 7) == 0) st_relaxed128(at(g_stat, (b * 16 + aw * 4 + rr) * 16), make_uint4(__float_as_uint(mb), __float_as_uint(rinv), ep, 0));
            unsigned u = __bfloat16_as_ushort(__float2bfloat16_rn((sx[0] + (c0 - mb) * sw) * rinv));
            u = (u & 0x8000u) ? (~u & 0xffffu) : (u | 0x8000u);
            u = (u << 16) | (0xffffu - (unsigned)(b * 16 + rr * 4 + aw));
            u = __reduce_max_sync(0xffffffffu, u);
            if (lane == 0) { *reinterpret_cast<unsigned*>(smem + OFF_XB + aw * 4) = u; mbar_arrive(BAR(B_LST)); }
            if (mt == 0) PROF_T(2);
            uint4 f[4];
            if (aw < 2) {
                const int t = SREC(aw * 128 + lane);
                GATHER(at(g_stat, (g * 256 + aw * 128 + lane) * 16), 4, f[i].z == ep);
#pragma unroll
                for (int i = 0; i < 4; i++) {
                    *reinterpret_cast<uint32_t*>(smem + OFF_RSTD + (POS(t) + i * 32) * 4) = f[i].y;
                    *reinterpret_cast<uint16_t*>(smem + OFF_MEAN + (POS(t) + i * 32) * 2) = (uint16_t)(f[i].x >> 16);
                }
            } else {
                const int e2 = (aw - 2) * 32 + lane;
                GATHER(at(g_rs, (grp * 64 + e2) * 16), 1, f[i].y == ep && f[i].w == ep);
#pragma unroll
                for (int i = 0; i < 2; i++) {
                    const float v = __uint_as_float(i ? f[0].z : f[0].x);
                    const float hi = rbf(v), mid = rbf(v - hi), lo = v - hi - mid;
                    *reinterpret_cast<uint4*>(smem + OFF_RS + (e2 * 2 + i) * 16) = make_uint4(pack_bf(hi, mid), pack_bf(lo, 0.f), 0, 0);
                }
            }
            fence_async_smem();
            __syncwarp();
            if (lane == 0) mbar_arrive(BAR(B_STATS));
            if (mt == 127) PROF_T(9);
        }
        const bool moe = pr < 28 || pr >= 36;
        const int pair = pr < 28 ? pr : pr - 8;
        if (moe) {
            const uint64_t pol = policy_evict_first();
            const __nv_bfloat16* wp = at((aw & 1) ? P.wu : P.wg, ((c * 512 + (aw >> 1) * 256 + (lane >> 3) * 8) * F_ + pair * 64 + (lane & 7) * 8) * 2);
            uint4 b0[8], b1[8];
#define FILL(buf, str) do { _Pragma("unroll") for (int q = 0; q < 8; q++) buf[q] = ldg_stream(wp + q * (str), pol); } while (0)
#define PAUSE() do { if (mbar_test(BAR(B_QUIET), 0)) mbar_wait_sleep(BAR(B_GO), 0); } while (0)
#define FILLO(buf, row) do { _Pragma("unroll") for (int q = 0; q < 8; q++) buf[q] = ldg_stream_ord(wp + ((row) + q) * F_, pol); } while (0)
            FILLO(b0, 0);
            mbar_wait(BAR(B_SEL), 0);
            uint4 xn;
            {
                const int sel = ~*reinterpret_cast<volatile unsigned*>(smem + OFF_SEL) & (S_ - 1);
                xn = __ldg(reinterpret_cast<const uint4*>(at(P.x, (sel * D_ + c * 512 + (aw >> 1) * 256 + (lane & 7) * 32 + (lane >> 3) * 8) * 2)));
                uint4 f[1];
                GATHER(at(g_stat, SREC(sel) * 16), 1, f[i].z == ep);
                FILLO(b1, 32);
                PAUSE();
                const float m = __uint_as_float(f[0].x), ri = __uint_as_float(f[0].y);
                xn = make_uint4(norm2(xn.x, m, ri), norm2(xn.y, m, ri), norm2(xn.z, m, ri), norm2(xn.w, m, ri));
            }
            float ag[8];
#pragma unroll
            for (int i = 0; i < 8; i++) ag[i] = 0.f;
#define ROUND(cur, nxt, rd) do { \
                PAUSE(); \
                if (lane == 0) TRACE(192 + aw * 12 + (rd)); \
                if ((rd) == 7) wp = at(P.wd - 16 * D_, ((pair * 64 + (lane >> 4) * 8) * D_ + c * 512 + aw * 128 + (lane & 15) * 8) * 2); \
                wp = at(wp, ((rd) < 7 ? 64 * F_ : 32 * D_) + (cur[7].x & zero)); \
                if ((rd) & 7) { if ((rd) < 7) FILL(nxt, F_); else if ((rd) < 11) FILL(nxt, D_); } \
                _Pragma("unroll") for (int q = 0; q < 8; q += 2) { \
                    const uint32_t xw = __shfl_sync(0xffffffffu, q == 0 ? xn.x : q == 2 ? xn.y : q == 4 ? xn.z : xn.w, (lane & 24) | ((rd) & 7)); \
                    fma8(ag, cur[q], bf_lo(xw)); \
                    fma8(ag, cur[q + 1], bf_hi(xw)); \
                    if (q < 6) yield(ag[7], zero); \
                } } while (0)
#pragma unroll 1
            for (int rd = 0; rd < 12; rd += 2) {
                ROUND(b0, b1, rd);
                ROUND(b1, b0, rd + 1);
                if (rd == 6 || rd == 10) {
#pragma unroll
                    for (int i = 0; i < 8; i++) ag[i] += __shfl_xor_sync(0xffffffffu, ag[i], 16);
                }
                if (rd == 6) {
#pragma unroll
                    for (int i = 0; i < 8; i++) ag[i] += __shfl_xor_sync(0xffffffffu, ag[i], 8);
                    if (lane < 8) {
                        const uint32_t dst = mapa(sb + OFF_XB + (c * 4 + aw) * 128 + (lane & 3) * 32, lane >> 2), pb = mapa(BAR(B_PEER), lane >> 2);
                        st_async4(dst, __float_as_uint(ag[0]), __float_as_uint(ag[1]), __float_as_uint(ag[2]), __float_as_uint(ag[3]), pb);
                        st_async4(dst + 16, __float_as_uint(ag[4]), __float_as_uint(ag[5]), __float_as_uint(ag[6]), __float_as_uint(ag[7]), pb);
                    }
                    __syncwarp();
                    wp += 16 * D_; FILL(b1, D_); wp -= 16 * D_;
                    if (aw == 3) {
                        mbar_wait_cluster(BAR(B_PEER), 0);
                        const float* ps = reinterpret_cast<const float*>(smem + OFF_XB) + lane;
                        const float go = (ps[0] + ps[64]) + (ps[128] + ps[192]), uo = (ps[32] + ps[96]) + (ps[160] + ps[224]);
                        const float h = rbf(silu_f(rbf(go))) * rbf(uo), ho = __shfl_xor_sync(0xffffffffu, h, 1);
                        asm volatile("st.async.weak.shared::cluster.mbarrier::complete_tx::bytes.b32 [%0], %1, [%2];"
                                     ::"r"(mapa(sb + OFF_H + c * 64 + (lane >> 1) * 4, lane & 1)), "r"((lane & 1) ? pack_bf(ho, h) : pack_bf(h, ho)),
                                       "r"(mapa(BAR(B_H), lane & 1)) : "memory");
                    }
                    mbar_wait_cluster(BAR(B_H), 0);
                    xn = *reinterpret_cast<const uint4*>(smem + OFF_H + (lane & 3) * 32 + (lane >> 4) * 16);
#pragma unroll
                    for (int i = 0; i < 8; i++) ag[i] = 0.f;
                    if (mt == 0) PROF_T(10);
                }
            }
            const int hi = lane >> 4;
            st_relaxed128(at(g_part, pair * 4096 + (c * 8 + aw * 2 + ((lane >> 3) & 1)) * 256 + hi * 128 + (lane & 7) * 16),
                          make_uint4((__float_as_uint(hi ? ag[4] : ag[0]) & ~15u) | (ep & 15u), __float_as_uint(hi ? ag[5] : ag[1]),
                                     __float_as_uint(hi ? ag[6] : ag[2]), __float_as_uint(hi ? ag[7] : ag[3])));
            if (mt == 0) PROF_T(11);
        } else {
            mbar_wait_sleep(BAR(B_SEL), 0);
        }
        const int sel = ~*reinterpret_cast<volatile unsigned*>(smem + OFF_SEL) & (S_ - 1);
        if ((sel >> 8) == g) {
            const int col = (lane & 7) * 8 + ((lane >> 3) & 1) * 4;
            const uint2 xv = __ldg(reinterpret_cast<const uint2*>(at(P.x, (sel * D_ + grp * 64 + col) * 2)));
            uint4 f[1];
            GATHER(at(g_stat, SREC(sel) * 16), 1, f[i].z == ep);
            const uint4 rec = f[0];
            const uint4* src = at(g_part, (aw * 14 + (lane >> 4)) * 4096 + grp * 256 + (lane & 15) * 16);
            if (!moe) {
                int n = 0;
                while (((ld_relaxed(src) ^ ep) & 15u) != 0 && ++n < SPIN_LIMIT) __nanosleep(500);
            }
            uint4 t[7];
            int n = 0;
            bool ok;
            do {
                ok = true;
#pragma unroll
                for (int u = 0; u < 7; u++) { t[u] = ld_relaxed128(src + u * 512); ok = ok && ((t[u].x ^ ep) & 15u) == 0; }
            } while (!__all_sync(0xffffffffu, ok) && ++n < SPIN_LIMIT);
            float4 a = make_float4(0.f, 0.f, 0.f, 0.f);
#pragma unroll
            for (int u = 0; u < 7; u++) {
                a.x += __uint_as_float(t[u].x & ~15u); a.y += __uint_as_float(t[u].y); a.z += __uint_as_float(t[u].z); a.w += __uint_as_float(t[u].w);
            }
            a.x += __shfl_xor_sync(0xffffffffu, a.x, 16); a.y += __shfl_xor_sync(0xffffffffu, a.y, 16);
            a.z += __shfl_xor_sync(0xffffffffu, a.z, 16); a.w += __shfl_xor_sync(0xffffffffu, a.w, 16);
            float4* park = reinterpret_cast<float4*>(smem + OFF_XB) + (lane & 15);
            if (lane < 16) park[aw * 16] = a;
            named_bar<4, 128>();
            if (aw == 0) {
                const float4 p1 = park[16], p2 = park[32], p3 = park[48];
                a.x = (a.x + p1.x) + (p2.x + p3.x); a.y = (a.y + p1.y) + (p2.y + p3.y);
                a.z = (a.z + p1.z) + (p2.z + p3.z); a.w = (a.w + p1.w) + (p2.w + p3.w);
                unsigned u = *reinterpret_cast<volatile unsigned*>(smem + OFF_SEL) >> 16;
                u = (u & 0x8000u) ? (u & 0x7fffu) : (~u & 0xffffu);
                const float sg = rbf(__fdividef(1.0f, 1.0f + __expf(-__uint_as_float(u << 16))));
                const float m = __uint_as_float(rec.x), ri = __uint_as_float(rec.y);
                const uint32_t n0 = norm2(xv.x, m, ri), n1 = norm2(xv.y, m, ri);
                uint2 o;
                o.x = silu2(pack_bf(bf_lo(n0) + rbf(rbf(a.x) * sg), bf_hi(n0) + rbf(rbf(a.y) * sg)));
                o.y = silu2(pack_bf(bf_lo(n1) + rbf(rbf(a.z) * sg), bf_hi(n1) + rbf(rbf(a.w) * sg)));
                if (lane < 16) *reinterpret_cast<uint2*>(smem + OFF_H + col * 2) = o;
                __syncwarp();
                if (lane == 0) { mbar_arrive(BAR(B_UPD)); PROF_T(12); }
            }
        }
    } else if (warp < 8) {
        asm volatile("setmaxnreg.inc.sync.aligned.u32 %0;" ::"n"(CONS_REGS));
        CLUSTER_WAIT();
        const int wg = warp >> 2, wq = warp & 3;
        const int wt = tid & 127;
        float acc[128];
        const uint32_t fL = BAR(B_FL + 4 * wg), eL = BAR(B_EL + 4 * wg);
        const uint32_t dL = desc_lo(SB0 + OFF_L, 16) + wg * 4096;
        constexpr uint32_t dS = desc_lo(SB0 + OFF_S, 16);
        constexpr uint32_t SL = SLOT >> 4;
#define RELEASE(ls, ss) do { if (wt == 0) { mbar_arrive(eL + 8u * (ls)); mbar_arrive(BAR(B_ES + (ss))); } } while (0)
#define WAIT_FULL(ls, lph, ss, sph) do { mbar_wait(BAR(B_FS + (ss)), sph); mbar_wait(fL + 8u * (ls), lph); } while (0)
#define TURN() do { if (wg) named_bar<6, 256>(); else named_bar<5, 256>(); } while (0)
#define PASS() do { if (wg) named_arrive<5, 256>(); else named_arrive<6, 256>(); } while (0)
#define WG_BAR() do { if (wg) named_bar<2, 128>(); else named_bar<1, 128>(); } while (0)
        if (wg == 1) PASS();

#define MMA1_H(O, s, first) do { _Pragma("unroll") for (int kk = 0; kk < 4; kk++) \
            wgmma128<O, 0>(acc, dL + (s) * SL + kk * 2 + (O) * 8, dS + DSLOT(s) * SL + kk * 2, !((first) && kk == 0)); } while (0)
#define WAIT1(s, ph) WAIT_FULL(s, ph, DSLOT(s), ph)
#define PROBE(ls, lph, ss, sph) (mbar_test(BAR(B_FS + (ss)), sph) & mbar_test(fL + 8u * (ls), lph))
#define REL1(s) RELEASE(s, DSLOT(s))
#pragma unroll 1
        for (int it = 0; it < 12; it++) {
            const int s = it & 3;
            const bool ok = PROBE(s, (it >> 2) & 1, DSLOT(s), (it >> 2) & 1);
            if (it) { wg_wait<0>(); REL1((s + 3) & 3); }
            if (!ok) WAIT1(s, (it >> 2) & 1);
            TURN();
            wg_fence(); MMA1_H(0, s, it == 0); MMA1_H(64, s, it == 0); wg_commit();
            PASS();
            if (it == 0 && tid == 0) PROF_T(16);
        }
        TS(12);
        float rs[4] = {};
        uint32_t nm[8] = {};
#define GET_STATS() do { mbar_wait(BAR(B_STATS), 0); \
            const int p0 = POS(wg * 128 + wq * 16 + (lane >> 2));                   \
            const uint32_t msk = (lane & 3) == 0 ? 0xffffffffu : (lane & 3) == 1 ? 0x0000ffffu : 0u; \
            _Pragma("unroll") for (int i = 0; i < 4; i++) { \
                const int p = p0 + (i & 1) * 2 + (i >> 1) * 64; \
                rs[i] = *reinterpret_cast<const float*>(smem + OFF_RSTD + p * 4); \
                const uint32_t m = *reinterpret_cast<const uint16_t*>(smem + OFF_MEAN + p * 2) ^ 0x8000u; \
                nm[i + (i & 2)] = (m | (m << 16)) & msk; \
            } } while (0)
        const bool early = wg || __all_sync(0xffffffffu, mbar_test(BAR(B_STATS), 0));
        if (early && !wg) GET_STATS();
        WAIT1(0, 1);
        TS(13);
        wg_wait<0>(); REL1(3);
        if (wg) GET_STATS();
        TS(14);
        TURN();
        wg_fence();
        MMA1_H(0, 0, false);
        if (tid == 0) { mbar_arrive(BAR(B_QUIET)); PROF_T(15); }
        WAIT1(1, 1); wg_fence(); MMA1_H(0, 1, false);
        WAIT1(2, 1); wg_fence(); MMA1_H(0, 2, false); wg_commit();
        if (!early) GET_STATS();
        asm volatile("" : "+r"(nm[0]), "+r"(nm[1]), "+r"(nm[2]), "+r"(nm[3]), "+r"(nm[4]), "+r"(nm[5]), "+r"(nm[6]), "+r"(nm[7])::"memory");
        wg_fence();
        wgmma128_rs<64>(acc, nm + 4, (SB0 + OFF_RS) >> 4);
        wgmma128_rs<0>(acc, nm, (SB0 + OFF_RS) >> 4);
        WAIT1(3, 1); wg_fence(); MMA1_H(0, 3, false); wg_commit();
        PASS();
        const int mrow = wq * 16 + ((lane >> 3) & 1) * 8 + (lane & 7);
#define EPI1(O, slot, FREE) do { const uint32_t dst = sb + OFF_S + (slot) * SLOT + mrow * 128; \
            uint32_t pk[32]; \
            _Pragma("unroll") for (int i = 0; i < 32; i += 4) { \
                _Pragma("unroll") for (int k = 0; k < 4; k++) \
                    pk[i + k] = pack_bf(acc[(O) + 2 * (i + k)] * rs[(O) / 32 + (k & 1)], acc[(O) + 2 * (i + k) + 1] * rs[(O) / 32 + (k & 1)]); \
                if (i == EF) { FREE; } \
                if (i >= EF) { _Pragma("unroll") for (int v = (i == EF ? 0 : i); v <= i; v += 4) \
                    stmatrix4(dst + ((v >> 4) ^ c ^ 1) * 8192 + ((((v >> 1) & 7) + (lane >> 4)) ^ (lane & 7)) * 16, pk[v], pk[v + 1], pk[v + 2], pk[v + 3]); } } \
            WG_BAR(); \
            if (wt == 0) mbar_arrive(BAR(B_FS + (slot))); } while (0)
        TS(15);
        wg_wait<0>();
        fence_regs64<0>(acc);
        TS(16);
        {
            constexpr int EF = 0;
            EPI1(0, wg, if (wg) mbar_wait(BAR(B_FS), 0));
        }
        TS(17);
        TURN();
        wg_fence();
        MMA1_H(64, 0, false); wg_commit();
        MMA1_H(64, 1, false); wg_commit();
        MMA1_H(64, 2, false); wg_commit();
        wg_wait<2>(); REL1(0);
        MMA1_H(64, 3, false); wg_commit();
        PASS();
        TS(18);
        wg_wait<2>(); REL1(1);
        mbar_wait(BAR(B_FS), 0); mbar_wait(BAR(B_FS + 1), 0); fence_async_smem();
        wg_wait<1>(); REL1(2);
        wg_wait<0>(); REL1(3);
        fence_regs64<64>(acc);
        TS(19);
        {
            constexpr int EF = 16;
            EPI1(64, 2 + wg, mbar_wait(BAR(B_ES + 2 + wg), 1));
        }
        TS(20);

        float ac2[128];
#define MMA2_H(O, ls, ss, first) do { _Pragma("unroll") for (int kk = 0; kk < 4; kk++) \
            wgmma128<O, 1>(ac2, dS + (ss) * SL + kk * 128 + (O) * 8, dL + (ls) * SL + kk * 2, !((first) && kk == 0)); } while (0)
#define WAIT2(j) WAIT_FULL((j) & 3, ((j) >> 2) & 1, PSLOT(j), PPAR(j))
#define MMA2(j) do { wg_fence(); MMA2_H(0, (j) & 3, PSLOT(j), (j) == 0); MMA2_H(64, (j) & 3, PSLOT(j), (j) == 0); wg_commit(); } while (0)
#define REL2(j) RELEASE((j) & 3, PSLOT(j))
        WAIT2(0); TURN(); MMA2(0);
        WAIT2(1); MMA2(1); PASS();
        TS(21);
        wg_wait<1>(); REL2(0);
        mbar_wait(BAR(B_FS + 2), 0); mbar_wait(BAR(B_FS + 3), 0); fence_async_smem();
        TS(22);
        {
            uint32_t l2 = 2, s2 = 2, sp = 1, lph = 0, sph = 0;
#pragma unroll 1
            for (int j = 2; j < XJ; j += 2) {
#pragma unroll
                for (int h = 0; h < 2; h++) {
                    const bool ok = PROBE(l2 + h, lph, s2 + h, sph);
                    wg_wait<0>(); RELEASE(h ? l2 : 3 - l2, h ? s2 : sp);
                    if (!ok) WAIT_FULL(l2 + h, lph, s2 + h, sph);
                    TURN();
                    wg_fence(); MMA2_H(0, l2 + h, s2 + h, false); MMA2_H(64, l2 + h, s2 + h, false); wg_commit();
                    PASS();
                    if (h == (GOJ & 1) && j == (GOJ & ~1) && wt == 0) { mbar_arrive(BAR(B_GO)); if (wg == 0) PROF_T(19); }
                }
                sp = s2 + 1; s2 = 2 * l2; sph = lph; l2 ^= 2;
                lph ^= l2 == 0;
            }
        }
        if (tid == 0) PROF_T(20);
        uint32_t gt[32];
        const uint32_t xrow = sb + OFF_S + 2 * SLOT + wg * 8192 + ((lane >> 4) * 8 + (lane & 7)) * 128 + (((2 * wq + ((lane >> 3) & 1)) ^ (lane & 7)) << 4);
        const uint32_t gsign = c ? 0x80008000u : 0u;
#define XOFF(v) (((v) >> 2) * SLOT + ((v) & 3) * 2048)
        int sel = 0;
        bool own = false;
#define PATCH() do { own = false; \
            const uint32_t v0 = *reinterpret_cast<const uint16_t*>(smem + OFF_H + (wq * 16 + (lane >> 2)) * 2) ^ gsign; \
            const uint32_t v1 = *reinterpret_cast<const uint16_t*>(smem + OFF_H + (wq * 16 + (lane >> 2)) * 2 + 16) ^ gsign; \
            const uint32_t pick = (lane & 3) != ((sel >> 1) & 3) ? 0x3210u : (sel & 1) ? 0x5410u : 0x3254u; \
            _Pragma("unroll") for (int i = 0; i < 16; i++) { \
                const uint32_t m = ((sel >> 3) & 15) == i ? pick : 0x3210u; \
                gt[2 * i] = __byte_perm(gt[2 * i], v0, m); \
                gt[2 * i + 1] = __byte_perm(gt[2 * i + 1], v1, m); \
            } } while (0)
#pragma unroll
        for (int u = 0; u < 8; u++) {
            if (u) { WAIT2(XJ + u - 1); wg_wait<0>(); REL2(XJ + u - 2); TURN(); MMA2(XJ + u - 1); PASS(); }
            uint32_t* o = &gt[4 * u];
            if (!(u & 3)) mbar_wait(BAR(B_FS + 2 + (u >> 2)), 1);
            ldmatrix4t(xrow + XOFF(u), o[0], o[1], o[2], o[3]);
            const float4 r4 = *reinterpret_cast<const float4*>(smem + OFF_RSTD + (wg * 128 + u * 16 + (lane & 3) * 4) * 4);
            const uint2 m2 = *reinterpret_cast<const uint2*>(smem + OFF_MEAN + (wg * 128 + u * 16 + (lane & 3) * 4) * 2);
            o[0] = gate2(o[0], m2.x, r4.x, r4.y) ^ gsign;
            o[1] = gate2(o[1], m2.x, r4.x, r4.y) ^ gsign;
            o[2] = gate2(o[2], m2.y, r4.z, r4.w) ^ gsign;
            o[3] = gate2(o[3], m2.y, r4.z, r4.w) ^ gsign;
            if (u == 2) {
                mbar_wait(BAR(B_SEL), 0);
                sel = ~*reinterpret_cast<volatile unsigned*>(smem + OFF_SEL) & (S_ - 1);
                own = (sel >> 7) == 2 * g + wg;
            }
            asm volatile("st.shared.v2.u32 [%0], {%1,%2};" ::"r"(sb + OFF_SEL + 16), "r"(o[0] ^ o[1]), "r"(o[2] ^ o[3]) : "memory");
        }
        if (tid == 0) PROF_T(21);
        WAIT2(27);
        wg_wait<0>(); REL2(26);
        if (own) {
            const uint32_t t0 = clock32();
            bool ok;
            while (!(ok = mbar_test(BAR(B_UPD), 0)) && clock32() - t0 < wg * 1900u) __nanosleep(50);
            if (__all_sync(0xffffffffu, ok)) PATCH();
        }
        TS(0);
        TURN();
        MMA2(27);
        WAIT2(28); wg_fence(); MMA2_H(0, 0, PSLOT(28), false); wg_commit();
        if (wg == 0) { wg_fence(); MMA2_H(64, 0, PSLOT(28), false); wg_commit(); }
        constexpr uint32_t dL0 = desc_lo(SB0 + OFF_L, 16);
        const uint32_t ct[3] = {wg ? 3u : 1u, wg ? 1u : 2u, wg ? 2u : 5u};
#define TMMA(O, i) wgmma128<O, 1>(ac2, ((i) < 8 ? dS + PSLOT(29 + ((i) >> 2)) * SL : dL0 + 6 * SL) + ((i) & 3) * 128 + (O) * 8, \
                                  dL0 + ct[(i) >> 2] * SL + ((i) & 3) * 2, 1)
#define KEEP(i) TMMA(64, i)
#pragma unroll
        for (int k = 0; k < 3; k++) {
            if (k < 2) mbar_wait(BAR(B_FS + PSLOT(29 + k)), PPAR(29 + k)); else mbar_wait(BAR(B_FL + 6), 1);
            mbar_wait(BAR(B_FL + ct[k]), k == 0 || wg == 0);
            wg_fence();
#pragma unroll
            for (int i = 4 * k; i < 4 * k + 4; i++) TMMA(0, i);
            wg_commit();
            if (k < 2) wg_wait<2>();
            if (k == 0 && tid == 0) mbar_arrive(BAR(B_EL + 3));
            if (k == 1 && tid == 0) mbar_arrive_cluster(mapa(BAR(B_RDY), c ^ 1));
        }
        TS(1);
        wg_fence();
#pragma unroll
        for (int i = 0; i < KQ; i++) KEEP(i);
        wg_commit();
        mbar_wait(BAR(B_RDY + wg), 0);
        wg_wait<1>();
        fence_regs64<0>(ac2);
        TS(2);
        wg_fence();
        {
            const uint32_t dst = mapa(sb + OFF_L + wg * 5 * SLOT + wt * 16, c ^ 1), rb = mapa(BAR(B_RECV + 2 * wg), c ^ 1);
#pragma unroll
            for (int v = 0; v < 8; v++) {
                if (KQ + v < 12) KEEP(KQ + v);
                if (KQ + v == 7) wg_commit();
                if (KQ + v == 11) { wg_commit(); if (wg == 0) PASS(); }
                st_async4(dst + v * 2048, pack_bf(ac2[8 * v + 0], ac2[8 * v + 1]), pack_bf(ac2[8 * v + 2], ac2[8 * v + 3]),
                          pack_bf(ac2[8 * v + 4], ac2[8 * v + 5]), pack_bf(ac2[8 * v + 6], ac2[8 * v + 7]), rb + (v >> 2) * 8);
            }
        }
        if (wg == 1) { wg_fence(); MMA2_H(64, 0, PSLOT(28), false); wg_commit(); }
        TS(3);
        uint32_t xr[32];
#define LDX(v) ldmatrix4t(xrow + XOFF(v), xr[4 * (v)], xr[4 * (v) + 1], xr[4 * (v) + 2], xr[4 * (v) + 3])
        if (wg == 0) {
            wg_wait<2>();
            if (wt == 0) mbar_arrive(BAR(B_EL + 1));
            wg_wait<1>();
            if (wt == 0) mbar_arrive(BAR(B_EL + 2));
        }
#pragma unroll
        for (int v = 0; v < XE; v++) LDX(v);
        if (wg == 0) {
            wg_wait<0>();
            if (wt == 0) mbar_arrive_cluster(mapa(BAR(B_RDY + 1), c ^ 1));
        }
        TS(4);
        if (own) { mbar_wait(BAR(B_UPD), 0); PATCH(); }
        TS(5);
        uint4 rv[8];
#define FETCH(v0) do { if ((v0) == 0 || (v0) == 4) mbar_wait_cluster(BAR(B_RECV + 2 * wg + (v0) / 4), 0); \
            _Pragma("unroll") for (int v = (v0); v < (v0) + 2; v++) { \
                asm volatile("ld.shared.v4.u32 {%0,%1,%2,%3}, [%4];" : "=r"(rv[v].x), "=r"(rv[v].y), "=r"(rv[v].z), "=r"(rv[v].w) \
                             : "r"(sb + OFF_L + wg * 5 * SLOT + v * 2048 + wt * 16) : "memory"); \
                if (v >= XE) LDX(v); } } while (0)
        FETCH(0);
        TS(6);
        wg_wait<0>();
        fence_regs64<64>(ac2);
        TS(7);
#pragma unroll
        for (int v0 = 0; v0 < 8; v0 += 2) {
#pragma unroll
            for (int v = v0; v < v0 + 2; v++) {
                const float* a = &ac2[64 + 8 * v];
                stmatrix4t(xrow + XOFF(v),
                           bfma2(bsub2(pack_bf(a[0], a[1]), rv[v].x), gt[4 * v + 0], xr[4 * v + 0]),
                           bfma2(bsub2(pack_bf(a[2], a[3]), rv[v].y), gt[4 * v + 1], xr[4 * v + 1]),
                           bfma2(bsub2(pack_bf(a[4], a[5]), rv[v].z), gt[4 * v + 2], xr[4 * v + 2]),
                           bfma2(bsub2(pack_bf(a[6], a[7]), rv[v].w), gt[4 * v + 3], xr[4 * v + 3]));
            }
            WG_BAR();
            if (wt == 0) mbar_arrive(eL + 4 * v0);
            if (v0 + 2 < 8) FETCH(v0 + 2);
            if (v0 == 0) TS(8);
        }
        TS(9);
    } else {
        asm volatile("setmaxnreg.dec.sync.aligned.u32 %0;" ::"n"(PROD_REGS));
#define XROWS(k) do { mbar_expect_tx(XBAR(k), 8192); bulk_g2s(sb + OFF_S + (k) * 8192, at(P.x, (b * 16 + (k) * 4) * D_ * 2), 8192, XBAR(k)); } while (0)
        if (warp == 12) {
            if (elect_one()) {
                const CUtensorMap* tmD = c ? &tm_dim : &tm_dre;
#pragma unroll 1
                for (int it = 1; it < 4; it++) {
                    while (clock32() - (uint32_t)tstart < LDEL + (it - 1) * LGAP) {}
                    LOAD0(it);
                    if (it >= X0) XROWS(it - X0);
                }
            }
            __syncwarp();
        }
        CLUSTER_WAIT();
        if (warp == 12) {
            if (elect_one()) {
                const CUtensorMap* tmD = c ? &tm_dim : &tm_dre;
#pragma unroll 1
                for (int it = 4; it < 16; it++) {
                    const int s = DSLOT(it);
                    mbar_wait(BAR(B_ES + s), ((it >> 2) & 1) ^ 1);
                    TRACE(it);
                    mbar_expect_tx(BAR(B_FS + s), SLOT);
                    tma_2d(sb + OFF_S + s * SLOT, tmD, it * 64, r * 128, BAR(B_FS + s));
                    if (it < 4 + X0) XROWS(it - X0);
                }
                const unsigned ep = load_epoch(b), e8 = ep & 0xffu;
                const uint8_t* abg = at(AB, grp * 32 * SLOT);
                const unsigned long long* fl = at(g_flag, grp * 128);
                unsigned long long rdy = ld_acquire64(fl);
                mbar_wait(BAR(B_SRD), 0);
                st_release8(at(g_flag, grp * 128 + g), e8);
                PROF_T(7);
                int j = 4;
#pragma unroll 1
                for (int cl = 0; cl < 4; cl++) {
                    if (cl) rdy = ld_acquire64(++fl);
                    fence_async_global();
#pragma unroll 1
                    for (int n = 1; n < 8; n++, j++) {
                        const int q = BLK(n), s = (j & 1) + ((j & 2) ? 0 : 4);
                        const uint32_t fb = BAR(j == 31 ? B_FL + 6 : B_FS + s);
                        if (j == 31) mbar_wait(BAR(B_EL + 6), 0); else mbar_wait(BAR(B_ES + s), ((j >> 2) ^ (j >> 1)) & 1);
                        if (j == 7) mbar_wait(BAR(B_SRD + 1), 0);
                        if (((unsigned)(rdy >> (8 * q)) & 0xffu) != e8) {
                            int m = 0;
                            do { rdy = ld_acquire64(fl); } while (((unsigned)(rdy >> (8 * q)) & 0xffu) != e8 && ++m < SPIN_LIMIT);
                            fence_async_global();
                        }
                        TRACE(16 + j);
                        mbar_expect_tx(fb, SLOT);
                        bulk_g2s(sb + (j == 31 ? OFF_L + 6 * SLOT : OFF_S + s * SLOT), at(abg, (4 * q + KO(cl)) * SLOT), SLOT, fb);
                    }
                }
                *at(g_epoch, b * 4) = ep;
            }
        } else if (warp < 15) {
            if (elect_one()) {
                const int w = warp - 13, row0 = g * 256 + w * 128;
                const CUtensorMap* tmC = c ? &tm_cim : &tm_cre;
                const uint32_t fb = BAR(B_FL + 4 * w), eb = BAR(B_EL + 4 * w), dst = sb + OFF_L + w * 4 * SLOT;
                [[maybe_unused]] unsigned long long mk = 0, mg = 0;
                int n = 0, cl = 0;
#pragma unroll 1
                for (int it = 4; it < 47 - 2 * w; it++) {
                    const int s = it & 3;
                    mbar_wait(eb + 8 * s, ((it >> 2) & 1) ^ 1);
                    TRACE(64 + w * 64 + it - 4);
                    MARK(it);
                    mbar_expect_tx(fb + 8 * s, SLOT);
                    tma_2d(dst + s * SLOT, it < 16 ? &tm_x : tmC, (it < 16 ? it : 4 * (n ? BLK(n) : g) + KO(cl)) * 64, row0, fb + 8 * s);
                    if (it == PTJ) prefetch_tmap(w ? &tm_x64 : tmC);
                    if (it == PTJ && w) prefetch_tmap(&tm_out);
                    if (it >= 16) {
                        if (it == 19) { n = 1; cl = 0; } else if (it < 19) cl++; else if (++n == 8) { n = 1; cl++; }
                    }
                }
#pragma unroll 1
                for (int i = 2 * w; i < 3; i++) {
                    const int s = w ? 1 : i ? i : 3;
                    mbar_wait(eb + 8 * s, w == 0 && i);
                    mbar_expect_tx(fb + 8 * s, SLOT);
                    tma_2d(dst + s * SLOT, tmC, (4 * BLK(5 + i) + 3) * 64, row0 ^ 128, fb + 8 * s);
                }
                if (w && (r & 3) < 2) tma_2d_prefetch(tmC, (4 * BLK(6 + (r & 1)) + 3) * 64, row0);
#pragma unroll 1
                for (int h = 0; h < 4; h++) {
                    mbar_wait(eb + 8 * h, ((w ? 7 : 9) >> h) & 1);
                    fence_async_smem();
                    tma_2d_store(&tm_out, grp * 64, row0 + h * 32, sb + OFF_S + (2 + (h >> 1)) * SLOT + w * 8192 + (h & 1) * 4096);
                    bulk_commit();
                }
                FINISH(w);
            }
        } else {
            const unsigned ep = load_epoch(b);
            uint4 f[4];
            {
                sleep_until((uint32_t)tstart + 6000);
                const uint4* keys = at(reinterpret_cast<const uint4*>(g_key), lane * 16);
                bool mine = false;
                int n = 0;
                do {
                    f[0] = ld_relaxed128(keys); f[1] = ld_relaxed128(keys + 32);
                    if (__all_sync(0xffffffffu, f[0].y == ep && f[0].w == ep && f[1].y == ep && f[1].w == ep)) break;
                    if (!mine) {
                        mbar_wait(BAR(B_LST), 0);
                        const uint4 k = *reinterpret_cast<const uint4*>(smem + OFF_XB);
                        if (lane == 0) st_relaxed64(at(g_key, b * 8), ((unsigned long long)ep << 32) | max(max(k.x, k.y), max(k.z, k.w)));
                        mine = true;
                    }
                    __nanosleep(GSL);
                } while (++n < SPIN_LIMIT);
                const unsigned key = __reduce_max_sync(0xffffffffu, max(max(f[0].x, f[0].z), max(f[1].x, f[1].z)));
                if (lane == 0) { *reinterpret_cast<unsigned*>(smem + OFF_SEL) = key; mbar_arrive(BAR(B_SEL)); PROF_T(8); }
            }
            if (elect_one()) {
#pragma unroll 1
                for (int cl = 0; cl < 4; cl++) {
                    uint8_t* dst = at(AB, (grp * 32 + 4 * g + KO(cl)) * SLOT);
                    const uint32_t src = sb + OFF_S + cl * SLOT, chunk = cl ? 1024 : SLOT;
                    mbar_wait(BAR(B_FS + cl), 0);
                    fence_async_smem();
                    if (cl == 0) PROF_T(3);
                    uint32_t t0 = clock32() + (cl == 1 ? PDEL : 0);
#pragma unroll 1
                    for (uint32_t o = 0; o < SLOT; o += chunk) {
                        sleep_until(t0);
                        bulk_s2g(dst + o, src + o, chunk);
                        bulk_commit();
                        t0 += cl == 1 ? PGAP1 : cl == 2 ? PGAP2 : PGAP3;
                    }
                    bulk_wait<0>();
                    fence_async_global();
                    TRACE(252 + cl);
                    if (cl < 2) mbar_arrive(BAR(B_SRD + cl));
                    else {
                        mbar_wait(BAR(B_ES + cl), 0);
                        mbar_expect_tx(BAR(B_FS + cl), SLOT);
                        tma_2d(src, &tm_x64, grp * 64, g * 256 + (cl - 2) * 64, BAR(B_FS + cl));
                        tma_2d(src + 8192, &tm_x64, grp * 64, g * 256 + (cl - 2) * 64 + 128, BAR(B_FS + cl));
                    }
                    if (cl) st_release8(at(g_flag, grp * 128 + cl * 8 + g), ep & 0xffu);
                    if (cl == 1) PROF_T(5);
                    if (cl == 3) PROF_T(4);
                }
            }
        }
    }
}

typedef CUresult (*EncodeFn)(CUtensorMap*, CUtensorMapDataType, cuuint32_t, void*, const cuuint64_t*, const cuuint64_t*,
                             const cuuint32_t*, const cuuint32_t*, CUtensorMapInterleave, CUtensorMapSwizzle,
                             CUtensorMapL2promotion, CUtensorMapFloatOOBfill);

void make_map(EncodeFn fn, CUtensorMap* tm, const void* p, uint64_t rows, uint64_t cols, uint32_t box_rows) {
    cuuint64_t dims[2] = {cols, rows};
    cuuint64_t strides[1] = {cols * 2};
    cuuint32_t box[2] = {64, box_rows};
    cuuint32_t es[2] = {1, 1};
    fn(tm, CU_TENSOR_MAP_DATA_TYPE_BFLOAT16, 2, const_cast<void*>(p), dims, strides, box, es, CU_TENSOR_MAP_INTERLEAVE_NONE,
       CU_TENSOR_MAP_SWIZZLE_128B, CU_TENSOR_MAP_L2_PROMOTION_L2_128B, CU_TENSOR_MAP_FLOAT_OOB_FILL_NONE);
}

}

extern "C" void kernel_launch(void* const* d_in, const int* in_sizes, int n_in, void* d_out, int out_size) {
    (void)in_sizes; (void)n_in; (void)out_size;
    static EncodeFn fn = nullptr;
    if (!fn) {
        void* p = nullptr;
        cudaDriverEntryPointQueryResult q;
        cudaGetDriverEntryPoint("cuTensorMapEncodeTiled", &p, cudaEnableDefault, &q);
        fn = (EncodeFn)p;
        cudaFuncSetAttribute(fnet_fused_kernel, cudaFuncAttributeMaxDynamicSharedMemorySize, SMEM_BYTES);
    }
    CUtensorMap tx, tdre, tdim, tcre, tcim, tout, tx64;
    make_map(fn, &tx, d_in[0], S_, D_, 128);
    make_map(fn, &tcre, d_in[1], S_, S_, 128);
    make_map(fn, &tcim, d_in[2], S_, S_, 128);
    make_map(fn, &tdre, d_in[3], D_, D_, 128);
    make_map(fn, &tdim, d_in[4], D_, D_, 128);
    make_map(fn, &tx64, d_in[0], S_, D_, 64);
    make_map(fn, &tout, d_out, S_, D_, 32);
    Params P;
    P.x = (const __nv_bfloat16*)d_in[0];
    P.dre = (const __nv_bfloat16*)d_in[3];
    P.dim = (const __nv_bfloat16*)d_in[4];
    P.wr = (const __nv_bfloat16*)d_in[6];
    P.wg = (const __nv_bfloat16*)d_in[7];
    P.wu = (const __nv_bfloat16*)d_in[8];
    P.wd = (const __nv_bfloat16*)d_in[9];
    P.zero = 0;
    fnet_fused_kernel<<<NCTA, NTHREADS, SMEM_BYTES, cudaStreamPerThread>>>(tx, tdre, tdim, tcre, tcim, tout, tx64, P);
}
```

```cpp
#include <cuda_runtime.h>
#include <cuda_bf16.h>
#include <cuda.h>
#include <stdint.h>

#define GSL 200
#define SLEEP_NS 200
#define PDEL 1000
#define PGAP1 200
#define PGAP2 200
#define PGAP3 240
#define GOJ 2
#define LDEL 1400
#define LGAP 700
#define PTJ 10
#define X0 2
#define KQ 5
#define XE 2
#define PROD_REGS 32
#define CONS_REGS 184

namespace {

constexpr int S_ = 2048, D_ = 1024, F_ = 3584;
constexpr int NCTA = 128;
constexpr int XJ = 20;
constexpr uint32_t SLOT = 16384;
constexpr uint32_t OFF_L = 0;
constexpr uint32_t OFF_S = 8 * SLOT;
constexpr uint32_t OFF_RS = OFF_S + SLOT;
constexpr uint32_t OFF_BAR = 14 * SLOT;
constexpr uint32_t OFF_SEL = OFF_BAR + 360;
constexpr uint32_t OFF_RSTD = OFF_BAR + 384;
constexpr uint32_t OFF_MEAN = OFF_RSTD + 1024;
constexpr uint32_t OFF_XB = OFF_MEAN + 512;
constexpr uint32_t OFF_H = OFF_XB + 1024;
constexpr uint32_t SMEM_BYTES = OFF_H + 128;
constexpr uint32_t SB0 = 1024;
constexpr int NTHREADS = 512;
static_assert(SMEM_BYTES <= 232448, "smem");

enum { B_FS = 0, B_ES = 6, B_FL = 12, B_EL = 20, B_SRD = 28, B_RECV = 30  , B_RDY = 34, B_STATS = 36, B_LST = 37, B_UPD = 38,
       B_QUIET = 39, B_GO = 40, B_PEER = 41, B_SEL = 42, B_H = 43, B_COUNT = 44 };
static_assert(B_COUNT * 8 <= 360, "barriers");

__device__ __align__(1024) uint8_t g_ab[16u * 32u * SLOT];
__device__ __align__(128) uint4 g_part[56 * (D_ / 4)];
__device__ __align__(128) uint4 g_stat[S_];
__device__ __align__(128) uint4 g_rs[D_];
__device__ __align__(128) unsigned long long g_key[NCTA];
__device__ __align__(128) unsigned long long g_flag[16 * 16];
__device__ __align__(128) unsigned g_epoch[NCTA];
#define PROF_T(i) do {} while (0)
#define TRACE(i) do {} while (0)
#define PROF_G(i) do {} while (0)
#define TS(i) do {} while (0)
#define FINISH(wg) bulk_wait_read<0>()

#define MARK(it) do {} while (0)

__device__ __forceinline__ uint32_t smem_u32(const void* p) { return (uint32_t)__cvta_generic_to_shared(p); }
__device__ __forceinline__ void mbar_init(uint32_t bar, uint32_t cnt) {
    asm volatile("mbarrier.init.shared::cta.b64 [%0], %1;" ::"r"(bar), "r"(cnt) : "memory");
}
__device__ __forceinline__ bool mbar_try(uint32_t bar, uint32_t parity) {
    uint32_t ok;
    asm volatile("{\n.reg .pred p;\nmbarrier.try_wait.parity.shared::cta.b64 p, [%1], %2;\nselp.u32 %0, 1, 0, p;\n}"
                 : "=r"(ok) : "r"(bar), "r"(parity) : "memory");
    return ok;
}
__device__ __forceinline__ bool mbar_test(uint32_t bar, uint32_t parity) {
    uint32_t ok;
    asm volatile("{\n.reg .pred p;\nmbarrier.test_wait.parity.shared::cta.b64 p, [%1], %2;\nselp.u32 %0, 1, 0, p;\n}"
                 : "=r"(ok) : "r"(bar), "r"(parity) : "memory");
    return ok;
}
__device__ __forceinline__ bool mbar_try_cluster(uint32_t bar, uint32_t parity) {
    uint32_t ok;
    asm volatile("{\n.reg .pred p;\nmbarrier.try_wait.parity.acquire.cluster.shared::cta.b64 p, [%1], %2;\nselp.u32 %0, 1, 0, p;\n}"
                 : "=r"(ok) : "r"(bar), "r"(parity) : "memory");
    return ok;
}
constexpr int SPIN_LIMIT = 1 << 20;
__device__ __forceinline__ void mbar_wait(uint32_t bar, uint32_t parity) {
    if (mbar_try(bar, parity)) return;
    int n = 0;
    while (!mbar_try(bar, parity) && ++n < SPIN_LIMIT) {}
}
__device__ __forceinline__ void mbar_wait_cluster(uint32_t bar, uint32_t parity) {
    int n = 0;
    while (!mbar_try_cluster(bar, parity) && ++n < SPIN_LIMIT) {}
}
__device__ __forceinline__ void mbar_wait_sleep(uint32_t bar, uint32_t parity) {
    int n = 0;
    while (!mbar_try(bar, parity) && ++n < SPIN_LIMIT) __nanosleep(SLEEP_NS);
}
__device__ __forceinline__ void mbar_arrive(uint32_t bar) {
    asm volatile("mbarrier.arrive.shared::cta.b64 _, [%0];" ::"r"(bar) : "memory");
}
__device__ __forceinline__ void mbar_arrive_cluster(uint32_t cluster_bar) {
    asm volatile("mbarrier.arrive.shared::cluster.b64 _, [%0];" ::"r"(cluster_bar) : "memory");
}
__device__ __forceinline__ void mbar_expect_tx(uint32_t bar, uint32_t bytes) {
    asm volatile("mbarrier.arrive.expect_tx.shared::cta.b64 _, [%0], %1;" ::"r"(bar), "r"(bytes) : "memory");
}
__device__ __forceinline__ bool elect_one() {
    uint32_t p;
    asm volatile("{\n.reg .pred p;\nelect.sync _|p, 0xffffffff;\nselp.u32 %0, 1, 0, p;\n}" : "=r"(p));
    return p;
}
__device__ __forceinline__ uint32_t mapa(uint32_t addr, uint32_t rank) {
    uint32_t r;
    asm("mapa.shared::cluster.u32 %0, %1, %2;" : "=r"(r) : "r"(addr), "r"(rank));
    return r;
}
__device__ __forceinline__ uint32_t clock32() { uint32_t t; asm volatile("mov.u32 %0, %%clock;" : "=r"(t)); return t; }
__device__ __forceinline__ void sleep_until(uint32_t t) {
    int n = 0;
    while ((int)(clock32() - t) < 0 && ++n < SPIN_LIMIT) __nanosleep(20);
}
__device__ __forceinline__ void yield(float last, uint32_t zero) {
    asm volatile("nanosleep.u32 %0;" ::"r"(__float_as_uint(last) & zero));
}
template <typename T> __device__ __forceinline__ T* at(T* p, uint32_t bytes) {
    asm("" : "+r"(bytes));
    return reinterpret_cast<T*>(reinterpret_cast<uintptr_t>(p) + bytes);
}
__device__ __forceinline__ void tma_2d(uint32_t dst, const CUtensorMap* tm, int c0, int c1, uint32_t bar) {
    asm volatile("cp.async.bulk.tensor.2d.shared::cluster.global.mbarrier::complete_tx::bytes [%0], [%1, {%3, %4}], [%2];"
                 ::"r"(dst), "l"(tm), "r"(bar), "r"(c0), "r"(c1) : "memory");
}
__device__ __forceinline__ void tma_2d_prefetch(const CUtensorMap* tm, int c0, int c1) {
    asm volatile("cp.async.bulk.prefetch.tensor.2d.L2.global [%0, {%1, %2}];" ::"l"(tm), "r"(c0), "r"(c1) : "memory");
}
__device__ __forceinline__ void tma_2d_store(const CUtensorMap* tm, int c0, int c1, uint32_t src) {
    asm volatile("cp.async.bulk.tensor.2d.global.shared::cta.bulk_group [%0, {%2, %3}], [%1];"
                 ::"l"(tm), "r"(src), "r"(c0), "r"(c1) : "memory");
}
__device__ __forceinline__ void bulk_g2s(uint32_t dst, const void* src, uint32_t bytes, uint32_t bar) {
    asm volatile("cp.async.bulk.shared::cluster.global.mbarrier::complete_tx::bytes [%0], [%1], %2, [%3];"
                 ::"r"(dst), "l"(src), "r"(bytes), "r"(bar) : "memory");
}
__device__ __forceinline__ void bulk_s2g(void* dst, uint32_t src, uint32_t bytes) {
    asm volatile("cp.async.bulk.global.shared::cta.bulk_group [%0], [%1], %2;" ::"l"(dst), "r"(src), "r"(bytes) : "memory");
}
__device__ __forceinline__ void st_async4(uint32_t dst, uint32_t a, uint32_t b, uint32_t c, uint32_t d, uint32_t bar) {
    asm volatile("st.async.weak.shared::cluster.mbarrier::complete_tx::bytes.v4.b32 [%0], {%1,%2,%3,%4}, [%5];"
                 ::"r"(dst), "r"(a), "r"(b), "r"(c), "r"(d), "r"(bar) : "memory");
}
__device__ __forceinline__ void bulk_commit() { asm volatile("cp.async.bulk.commit_group;" ::: "memory"); }
template <int N> __device__ __forceinline__ void bulk_wait_read() { asm volatile("cp.async.bulk.wait_group.read %0;" ::"n"(N) : "memory"); }
template <int N> __device__ __forceinline__ void bulk_wait() { asm volatile("cp.async.bulk.wait_group %0;" ::"n"(N) : "memory"); }
__device__ __forceinline__ void fence_async_smem() { asm volatile("fence.proxy.async.shared::cta;" ::: "memory"); }
__device__ __forceinline__ void fence_async_global() { asm volatile("fence.proxy.async.global;" ::: "memory"); }
__device__ __forceinline__ void prefetch_tmap(const CUtensorMap* tm) {
    asm volatile("prefetch.tensormap [%0];" ::"l"(tm) : "memory");
}
__device__ __forceinline__ unsigned long long ld_acquire64(const unsigned long long* p) {
    unsigned long long v; asm volatile("ld.acquire.gpu.global.u64 %0, [%1];" : "=l"(v) : "l"(p) : "memory"); return v;
}
__device__ __forceinline__ unsigned load_epoch(int b) {
    unsigned v; asm volatile("ld.global.u32 %0, [%1];" : "=r"(v) : "l"(at(g_epoch, b * 4)) : "memory"); return v + 1;
}
__device__ __forceinline__ unsigned ld_relaxed(const void* p) {
    unsigned v; asm volatile("ld.relaxed.gpu.global.u32 %0, [%1];" : "=r"(v) : "l"(p) : "memory"); return v;
}
__device__ __forceinline__ uint4 ld_relaxed128(const uint4* p) {
    uint4 v;
    asm volatile("{\n.reg .b128 t;\n.reg .b64 lo, hi;\nld.relaxed.gpu.global.b128 t, [%4];\nmov.b128 {lo, hi}, t;\n"
                 "mov.b64 {%0, %1}, lo;\nmov.b64 {%2, %3}, hi;\n}"
                 : "=r"(v.x), "=r"(v.y), "=r"(v.z), "=r"(v.w) : "l"(p) : "memory");
    return v;
}
__device__ __forceinline__ void st_relaxed128(uint4* p, const uint4& v) {
    asm volatile("{\n.reg .b128 t;\n.reg .b64 lo, hi;\nmov.b64 lo, {%1, %2};\nmov.b64 hi, {%3, %4};\nmov.b128 t, {lo, hi};\n"
                 "st.relaxed.gpu.global.b128 [%0], t;\n}"
                 ::"l"(p), "r"(v.x), "r"(v.y), "r"(v.z), "r"(v.w) : "memory");
}
__device__ __forceinline__ void st_relaxed64(unsigned long long* p, unsigned long long v) {
    asm volatile("st.relaxed.gpu.global.u64 [%0], %1;" ::"l"(p), "l"(v) : "memory");
}
__device__ __forceinline__ void st_release8(void* p, unsigned v) {
    asm volatile("st.release.gpu.global.u8 [%0], %1;" ::"l"(p), "r"(v) : "memory");
}
__device__ __forceinline__ uint64_t policy_evict_first() {
    uint64_t pol;
    asm("createpolicy.fractional.L2::evict_first.b64 %0, 1.0;" : "=l"(pol));
    return pol;
}
__device__ __forceinline__ uint4 ldg_stream(const void* p, uint64_t pol) {
    uint4 v;
    asm volatile("ld.global.nc.L1::no_allocate.L2::cache_hint.v4.u32 {%0,%1,%2,%3}, [%4], %5;"
                 : "=r"(v.x), "=r"(v.y), "=r"(v.z), "=r"(v.w) : "l"(p), "l"(pol));
    return v;
}
__device__ __forceinline__ uint4 ldg_stream_ord(const void* p, uint64_t pol) {
    uint4 v;
    asm volatile("ld.relaxed.gpu.global.L1::no_allocate.L2::cache_hint.v4.u32 {%0,%1,%2,%3}, [%4], %5;"
                 : "=r"(v.x), "=r"(v.y), "=r"(v.z), "=r"(v.w) : "l"(p), "l"(pol) : "memory");
    return v;
}
template <int ID, int N> __device__ __forceinline__ void named_arrive() { asm volatile("bar.arrive %0, %1;" ::"n"(ID), "n"(N) : "memory"); }
template <int ID, int N> __device__ __forceinline__ void named_bar() { asm volatile("bar.sync %0, %1;" ::"n"(ID), "n"(N) : "memory"); }

__device__ __forceinline__ float bf_lo(uint32_t u) { return __uint_as_float(u << 16); }
__device__ __forceinline__ float bf_hi(uint32_t u) { return __uint_as_float(u & 0xffff0000u); }
__device__ __forceinline__ uint32_t pack_bf(float lo, float hi) {
    uint32_t r; asm("cvt.rn.bf16x2.f32 %0, %1, %2;" : "=r"(r) : "f"(hi), "f"(lo)); return r;
}
__device__ __forceinline__ float rbf(float v) { return __uint_as_float(pack_bf(0.f, v)); }
__device__ __forceinline__ float sqrt_f(float v) { float r; asm("sqrt.approx.f32 %0, %1;" : "=f"(r) : "f"(v)); return r; }
__device__ __forceinline__ float rcp_f(float v) { float r; asm("rcp.approx.f32 %0, %1;" : "=f"(r) : "f"(v)); return r; }
__device__ __forceinline__ float silu_f(float z) { return __fdividef(z, 1.0f + __expf(-z)); }
__device__ __forceinline__ uint32_t bsub2(uint32_t a, uint32_t b) {
    uint32_t r; asm("sub.rn.bf16x2 %0, %1, %2;" : "=r"(r) : "r"(a), "r"(b)); return r;
}
__device__ __forceinline__ uint32_t bfma2(uint32_t a, uint32_t b, uint32_t c) {
    uint32_t r; asm("fma.rn.bf16x2 %0, %1, %2, %3;" : "=r"(r) : "r"(a), "r"(b), "r"(c)); return r;
}
__device__ __forceinline__ uint32_t norm2(uint32_t xv, float m, float rinv) {
    uint32_t t = pack_bf(bf_lo(xv) - m, bf_hi(xv) - m);
    return pack_bf(bf_lo(t) * rinv, bf_hi(t) * rinv);
}
__device__ __forceinline__ float gate1(float z) {
    float t;
    const float h = 0.5f * z;
    asm("tanh.approx.f32 %0, %1;" : "=f"(t) : "f"(h));
    return fmaf(h, t, h);
}
__device__ __forceinline__ uint32_t gate2(uint32_t xv, uint32_t mean2, float r0, float r1) {
    const uint32_t t = bsub2(xv, mean2);
    return pack_bf(gate1(bf_lo(t) * r0), gate1(bf_hi(t) * r1));
}
__device__ __forceinline__ uint32_t silu2(uint32_t z) { return pack_bf(silu_f(bf_lo(z)), silu_f(bf_hi(z))); }

__device__ __forceinline__ void stmatrix4(uint32_t addr, uint32_t r0, uint32_t r1, uint32_t r2, uint32_t r3) {
    asm volatile("stmatrix.sync.aligned.m8n8.x4.shared.b16 [%0], {%1,%2,%3,%4};"
                 ::"r"(addr), "r"(r0), "r"(r1), "r"(r2), "r"(r3));
}
__device__ __forceinline__ void stmatrix4t(uint32_t addr, uint32_t r0, uint32_t r1, uint32_t r2, uint32_t r3) {
    asm volatile("stmatrix.sync.aligned.m8n8.x4.trans.shared.b16 [%0], {%1,%2,%3,%4};"
                 ::"r"(addr), "r"(r0), "r"(r1), "r"(r2), "r"(r3));
}
__device__ __forceinline__ void ldmatrix4t(uint32_t addr, uint32_t& r0, uint32_t& r1, uint32_t& r2, uint32_t& r3) {
    asm volatile("ldmatrix.sync.aligned.m8n8.x4.trans.shared.b16 {%0,%1,%2,%3}, [%4];"
                 : "=r"(r0), "=r"(r1), "=r"(r2), "=r"(r3) : "r"(addr));
}

__device__ __forceinline__ void wg_fence() { asm volatile("wgmma.fence.sync.aligned;" ::: "memory"); }
__device__ __forceinline__ void wg_commit() { asm volatile("wgmma.commit_group.sync.aligned;" ::: "memory"); }
template <int N> __device__ __forceinline__ void wg_wait() { asm volatile("wgmma.wait_group.sync.aligned %0;" ::"n"(N) : "memory"); }

__host__ __device__ constexpr uint32_t desc_lo(uint32_t addr, uint32_t lbo) { return ((addr & 0x3FFFF) >> 4) | ((lbo >> 4) << 16); }
#define DESC_HI "0x40000040"

#define R8(a, o) "+f"(a[(o) + 0]), "+f"(a[(o) + 1]), "+f"(a[(o) + 2]), "+f"(a[(o) + 3]), \
                 "+f"(a[(o) + 4]), "+f"(a[(o) + 5]), "+f"(a[(o) + 6]), "+f"(a[(o) + 7])
#define R64(a, o) R8(a, (o) + 0), R8(a, (o) + 8), R8(a, (o) + 16), R8(a, (o) + 24), \
                  R8(a, (o) + 32), R8(a, (o) + 40), R8(a, (o) + 48), R8(a, (o) + 56)

template <int O, int TA>
__device__ __forceinline__ void wgmma128(float (&a)[128], uint32_t da, uint32_t db, int scale_d) {
    asm volatile(
        "{\n.reg .pred p;\n.reg .b64 da, db;\nsetp.ne.b32 p, %66, 0;\n"
        "mov.b64 da, {%64, " DESC_HI "};\nmov.b64 db, {%65, " DESC_HI "};\n"
        "wgmma.mma_async.sync.aligned.m64n128k16.f32.bf16.bf16 "
        "{%0,%1,%2,%3,%4,%5,%6,%7,%8,%9,%10,%11,%12,%13,%14,%15,"
        "%16,%17,%18,%19,%20,%21,%22,%23,%24,%25,%26,%27,%28,%29,%30,%31,"
        "%32,%33,%34,%35,%36,%37,%38,%39,%40,%41,%42,%43,%44,%45,%46,%47,"
        "%48,%49,%50,%51,%52,%53,%54,%55,%56,%57,%58,%59,%60,%61,%62,%63},"
        "da, db, p, 1, 1, %67, 0;\n}"
        : R64(a, O)
        : "r"(da), "r"(db), "r"(scale_d), "n"(TA));
}
template <int O>
__device__ __forceinline__ void wgmma128_rs(float (&a)[128], const uint32_t* f, uint32_t db) {
    asm volatile(
        "{\n.reg .b64 db;\nmov.b64 db, {%68, 8};\n"
        "wgmma.mma_async.sync.aligned.m64n128k16.f32.bf16.bf16 "
        "{%0,%1,%2,%3,%4,%5,%6,%7,%8,%9,%10,%11,%12,%13,%14,%15,"
        "%16,%17,%18,%19,%20,%21,%22,%23,%24,%25,%26,%27,%28,%29,%30,%31,"
        "%32,%33,%34,%35,%36,%37,%38,%39,%40,%41,%42,%43,%44,%45,%46,%47,"
        "%48,%49,%50,%51,%52,%53,%54,%55,%56,%57,%58,%59,%60,%61,%62,%63},"
        "{%64, %65, %66, %67}, db, 1, 1, 1, 0;\n}"
        : R64(a, O)
        : "r"(f[0]), "r"(f[1]), "r"(f[2]), "r"(f[3]), "r"(db));
}
template <int O>
__device__ __forceinline__ void fence_regs64(float (&a)[128]) {
    asm volatile("" : R64(a, O)::"memory");
}

struct Params {
    const __nv_bfloat16* x;
    const __nv_bfloat16* dre;
    const __nv_bfloat16* dim;
    const __nv_bfloat16* wr;
    const __nv_bfloat16* wg;
    const __nv_bfloat16* wu;
    const __nv_bfloat16* wd;
    uint32_t zero;
#define AB g_ab
};

__device__ __forceinline__ float warp_sum(float v) {
#pragma unroll
    for (int o = 16; o; o >>= 1) v += __shfl_xor_sync(0xffffffffu, v, o);
    return v;
}
__device__ __forceinline__ void fma8(float* acc, const uint4& w, float s) {
    acc[0] += s * bf_lo(w.x); acc[1] += s * bf_hi(w.x); acc[2] += s * bf_lo(w.y); acc[3] += s * bf_hi(w.y);
    acc[4] += s * bf_lo(w.z); acc[5] += s * bf_hi(w.z); acc[6] += s * bf_lo(w.w); acc[7] += s * bf_hi(w.w);
}
__device__ __forceinline__ int POS(int t) { return (t & ~15) | ((t & 6) << 1) | ((t & 8) >> 2) | (t & 1); }
__host__ __device__ constexpr int PSLOT(int j) { return j < 4 ? j : (j & 1) + ((j & 2) ? 0 : 4); }
__host__ __device__ constexpr int PPAR(int j) { return j < 4 ? 0 : ((j >> 2) ^ (j >> 1) ^ 1) & 1; }
__host__ __device__ constexpr int DSLOT(int it) { return (it & 3) + 2; }
__device__ __forceinline__ int SREC(int t) { return (t & ~15) | ((t & 3) << 2) | ((t >> 2) & 3); }
__device__ __forceinline__ int KO(int cl) { return ((cl & 1) << 1) | (cl >> 1); }

__global__ void __cluster_dims__(2, 1, 1) __launch_bounds__(NTHREADS, 1)
fnet_fused_kernel(const __grid_constant__ CUtensorMap tm_x, const __grid_constant__ CUtensorMap tm_dre,
                  const __grid_constant__ CUtensorMap tm_dim, const __grid_constant__ CUtensorMap tm_cre,
                  const __grid_constant__ CUtensorMap tm_cim, const __grid_constant__ CUtensorMap tm_out,
                  const __grid_constant__ CUtensorMap tm_x64,
                  const Params P) {
    extern __shared__ __align__(1024) uint8_t smem[];
    const unsigned long long tstart = clock64();
    const uint32_t sb = smem_u32(smem);
    const int tid = threadIdx.x, lane = tid & 31;
    const int pr = blockIdx.x >> 1, p7 = ((pr - 36) * 37) >> 8;
    const int c = blockIdx.x & 1;
    const bool upper = pr >= 36;
    const int col = upper ? pr - 36 - 7 * p7 + 8 : pr < 4 ? 15 : (pr - 4) & 7;
    const int gi = (int)(0x7eca8531fdb96420ull >> (4 * col)) & 15;
    const int g = gi & 7;
    const int r = (gi >> 3) * 4 + (upper ? p7 : pr < 4 ? pr : (pr - 4) >> 3);
#define BLK(n) ((n) - ((n) <= g))
    const int grp = 2 * r + c;
    const int b = g * 16 + grp;
    const uint32_t bar0 = sb + OFF_BAR;
    const uint32_t zero = P.zero;
#define BAR(i) (bar0 + 8u * (i))
#define XBAR(i) (sb + OFF_XB + 64 + 8u * (i))
#define CLUSTER_ARRIVE() asm volatile("barrier.cluster.arrive.relaxed.aligned;" ::: "memory")
#define CLUSTER_WAIT() asm volatile("barrier.cluster.wait.aligned;" ::: "memory")

#define LOAD0(it) do { \
            mbar_expect_tx(BAR(B_FS + DSLOT(it)), SLOT); tma_2d(sb + OFF_S + DSLOT(it) * SLOT, tmD, (it) * 64, r * 128, BAR(B_FS + DSLOT(it))); \
            mbar_expect_tx(BAR(B_FL + (it)), SLOT); tma_2d(sb + OFF_L + (it) * SLOT, &tm_x, (it) * 64, g * 256, BAR(B_FL + (it))); \
            mbar_expect_tx(BAR(B_FL + 4 + (it)), SLOT); tma_2d(sb + OFF_L + (4 + (it)) * SLOT, &tm_x, (it) * 64, g * 256 + 128, BAR(B_FL + 4 + (it))); \
        } while (0)
    if (tid < 32) {
        if (elect_one()) {
            const CUtensorMap* tmD = c ? &tm_dim : &tm_dre;
            prefetch_tmap(tmD); prefetch_tmap(&tm_x);
            mbar_init(BAR(B_FS + 2), 1); mbar_init(BAR(B_FL), 1); mbar_init(BAR(B_FL + 4), 1);
            asm volatile("fence.mbarrier_init.release.cluster;" ::: "memory");
            LOAD0(0);
        }
        __syncwarp();
    }
    const int warp = __shfl_sync(0xffffffffu, tid >> 5, 0);
    if (warp == 12) {
        if (elect_one()) {
#pragma unroll
            for (int i = 1; i < 4; i++) { mbar_init(BAR(B_FS + 2 + i), 1); mbar_init(BAR(B_FL + i), 1); mbar_init(BAR(B_FL + 4 + i), 1); }
#pragma unroll
            for (int i = 0; i < 4; i++) mbar_init(XBAR(i), 1);
            asm volatile("fence.mbarrier_init.release.cluster;" ::: "memory");
        }
        __syncwarp();
    }
    if (warp == 14) {
        if (elect_one()) {
#pragma unroll
            for (int i = 0; i < 8; i++) { mbar_init(BAR(B_EL + i), 1); mbar_init(XBAR(4 + i), 1); if (i < 6) mbar_init(BAR(B_ES + i), 2); }
            asm volatile("fence.mbarrier_init.release.cluster;" ::: "memory");
        }
        __syncwarp();
    }
    if (warp == 15) {
        if (elect_one()) {
            mbar_init(BAR(B_FS), 1); mbar_init(BAR(B_FS + 1), 1);
#pragma unroll
            for (int i = B_SRD; i < B_COUNT; i++) mbar_init(BAR(i), i == B_GO ? 2 : i == B_STATS || i == B_LST ? 4 : 1);
#pragma unroll
            for (int i = 0; i < 4; i++) mbar_expect_tx(BAR(B_RECV + i), SLOT / 2);
            mbar_expect_tx(BAR(B_PEER), 1024); mbar_expect_tx(BAR(B_H), 128);
            asm volatile("fence.mbarrier_init.release.cluster;" ::: "memory");
        }
        __syncwarp();
    }
    CLUSTER_ARRIVE();
    if ((sb & 0xffffffu) != SB0) return;

#define GATHER(ptr, cnt, valid) do { int n = 0; bool ok; _Pragma("unroll 1") do { ok = true; \
                _Pragma("unroll") for (int i = 0; i < (cnt); i++) { f[i] = ld_relaxed128((ptr) + i * 32); ok = ok && (valid); } \
                if (__all_sync(0xffffffffu, ok)) break; \
                __nanosleep(GSL); \
            } while (++n < SPIN_LIMIT); } while (0)
    if (warp >= 8 && warp < 12) {
        asm volatile("setmaxnreg.dec.sync.aligned.u32 %0;" ::"n"(512 - PROD_REGS - 2 * CONS_REGS));
        const int aw = warp - 8, mt = tid - 256;
        unsigned ep;
        {
            const uint8_t* rp = smem + OFF_S + aw * 2048 + lane * 16;
            const __nv_bfloat16* dp = at(c ? P.dim : P.dre, (r * 128 + g * 16 + aw * 4) * D_ * 2);
            float wf[32], sw = 0.f;
#pragma unroll
            for (int i = 0; i < 4; i++) {
                const uint4 w = __ldg(reinterpret_cast<const uint4*>(at(P.wr, lane * 16) + i * 256));
                const uint32_t wv[4] = {w.x, w.y, w.z, w.w};
#pragma unroll
                for (int e = 0; e < 4; e++) { wf[8 * i + 2 * e] = bf_lo(wv[e]); wf[8 * i + 2 * e + 1] = bf_hi(wv[e]); sw = (sw + bf_lo(wv[e])) + bf_hi(wv[e]); }
            }
            ep = load_epoch(b);
            sw = warp_sum(sw);
            CLUSTER_WAIT();
            float x0[4] = {}, s1[4] = {}, s2[4] = {}, sx[4] = {}, sd[4] = {};
#define PUSH(a, v) do { a[0] = a[1]; a[1] = a[2]; a[2] = a[3]; a[3] = v; } while (0)
#pragma unroll 1
            for (int k = 0; k < 4; k++) {
                mbar_wait(XBAR(k), 0);
                uint4 v[4];
#pragma unroll
                for (int i = 0; i < 4; i++) v[i] = *reinterpret_cast<const uint4*>(rp + k * 8192 + i * 512);
                uint32_t sh = v[0].x << 16;
                float a1s = 0.f, a2s = 0.f, axs = 0.f;
#pragma unroll
                for (int i = 0; i < 4; i++) {
                    sh = __shfl_sync(0xffffffffu, sh | (__float_as_uint(axs) & zero), 0);
                    const uint32_t xv[4] = {v[i].x, v[i].y, v[i].z, v[i].w};
#pragma unroll
                    for (int e = 0; e < 4; e++) {
                        const float a0 = bf_lo(xv[e]) - __uint_as_float(sh), a1 = bf_hi(xv[e]) - __uint_as_float(sh);
                        a1s += a0 + a1;
                        a2s = fmaf(a0, a0, fmaf(a1, a1, a2s));
                        axs = fmaf(a0, wf[8 * i + 2 * e], fmaf(a1, wf[8 * i + 2 * e + 1], axs));
                    }
                }
                PUSH(x0, __uint_as_float(sh)); PUSH(s1, a1s); PUSH(s2, a2s); PUSH(sx, axs);
                fence_async_smem();
                __syncwarp();
                if (elect_one()) {
                    const uint32_t db = XBAR(k == 3 ? 8 + aw : 4 + aw);
                    if (k == 0 || k == 3) mbar_expect_tx(db, k ? 2048 : 6144);
                    bulk_g2s(sb + OFF_S + k * 8192 + aw * 2048, dp + k * D_, 2048, db);
                }
            }
#define FOLD4(a) do { const bool u16 = lane & 16, u8 = lane & 8; \
                float p0 = (u16 ? a[2] : a[0]) + __shfl_xor_sync(0xffffffffu, u16 ? a[0] : a[2], 16); \
                float p1 = (u16 ? a[3] : a[1]) + __shfl_xor_sync(0xffffffffu, u16 ? a[1] : a[3], 16); \
                a[0] = (u8 ? p1 : p0) + __shfl_xor_sync(0xffffffffu, u8 ? p0 : p1, 8); \
                _Pragma("unroll") for (int o = 4; o; o >>= 1) a[0] += __shfl_xor_sync(0xffffffffu, a[0], o); } while (0)
#pragma unroll 1
            for (int k = 0; k < 4; k++) {
                mbar_wait(XBAR(k == 3 ? 8 + aw : 4 + aw), 0);
                float run = 0.f;
#pragma unroll
                for (int i = 0; i < 4; i++) {
                    const uint4 v = *reinterpret_cast<const uint4*>(rp + k * 8192 + i * 512);
                    const uint32_t dv[4] = {v.x, v.y, v.z, v.w};
#pragma unroll
                    for (int e = 0; e < 4; e++) run += bf_lo(dv[e]) + bf_hi(dv[e]);
                }
                PUSH(sd, run);
            }
            named_bar<4, 128>();
            if (mt < 12) asm volatile("mbarrier.inval.shared::cta.b64 [%0];" ::"r"(XBAR(mt)) : "memory");
            FOLD4(sd); FOLD4(s1); FOLD4(s2); FOLD4(sx);
            const float nb = __shfl_down_sync(0xffffffffu, sd[0], 8);
            if ((lane & 15) == 0)
                st_relaxed128(at(g_rs, (grp * 64 + g * 8 + aw * 2 + (lane >> 4)) * 16), make_uint4(__float_as_uint(sd[0]), ep, __float_as_uint(nb), ep));
            if (mt == 0) PROF_T(6);
            const int rr = lane >> 3;
            const float c0 = rr == 0 ? x0[0] : rr == 1 ? x0[1] : rr == 2 ? x0[2] : x0[3];
            const float dm = s1[0] * (1.0f / D_);
            const float mb = rbf(c0 + dm);
            const float rinv = rcp_f(rbf(sqrt_f(rbf(rbf(fmaxf(s2[0] * (1.0f / D_) - dm * dm, 0.f)) + 1e-5f))));
            if ((lane & 7) == 0) st_relaxed128(at(g_stat, (b * 16 + aw * 4 + rr) * 16), make_uint4(__float_as_uint(mb), __float_as_uint(rinv), ep, 0));
            unsigned u = __bfloat16_as_ushort(__float2bfloat16_rn((sx[0] + (c0 - mb) * sw) * rinv));
            u = (u & 0x8000u) ? (~u & 0xffffu) : (u | 0x8000u);
            u = (u << 16) | (0xffffu - (unsigned)(b * 16 + rr * 4 + aw));
            u = __reduce_max_sync(0xffffffffu, u);
            if (lane == 0) { *reinterpret_cast<unsigned*>(smem + OFF_XB + aw * 4) = u; mbar_arrive(BAR(B_LST)); }
            if (mt == 0) PROF_T(2);
            uint4 f[4];
            if (aw < 2) {
                const int t = SREC(aw * 128 + lane);
                GATHER(at(g_stat, (g * 256 + aw * 128 + lane) * 16), 4, f[i].z == ep);
#pragma unroll
                for (int i = 0; i < 4; i++) {
                    *reinterpret_cast<uint32_t*>(smem + OFF_RSTD + (POS(t) + i * 32) * 4) = f[i].y;
                    *reinterpret_cast<uint16_t*>(smem + OFF_MEAN + (POS(t) + i * 32) * 2) = (uint16_t)(f[i].x >> 16);
                }
            } else {
                const int e2 = (aw - 2) * 32 + lane;
                GATHER(at(g_rs, (grp * 64 + e2) * 16), 1, f[i].y == ep && f[i].w == ep);
#pragma unroll
                for (int i = 0; i < 2; i++) {
                    const float v = __uint_as_float(i ? f[0].z : f[0].x);
                    const float hi = rbf(v), mid = rbf(v - hi), lo = v - hi - mid;
                    *reinterpret_cast<uint4*>(smem + OFF_RS + (e2 * 2 + i) * 16) = make_uint4(pack_bf(hi, mid), pack_bf(lo, 0.f), 0, 0);
                }
            }
            fence_async_smem();
            __syncwarp();
            if (lane == 0) mbar_arrive(BAR(B_STATS));
            if (mt == 127) PROF_T(9);
        }
        const bool moe = pr < 28 || pr >= 36;
        const int pair = pr < 28 ? pr : pr - 8;
        if (moe) {
            const uint64_t pol = policy_evict_first();
            const __nv_bfloat16* wp = at((aw & 1) ? P.wu : P.wg, ((c * 512 + (aw >> 1) * 256 + (lane >> 3) * 8) * F_ + pair * 64 + (lane & 7) * 8) * 2);
            uint4 b0[8], b1[8];
#define FILL(buf, str) do { _Pragma("unroll") for (int q = 0; q < 8; q++) buf[q] = ldg_stream(wp + q * (str), pol); } while (0)
#define PAUSE() do { if (mbar_test(BAR(B_QUIET), 0)) mbar_wait_sleep(BAR(B_GO), 0); } while (0)
#define FILLO(buf, row) do { _Pragma("unroll") for (int q = 0; q < 8; q++) buf[q] = ldg_stream_ord(wp + ((row) + q) * F_, pol); } while (0)
            FILLO(b0, 0);
            mbar_wait(BAR(B_SEL), 0);
            uint4 xn;
            {
                const int sel = ~*reinterpret_cast<volatile unsigned*>(smem + OFF_SEL) & (S_ - 1);
                xn = __ldg(reinterpret_cast<const uint4*>(at(P.x, (sel * D_ + c * 512 + (aw >> 1) * 256 + (lane & 7) * 32 + (lane >> 3) * 8) * 2)));
                uint4 f[1];
                GATHER(at(g_stat, SREC(sel) * 16), 1, f[i].z == ep);
                FILLO(b1, 32);
                PAUSE();
                const float m = __uint_as_float(f[0].x), ri = __uint_as_float(f[0].y);
                xn = make_uint4(norm2(xn.x, m, ri), norm2(xn.y, m, ri), norm2(xn.z, m, ri), norm2(xn.w, m, ri));
            }
            float ag[8];
#pragma unroll
            for (int i = 0; i < 8; i++) ag[i] = 0.f;
#define ROUND(cur, nxt, rd) do { \
                PAUSE(); \
                if (lane == 0) TRACE(192 + aw * 12 + (rd)); \
                if ((rd) == 7) wp = at(P.wd - 16 * D_, ((pair * 64 + (lane >> 4) * 8) * D_ + c * 512 + aw * 128 + (lane & 15) * 8) * 2); \
                wp = at(wp, ((rd) < 7 ? 64 * F_ : 32 * D_) + (cur[7].x & zero)); \
                if ((rd) & 7) { if ((rd) < 7) FILL(nxt, F_); else if ((rd) < 11) FILL(nxt, D_); } \
                _Pragma("unroll") for (int q = 0; q < 8; q += 2) { \
                    const uint32_t xw = __shfl_sync(0xffffffffu, q == 0 ? xn.x : q == 2 ? xn.y : q == 4 ? xn.z : xn.w, (lane & 24) | ((rd) & 7)); \
                    fma8(ag, cur[q], bf_lo(xw)); \
                    fma8(ag, cur[q + 1], bf_hi(xw)); \
                    if (q < 6) yield(ag[7], zero); \
                } } while (0)
#pragma unroll 1
            for (int rd = 0; rd < 12; rd += 2) {
                ROUND(b0, b1, rd);
                ROUND(b1, b0, rd + 1);
                if (rd == 6 || rd == 10) {
#pragma unroll
                    for (int i = 0; i < 8; i++) ag[i] += __shfl_xor_sync(0xffffffffu, ag[i], 16);
                }
                if (rd == 6) {
#pragma unroll
                    for (int i = 0; i < 8; i++) ag[i] += __shfl_xor_sync(0xffffffffu, ag[i], 8);
                    if (lane < 8) {
                        const uint32_t dst = mapa(sb + OFF_XB + (c * 4 + aw) * 128 + (lane & 3) * 32, lane >> 2), pb = mapa(BAR(B_PEER), lane >> 2);
                        st_async4(dst, __float_as_uint(ag[0]), __float_as_uint(ag[1]), __float_as_uint(ag[2]), __float_as_uint(ag[3]), pb);
                        st_async4(dst + 16, __float_as_uint(ag[4]), __float_as_uint(ag[5]), __float_as_uint(ag[6]), __float_as_uint(ag[7]), pb);
                    }
                    __syncwarp();
                    wp += 16 * D_; FILL(b1, D_); wp -= 16 * D_;
                    if (aw == 3) {
                        mbar_wait_cluster(BAR(B_PEER), 0);
                        const float* ps = reinterpret_cast<const float*>(smem + OFF_XB) + lane;
                        const float go = (ps[0] + ps[64]) + (ps[128] + ps[192]), uo = (ps[32] + ps[96]) + (ps[160] + ps[224]);
                        const float h = rbf(silu_f(rbf(go))) * rbf(uo), ho = __shfl_xor_sync(0xffffffffu, h, 1);
                        asm volatile("st.async.weak.shared::cluster.mbarrier::complete_tx::bytes.b32 [%0], %1, [%2];"
                                     ::"r"(mapa(sb + OFF_H + c * 64 + (lane >> 1) * 4, lane & 1)), "r"((lane & 1) ? pack_bf(ho, h) : pack_bf(h, ho)),
                                       "r"(mapa(BAR(B_H), lane & 1)) : "memory");
                    }
                    mbar_wait_cluster(BAR(B_H), 0);
                    xn = *reinterpret_cast<const uint4*>(smem + OFF_H + (lane & 3) * 32 + (lane >> 4) * 16);
#pragma unroll
                    for (int i = 0; i < 8; i++) ag[i] = 0.f;
                    if (mt == 0) PROF_T(10);
                }
            }
            const int hi = lane >> 4;
            st_relaxed128(at(g_part, pair * 4096 + (c * 8 + aw * 2 + ((lane >> 3) & 1)) * 256 + hi * 128 + (lane & 7) * 16),
                          make_uint4((__float_as_uint(hi ? ag[4] : ag[0]) & ~15u) | (ep & 15u), __float_as_uint(hi ? ag[5] : ag[1]),
                                     __float_as_uint(hi ? ag[6] : ag[2]), __float_as_uint(hi ? ag[7] : ag[3])));
            if (mt == 0) PROF_T(11);
        } else {
            mbar_wait_sleep(BAR(B_SEL), 0);
        }
        const int sel = ~*reinterpret_cast<volatile unsigned*>(smem + OFF_SEL) & (S_ - 1);
        if ((sel >> 8) == g) {
            const int col = (lane & 7) * 8 + ((lane >> 3) & 1) * 4;
            const uint2 xv = __ldg(reinterpret_cast<const uint2*>(at(P.x, (sel * D_ + grp * 64 + col) * 2)));
            uint4 f[1];
            GATHER(at(g_stat, SREC(sel) * 16), 1, f[i].z == ep);
            const uint4 rec = f[0];
            const uint4* src = at(g_part, (aw * 14 + (lane >> 4)) * 4096 + grp * 256 + (lane & 15) * 16);
            if (!moe) {
                int n = 0;
                while (((ld_relaxed(src) ^ ep) & 15u) != 0 && ++n < SPIN_LIMIT) __nanosleep(500);
            }
            uint4 t[7];
            int n = 0;
            bool ok;
            do {
                ok = true;
#pragma unroll
                for (int u = 0; u < 7; u++) { t[u] = ld_relaxed128(src + u * 512); ok = ok && ((t[u].x ^ ep) & 15u) == 0; }
            } while (!__all_sync(0xffffffffu, ok) && ++n < SPIN_LIMIT);
            float4 a = make_float4(0.f, 0.f, 0.f, 0.f);
#pragma unroll
            for (int u = 0; u < 7; u++) {
                a.x += __uint_as_float(t[u].x & ~15u); a.y += __uint_as_float(t[u].y); a.z += __uint_as_float(t[u].z); a.w += __uint_as_float(t[u].w);
            }
            a.x += __shfl_xor_sync(0xffffffffu, a.x, 16); a.y += __shfl_xor_sync(0xffffffffu, a.y, 16);
            a.z += __shfl_xor_sync(0xffffffffu, a.z, 16); a.w += __shfl_xor_sync(0xffffffffu, a.w, 16);
            float4* park = reinterpret_cast<float4*>(smem + OFF_XB) + (lane & 15);
            if (lane < 16) park[aw * 16] = a;
            named_bar<4, 128>();
            if (aw == 0) {
                const float4 p1 = park[16], p2 = park[32], p3 = park[48];
                a.x = (a.x + p1.x) + (p2.x + p3.x); a.y = (a.y + p1.y) + (p2.y + p3.y);
                a.z = (a.z + p1.z) + (p2.z + p3.z); a.w = (a.w + p1.w) + (p2.w + p3.w);
                unsigned u = *reinterpret_cast<volatile unsigned*>(smem + OFF_SEL) >> 16;
                u = (u & 0x8000u) ? (u & 0x7fffu) : (~u & 0xffffu);
                const float sg = rbf(__fdividef(1.0f, 1.0f + __expf(-__uint_as_float(u << 16))));
                const float m = __uint_as_float(rec.x), ri = __uint_as_float(rec.y);
                const uint32_t n0 = norm2(xv.x, m, ri), n1 = norm2(xv.y, m, ri);
                uint2 o;
                o.x = silu2(pack_bf(bf_lo(n0) + rbf(rbf(a.x) * sg), bf_hi(n0) + rbf(rbf(a.y) * sg)));
                o.y = silu2(pack_bf(bf_lo(n1) + rbf(rbf(a.z) * sg), bf_hi(n1) + rbf(rbf(a.w) * sg)));
                if (lane < 16) *reinterpret_cast<uint2*>(smem + OFF_H + col * 2) = o;
                __syncwarp();
                if (lane == 0) { mbar_arrive(BAR(B_UPD)); PROF_T(12); }
            }
        }
    } else if (warp < 8) {
        asm volatile("setmaxnreg.inc.sync.aligned.u32 %0;" ::"n"(CONS_REGS));
        CLUSTER_WAIT();
        const int wg = warp >> 2, wq = warp & 3;
        const int wt = tid & 127;
        float acc[128];
        const uint32_t fL = BAR(B_FL + 4 * wg), eL = BAR(B_EL + 4 * wg);
        const uint32_t dL = desc_lo(SB0 + OFF_L, 16) + wg * 4096;
        constexpr uint32_t dS = desc_lo(SB0 + OFF_S, 16);
        constexpr uint32_t SL = SLOT >> 4;
#define RELEASE(ls, ss) do { if (wt == 0) { mbar_arrive(eL + 8u * (ls)); mbar_arrive(BAR(B_ES + (ss))); } } while (0)
#define WAIT_FULL(ls, lph, ss, sph) do { mbar_wait(BAR(B_FS + (ss)), sph); mbar_wait(fL + 8u * (ls), lph); } while (0)
#define TURN() do { if (wg) named_bar<6, 256>(); else named_bar<5, 256>(); } while (0)
#define PASS() do { if (wg) named_arrive<5, 256>(); else named_arrive<6, 256>(); } while (0)
#define WG_BAR() do { if (wg) named_bar<2, 128>(); else named_bar<1, 128>(); } while (0)
        if (wg == 1) PASS();

#define MMA1_H(O, s, first) do { _Pragma("unroll") for (int kk = 0; kk < 4; kk++) \
            wgmma128<O, 0>(acc, dL + (s) * SL + kk * 2 + (O) * 8, dS + DSLOT(s) * SL + kk * 2, !((first) && kk == 0)); } while (0)
#define WAIT1(s, ph) WAIT_FULL(s, ph, DSLOT(s), ph)
#define PROBE(ls, lph, ss, sph) (mbar_test(BAR(B_FS + (ss)), sph) & mbar_test(fL + 8u * (ls), lph))
#define REL1(s) RELEASE(s, DSLOT(s))
#pragma unroll 1
        for (int it = 0; it < 12; it++) {
            const int s = it & 3;
            const bool ok = PROBE(s, (it >> 2) & 1, DSLOT(s), (it >> 2) & 1);
            if (it) { wg_wait<0>(); REL1((s + 3) & 3); }
            if (!ok) WAIT1(s, (it >> 2) & 1);
            TURN();
            wg_fence(); MMA1_H(0, s, it == 0); MMA1_H(64, s, it == 0); wg_commit();
            PASS();
            if (it == 0 && tid == 0) PROF_T(16);
        }
        TS(12);
        float rs[4] = {};
        uint32_t nm[8] = {};
#define GET_STATS() do { mbar_wait(BAR(B_STATS), 0); \
            const int p0 = POS(wg * 128 + wq * 16 + (lane >> 2));                   \
            const uint32_t msk = (lane & 3) == 0 ? 0xffffffffu : (lane & 3) == 1 ? 0x0000ffffu : 0u; \
            _Pragma("unroll") for (int i = 0; i < 4; i++) { \
                const int p = p0 + (i & 1) * 2 + (i >> 1) * 64; \
                rs[i] = *reinterpret_cast<const float*>(smem + OFF_RSTD + p * 4); \
                const uint32_t m = *reinterpret_cast<const uint16_t*>(smem + OFF_MEAN + p * 2) ^ 0x8000u; \
                nm[i + (i & 2)] = (m | (m << 16)) & msk; \
            } } while (0)
        const bool early = wg || __all_sync(0xffffffffu, mbar_test(BAR(B_STATS), 0));
        if (early && !wg) GET_STATS();
        WAIT1(0, 1);
        TS(13);
        wg_wait<0>(); REL1(3);
        if (wg) GET_STATS();
        TS(14);
        TURN();
        wg_fence();
        MMA1_H(0, 0, false);
        if (tid == 0) { mbar_arrive(BAR(B_QUIET)); PROF_T(15); }
        WAIT1(1, 1); wg_fence(); MMA1_H(0, 1, false);
        WAIT1(2, 1); wg_fence(); MMA1_H(0, 2, false); wg_commit();
        if (!early) GET_STATS();
        asm volatile("" : "+r"(nm[0]), "+r"(nm[1]), "+r"(nm[2]), "+r"(nm[3]), "+r"(nm[4]), "+r"(nm[5]), "+r"(nm[6]), "+r"(nm[7])::"memory");
        wg_fence();
        wgmma128_rs<64>(acc, nm + 4, (SB0 + OFF_RS) >> 4);
        wgmma128_rs<0>(acc, nm, (SB0 + OFF_RS) >> 4);
        WAIT1(3, 1); wg_fence(); MMA1_H(0, 3, false); wg_commit();
        PASS();
        const int mrow = wq * 16 + ((lane >> 3) & 1) * 8 + (lane & 7);
#define EPI1(O, slot, FREE) do { const uint32_t dst = sb + OFF_S + (slot) * SLOT + mrow * 128; \
            uint32_t pk[32]; \
            _Pragma("unroll") for (int i = 0; i < 32; i += 4) { \
                _Pragma("unroll") for (int k = 0; k < 4; k++) \
                    pk[i + k] = pack_bf(acc[(O) + 2 * (i + k)] * rs[(O) / 32 + (k & 1)], acc[(O) + 2 * (i + k) + 1] * rs[(O) / 32 + (k & 1)]); \
                if (i == EF) { FREE; } \
                if (i >= EF) { _Pragma("unroll") for (int v = (i == EF ? 0 : i); v <= i; v += 4) \
                    stmatrix4(dst + ((v >> 4) ^ c ^ 1) * 8192 + ((((v >> 1) & 7) + (lane >> 4)) ^ (lane & 7)) * 16, pk[v], pk[v + 1], pk[v + 2], pk[v + 3]); } } \
            WG_BAR(); \
            if (wt == 0) mbar_arrive(BAR(B_FS + (slot))); } while (0)
        TS(15);
        wg_wait<0>();
        fence_regs64<0>(acc);
        TS(16);
        {
            constexpr int EF = 0;
            EPI1(0, wg, if (wg) mbar_wait(BAR(B_FS), 0));
        }
        TS(17);
        TURN();
        wg_fence();
        MMA1_H(64, 0, false); wg_commit();
        MMA1_H(64, 1, false); wg_commit();
        MMA1_H(64, 2, false); wg_commit();
        wg_wait<2>(); REL1(0);
        MMA1_H(64, 3, false); wg_commit();
        PASS();
        TS(18);
        wg_wait<2>(); REL1(1);
        mbar_wait(BAR(B_FS), 0); mbar_wait(BAR(B_FS + 1), 0); fence_async_smem();
        wg_wait<1>(); REL1(2);
        wg_wait<0>(); REL1(3);
        fence_regs64<64>(acc);
        TS(19);
        {
            constexpr int EF = 16;
            EPI1(64, 2 + wg, mbar_wait(BAR(B_ES + 2 + wg), 1));
        }
        TS(20);

        float ac2[128];
#define MMA2_H(O, ls, ss, first) do { _Pragma("unroll") for (int kk = 0; kk < 4; kk++) \
            wgmma128<O, 1>(ac2, dS + (ss) * SL + kk * 128 + (O) * 8, dL + (ls) * SL + kk * 2, !((first) && kk == 0)); } while (0)
#define WAIT2(j) WAIT_FULL((j) & 3, ((j) >> 2) & 1, PSLOT(j), PPAR(j))
#define MMA2(j) do { wg_fence(); MMA2_H(0, (j) & 3, PSLOT(j), (j) == 0); MMA2_H(64, (j) & 3, PSLOT(j), (j) == 0); wg_commit(); } while (0)
#define REL2(j) RELEASE((j) & 3, PSLOT(j))
        WAIT2(0); TURN(); MMA2(0);
        WAIT2(1); MMA2(1); PASS();
        TS(21);
        wg_wait<1>(); REL2(0);
        mbar_wait(BAR(B_FS + 2), 0); mbar_wait(BAR(B_FS + 3), 0); fence_async_smem();
        TS(22);
        {
            uint32_t l2 = 2, s2 = 2, sp = 1, lph = 0, sph = 0;
#pragma unroll 1
            for (int j = 2; j < XJ; j += 2) {
#pragma unroll
                for (int h = 0; h < 2; h++) {
                    const bool ok = PROBE(l2 + h, lph, s2 + h, sph);
                    wg_wait<0>(); RELEASE(h ? l2 : 3 - l2, h ? s2 : sp);
                    if (!ok) WAIT_FULL(l2 + h, lph, s2 + h, sph);
                    TURN();
                    wg_fence(); MMA2_H(0, l2 + h, s2 + h, false); MMA2_H(64, l2 + h, s2 + h, false); wg_commit();
                    PASS();
                    if (h == (GOJ & 1) && j == (GOJ & ~1) && wt == 0) { mbar_arrive(BAR(B_GO)); if (wg == 0) PROF_T(19); }
                }
                sp = s2 + 1; s2 = 2 * l2; sph = lph; l2 ^= 2;
                lph ^= l2 == 0;
            }
        }
        if (tid == 0) PROF_T(20);
        uint32_t gt[32];
        const uint32_t xrow = sb + OFF_S + 2 * SLOT + wg * 8192 + ((lane >> 4) * 8 + (lane & 7)) * 128 + (((2 * wq + ((lane >> 3) & 1)) ^ (lane & 7)) << 4);
        const uint32_t gsign = c ? 0x80008000u : 0u;
#define XOFF(v) (((v) >> 2) * SLOT + ((v) & 3) * 2048)
        int sel = 0;
        bool own = false;
#define PATCH() do { own = false; \
            const uint32_t v0 = *reinterpret_cast<const uint16_t*>(smem + OFF_H + (wq * 16 + (lane >> 2)) * 2) ^ gsign; \
            const uint32_t v1 = *reinterpret_cast<const uint16_t*>(smem + OFF_H + (wq * 16 + (lane >> 2)) * 2 + 16) ^ gsign; \
            const uint32_t pick = (lane & 3) != ((sel >> 1) & 3) ? 0x3210u : (sel & 1) ? 0x5410u : 0x3254u; \
            _Pragma("unroll") for (int i = 0; i < 16; i++) { \
                const uint32_t m = ((sel >> 3) & 15) == i ? pick : 0x3210u; \
                gt[2 * i] = __byte_perm(gt[2 * i], v0, m); \
                gt[2 * i + 1] = __byte_perm(gt[2 * i + 1], v1, m); \
            } } while (0)
#pragma unroll
        for (int u = 0; u < 8; u++) {
            if (u) { WAIT2(XJ + u - 1); wg_wait<0>(); REL2(XJ + u - 2); TURN(); MMA2(XJ + u - 1); PASS(); }
            uint32_t* o = &gt[4 * u];
            if (!(u & 3)) mbar_wait(BAR(B_FS + 2 + (u >> 2)), 1);
            ldmatrix4t(xrow + XOFF(u), o[0], o[1], o[2], o[3]);
            const float4 r4 = *reinterpret_cast<const float4*>(smem + OFF_RSTD + (wg * 128 + u * 16 + (lane & 3) * 4) * 4);
            const uint2 m2 = *reinterpret_cast<const uint2*>(smem + OFF_MEAN + (wg * 128 + u * 16 + (lane & 3) * 4) * 2);
            o[0] = gate2(o[0], m2.x, r4.x, r4.y) ^ gsign;
            o[1] = gate2(o[1], m2.x, r4.x, r4.y) ^ gsign;
            o[2] = gate2(o[2], m2.y, r4.z, r4.w) ^ gsign;
            o[3] = gate2(o[3], m2.y, r4.z, r4.w) ^ gsign;
            if (u == 2) {
                mbar_wait(BAR(B_SEL), 0);
                sel = ~*reinterpret_cast<volatile unsigned*>(smem + OFF_SEL) & (S_ - 1);
                own = (sel >> 7) == 2 * g + wg;
            }
            asm volatile("st.shared.v2.u32 [%0], {%1,%2};" ::"r"(sb + OFF_SEL + 16), "r"(o[0] ^ o[1]), "r"(o[2] ^ o[3]) : "memory");
        }
        if (tid == 0) PROF_T(21);
        WAIT2(27);
        wg_wait<0>(); REL2(26);
        if (own) {
            const uint32_t t0 = clock32();
            bool ok;
            while (!(ok = mbar_test(BAR(B_UPD), 0)) && clock32() - t0 < wg * 1900u) __nanosleep(50);
            if (__all_sync(0xffffffffu, ok)) PATCH();
        }
        TS(0);
        TURN();
        MMA2(27);
        WAIT2(28); wg_fence(); MMA2_H(0, 0, PSLOT(28), false); wg_commit();
        if (wg == 0) { wg_fence(); MMA2_H(64, 0, PSLOT(28), false); wg_commit(); }
        constexpr uint32_t dL0 = desc_lo(SB0 + OFF_L, 16);
        const uint32_t ct[3] = {wg ? 3u : 1u, wg ? 1u : 2u, wg ? 2u : 5u};
#define TMMA(O, i) wgmma128<O, 1>(ac2, ((i) < 8 ? dS + PSLOT(29 + ((i) >> 2)) * SL : dL0 + 6 * SL) + ((i) & 3) * 128 + (O) * 8, \
                                  dL0 + ct[(i) >> 2] * SL + ((i) & 3) * 2, 1)
#define KEEP(i) TMMA(64, i)
#pragma unroll
        for (int k = 0; k < 3; k++) {
            if (k < 2) mbar_wait(BAR(B_FS + PSLOT(29 + k)), PPAR(29 + k)); else mbar_wait(BAR(B_FL + 6), 1);
            mbar_wait(BAR(B_FL + ct[k]), k == 0 || wg == 0);
            wg_fence();
#pragma unroll
            for (int i = 4 * k; i < 4 * k + 4; i++) TMMA(0, i);
            wg_commit();
            if (k < 2) wg_wait<2>();
            if (k == 0 && tid == 0) mbar_arrive(BAR(B_EL + 3));
            if (k == 1 && tid == 0) mbar_arrive_cluster(mapa(BAR(B_RDY), c ^ 1));
        }
        TS(1);
        wg_fence();
#pragma unroll
        for (int i = 0; i < KQ; i++) KEEP(i);
        wg_commit();
        mbar_wait(BAR(B_RDY + wg), 0);
        wg_wait<1>();
        fence_regs64<0>(ac2);
        TS(2);
        wg_fence();
        {
            const uint32_t dst = mapa(sb + OFF_L + wg * 5 * SLOT + wt * 16, c ^ 1), rb = mapa(BAR(B_RECV + 2 * wg), c ^ 1);
#pragma unroll
            for (int v = 0; v < 8; v++) {
                if (KQ + v < 12) KEEP(KQ + v);
                if (KQ + v == 7) wg_commit();
                if (KQ + v == 11) { wg_commit(); if (wg == 0) PASS(); }
                st_async4(dst + v * 2048, pack_bf(ac2[8 * v + 0], ac2[8 * v + 1]), pack_bf(ac2[8 * v + 2], ac2[8 * v + 3]),
                          pack_bf(ac2[8 * v + 4], ac2[8 * v + 5]), pack_bf(ac2[8 * v + 6], ac2[8 * v + 7]), rb + (v >> 2) * 8);
            }
        }
        if (wg == 1) { wg_fence(); MMA2_H(64, 0, PSLOT(28), false); wg_commit(); }
        TS(3);
        uint32_t xr[32];
#define LDX(v) ldmatrix4t(xrow + XOFF(v), xr[4 * (v)], xr[4 * (v) + 1], xr[4 * (v) + 2], xr[4 * (v) + 3])
        if (wg == 0) {
            wg_wait<2>();
            if (wt == 0) mbar_arrive(BAR(B_EL + 1));
            wg_wait<1>();
            if (wt == 0) mbar_arrive(BAR(B_EL + 2));
        }
#pragma unroll
        for (int v = 0; v < XE; v++) LDX(v);
        if (wg == 0) {
            wg_wait<0>();
            if (wt == 0) mbar_arrive_cluster(mapa(BAR(B_RDY + 1), c ^ 1));
        }
        TS(4);
        if (own) { mbar_wait(BAR(B_UPD), 0); PATCH(); }
        TS(5);
        uint4 rv[8];
#define FETCH(v0) do { if ((v0) == 0 || (v0) == 4) mbar_wait_cluster(BAR(B_RECV + 2 * wg + (v0) / 4), 0); \
            _Pragma("unroll") for (int v = (v0); v < (v0) + 2; v++) { \
                asm volatile("ld.shared.v4.u32 {%0,%1,%2,%3}, [%4];" : "=r"(rv[v].x), "=r"(rv[v].y), "=r"(rv[v].z), "=r"(rv[v].w) \
                             : "r"(sb + OFF_L + wg * 5 * SLOT + v * 2048 + wt * 16) : "memory"); \
                if (v >= XE) LDX(v); } } while (0)
        FETCH(0);
        TS(6);
        wg_wait<0>();
        fence_regs64<64>(ac2);
        TS(7);
#pragma unroll
        for (int v0 = 0; v0 < 8; v0 += 2) {
#pragma unroll
            for (int v = v0; v < v0 + 2; v++) {
                const float* a = &ac2[64 + 8 * v];
                stmatrix4t(xrow + XOFF(v),
                           bfma2(bsub2(pack_bf(a[0], a[1]), rv[v].x), gt[4 * v + 0], xr[4 * v + 0]),
                           bfma2(bsub2(pack_bf(a[2], a[3]), rv[v].y), gt[4 * v + 1], xr[4 * v + 1]),
                           bfma2(bsub2(pack_bf(a[4], a[5]), rv[v].z), gt[4 * v + 2], xr[4 * v + 2]),
                           bfma2(bsub2(pack_bf(a[6], a[7]), rv[v].w), gt[4 * v + 3], xr[4 * v + 3]));
            }
            WG_BAR();
            if (wt == 0) mbar_arrive(eL + 4 * v0);
            if (v0 + 2 < 8) FETCH(v0 + 2);
            if (v0 == 0) TS(8);
        }
        TS(9);
    } else {
        asm volatile("setmaxnreg.dec.sync.aligned.u32 %0;" ::"n"(PROD_REGS));
#define XROWS(k) do { mbar_expect_tx(XBAR(k), 8192); bulk_g2s(sb + OFF_S + (k) * 8192, at(P.x, (b * 16 + (k) * 4) * D_ * 2), 8192, XBAR(k)); } while (0)
        if (warp == 12) {
            if (elect_one()) {
                const CUtensorMap* tmD = c ? &tm_dim : &tm_dre;
#pragma unroll 1
                for (int it = 1; it < 4; it++) {
                    while (clock32() - (uint32_t)tstart < LDEL + (it - 1) * LGAP) {}
                    LOAD0(it);
                    if (it >= X0) XROWS(it - X0);
                }
            }
            __syncwarp();
        }
        CLUSTER_WAIT();
        if (warp == 12) {
            if (elect_one()) {
                const CUtensorMap* tmD = c ? &tm_dim : &tm_dre;
#pragma unroll 1
                for (int it = 4; it < 16; it++) {
                    const int s = DSLOT(it);
                    mbar_wait(BAR(B_ES + s), ((it >> 2) & 1) ^ 1);
                    TRACE(it);
                    mbar_expect_tx(BAR(B_FS + s), SLOT);
                    tma_2d(sb + OFF_S + s * SLOT, tmD, it * 64, r * 128, BAR(B_FS + s));
                    if (it < 4 + X0) XROWS(it - X0);
                }
                const unsigned ep = load_epoch(b), e8 = ep & 0xffu;
                const uint8_t* abg = at(AB, grp * 32 * SLOT);
                const unsigned long long* fl = at(g_flag, grp * 128);
                unsigned long long rdy = ld_acquire64(fl);
                mbar_wait(BAR(B_SRD), 0);
                st_release8(at(g_flag, grp * 128 + g), e8);
                PROF_T(7);
                int j = 4;
#pragma unroll 1
                for (int cl = 0; cl < 4; cl++) {
                    if (cl) rdy = ld_acquire64(++fl);
                    fence_async_global();
#pragma unroll 1
                    for (int n = 1; n < 8; n++, j++) {
                        const int q = BLK(n), s = (j & 1) + ((j & 2) ? 0 : 4);
                        const uint32_t fb = BAR(j == 31 ? B_FL + 6 : B_FS + s);
                        if (j == 31) mbar_wait(BAR(B_EL + 6), 0); else mbar_wait(BAR(B_ES + s), ((j >> 2) ^ (j >> 1)) & 1);
                        if (j == 7) mbar_wait(BAR(B_SRD + 1), 0);
                        if (((unsigned)(rdy >> (8 * q)) & 0xffu) != e8) {
                            int m = 0;
                            do { rdy = ld_acquire64(fl); } while (((unsigned)(rdy >> (8 * q)) & 0xffu) != e8 && ++m < SPIN_LIMIT);
                            fence_async_global();
                        }
                        TRACE(16 + j);
                        mbar_expect_tx(fb, SLOT);
                        bulk_g2s(sb + (j == 31 ? OFF_L + 6 * SLOT : OFF_S + s * SLOT), at(abg, (4 * q + KO(cl)) * SLOT), SLOT, fb);
                    }
                }
                *at(g_epoch, b * 4) = ep;
            }
        } else if (warp < 15) {
            if (elect_one()) {
                const int w = warp - 13, row0 = g * 256 + w * 128;
                const CUtensorMap* tmC = c ? &tm_cim : &tm_cre;
                const uint32_t fb = BAR(B_FL + 4 * w), eb = BAR(B_EL + 4 * w), dst = sb + OFF_L + w * 4 * SLOT;
                [[maybe_unused]] unsigned long long mk = 0, mg = 0;
                int n = 0, cl = 0;
#pragma unroll 1
                for (int it = 4; it < 47 - 2 * w; it++) {
                    const int s = it & 3;
                    mbar_wait(eb + 8 * s, ((it >> 2) & 1) ^ 1);
                    TRACE(64 + w * 64 + it - 4);
                    MARK(it);
                    mbar_expect_tx(fb + 8 * s, SLOT);
                    tma_2d(dst + s * SLOT, it < 16 ? &tm_x : tmC, (it < 16 ? it : 4 * (n ? BLK(n) : g) + KO(cl)) * 64, row0, fb + 8 * s);
                    if (it == PTJ) prefetch_tmap(w ? &tm_x64 : tmC);
                    if (it == PTJ && w) prefetch_tmap(&tm_out);
                    if (it >= 16) {
                        if (it == 19) { n = 1; cl = 0; } else if (it < 19) cl++; else if (++n == 8) { n = 1; cl++; }
                    }
                }
#pragma unroll 1
                for (int i = 2 * w; i < 3; i++) {
                    const int s = w ? 1 : i ? i : 3;
                    mbar_wait(eb + 8 * s, w == 0 && i);
                    mbar_expect_tx(fb + 8 * s, SLOT);
                    tma_2d(dst + s * SLOT, tmC, (4 * BLK(5 + i) + 3) * 64, row0 ^ 128, fb + 8 * s);
                }
                if (w && (r & 3) < 2) tma_2d_prefetch(tmC, (4 * BLK(6 + (r & 1)) + 3) * 64, row0);
#pragma unroll 1
                for (int h = 0; h < 4; h++) {
                    mbar_wait(eb + 8 * h, ((w ? 7 : 9) >> h) & 1);
                    fence_async_smem();
                    tma_2d_store(&tm_out, grp * 64, row0 + h * 32, sb + OFF_S + (2 + (h >> 1)) * SLOT + w * 8192 + (h & 1) * 4096);
                    bulk_commit();
                }
                FINISH(w);
            }
        } else {
            const unsigned ep = load_epoch(b);
            uint4 f[4];
            {
                sleep_until((uint32_t)tstart + 6000);
                const uint4* keys = at(reinterpret_cast<const uint4*>(g_key), lane * 16);
                bool mine = false;
                int n = 0;
                do {
                    f[0] = ld_relaxed128(keys); f[1] = ld_relaxed128(keys + 32);
                    if (__all_sync(0xffffffffu, f[0].y == ep && f[0].w == ep && f[1].y == ep && f[1].w == ep)) break;
                    if (!mine) {
                        mbar_wait(BAR(B_LST), 0);
                        const uint4 k = *reinterpret_cast<const uint4*>(smem + OFF_XB);
                        if (lane == 0) st_relaxed64(at(g_key, b * 8), ((unsigned long long)ep << 32) | max(max(k.x, k.y), max(k.z, k.w)));
                        mine = true;
                    }
                    __nanosleep(GSL);
                } while (++n < SPIN_LIMIT);
                const unsigned key = __reduce_max_sync(0xffffffffu, max(max(f[0].x, f[0].z), max(f[1].x, f[1].z)));
                if (lane == 0) { *reinterpret_cast<unsigned*>(smem + OFF_SEL) = key; mbar_arrive(BAR(B_SEL)); PROF_T(8); }
            }
            if (elect_one()) {
#pragma unroll 1
                for (int cl = 0; cl < 4; cl++) {
                    uint8_t* dst = at(AB, (grp * 32 + 4 * g + KO(cl)) * SLOT);
                    const uint32_t src = sb + OFF_S + cl * SLOT, chunk = cl ? 1024 : SLOT;
                    mbar_wait(BAR(B_FS + cl), 0);
                    fence_async_smem();
                    if (cl == 0) PROF_T(3);
                    uint32_t t0 = clock32() + (cl == 1 ? PDEL : 0);
#pragma unroll 1
                    for (uint32_t o = 0; o < SLOT; o += chunk) {
                        sleep_until(t0);
                        bulk_s2g(dst + o, src + o, chunk);
                        bulk_commit();
                        t0 += cl == 1 ? PGAP1 : cl == 2 ? PGAP2 : PGAP3;
                    }
                    bulk_wait<0>();
                    fence_async_global();
                    TRACE(252 + cl);
                    if (cl < 2) mbar_arrive(BAR(B_SRD + cl));
                    else {
                        mbar_wait(BAR(B_ES + cl), 0);
                        mbar_expect_tx(BAR(B_FS + cl), SLOT);
                        tma_2d(src, &tm_x64, grp * 64, g * 256 + (cl - 2) * 64, BAR(B_FS + cl));
                        tma_2d(src + 8192, &tm_x64, grp * 64, g * 256 + (cl - 2) * 64 + 128, BAR(B_FS + cl));
                    }
                    if (cl) st_release8(at(g_flag, grp * 128 + cl * 8 + g), ep & 0xffu);
                    if (cl == 1) PROF_T(5);
                    if (cl == 3) PROF_T(4);
                }
            }
        }
    }
}

typedef CUresult (*EncodeFn)(CUtensorMap*, CUtensorMapDataType, cuuint32_t, void*, const cuuint64_t*, const cuuint64_t*,
                             const cuuint32_t*, const cuuint32_t*, CUtensorMapInterleave, CUtensorMapSwizzle,
                             CUtensorMapL2promotion, CUtensorMapFloatOOBfill);

void make_map(EncodeFn fn, CUtensorMap* tm, const void* p, uint64_t rows, uint64_t cols, uint32_t box_rows) {
    cuuint64_t dims[2] = {cols, rows};
    cuuint64_t strides[1] = {cols * 2};
    cuuint32_t box[2] = {64, box_rows};
    cuuint32_t es[2] = {1, 1};
    fn(tm, CU_TENSOR_MAP_DATA_TYPE_BFLOAT16, 2, const_cast<void*>(p), dims, strides, box, es, CU_TENSOR_MAP_INTERLEAVE_NONE,
       CU_TENSOR_MAP_SWIZZLE_128B, CU_TENSOR_MAP_L2_PROMOTION_L2_128B, CU_TENSOR_MAP_FLOAT_OOB_FILL_NONE);
}

}

extern "C" void kernel_launch(void* const* d_in, const int* in_sizes, int n_in, void* d_out, int out_size) {
    (void)in_sizes; (void)n_in; (void)out_size;
    static EncodeFn fn = nullptr;
    if (!fn) {
        void* p = nullptr;
        cudaDriverEntryPointQueryResult q;
        cudaGetDriverEntryPoint("cuTensorMapEncodeTiled", &p, cudaEnableDefault, &q);
        fn = (EncodeFn)p;
        cudaFuncSetAttribute(fnet_fused_kernel, cudaFuncAttributeMaxDynamicSharedMemorySize, SMEM_BYTES);
    }
    CUtensorMap tx, tdre, tdim, tcre, tcim, tout, tx64;
    make_map(fn, &tx, d_in[0], S_, D_, 128);
    make_map(fn, &tcre, d_in[1], S_, S_, 128);
    make_map(fn, &tcim, d_in[2], S_, S_, 128);
    make_map(fn, &tdre, d_in[3], D_, D_, 128);
    make_map(fn, &tdim, d_in[4], D_, D_, 128);
    make_map(fn, &tx64, d_in[0], S_, D_, 64);
    make_map(fn, &tout, d_out, S_, D_, 32);
    Params P;
    P.x = (const __nv_bfloat16*)d_in[0];
    P.dre = (const __nv_bfloat16*)d_in[3];
    P.dim = (const __nv_bfloat16*)d_in[4];
    P.wr = (const __nv_bfloat16*)d_in[6];
    P.wg = (const __nv_bfloat16*)d_in[7];
    P.wu = (const __nv_bfloat16*)d_in[8];
    P.wd = (const __nv_bfloat16*)d_in[9];
    P.zero = 0;
    fnet_fused_kernel<<<NCTA, NTHREADS, SMEM_BYTES, cudaStreamPerThread>>>(tx, tdre, tdim, tcre, tcim, tout, tx64, P);
}
```

```cpp
#include <cuda_runtime.h>
#include <cuda_bf16.h>
#include <cuda.h>
#include <stdint.h>

#define GSL 200
#define SLEEP_NS 200
#define PDEL 1000
#define PGAP1 200
#define PGAP2 200
#define PGAP3 240
#define GOJ 2
#define LDEL 1400
#define LGAP 700
#define PTJ 10
#define X0 2
#define KQ 5
#define XE 2
#define PROD_REGS 32
#define CONS_REGS 184

namespace {

constexpr int S_ = 2048, D_ = 1024, F_ = 3584;
constexpr int NCTA = 128;
constexpr int XJ = 20;
constexpr uint32_t SLOT = 16384;
constexpr uint32_t OFF_L = 0;
constexpr uint32_t OFF_S = 8 * SLOT;
constexpr uint32_t OFF_RS = OFF_S + SLOT;
constexpr uint32_t OFF_BAR = 14 * SLOT;
constexpr uint32_t OFF_SEL = OFF_BAR + 360;
constexpr uint32_t OFF_RSTD = OFF_BAR + 384;
constexpr uint32_t OFF_MEAN = OFF_RSTD + 1024;
constexpr uint32_t OFF_XB = OFF_MEAN + 512;
constexpr uint32_t OFF_H = OFF_XB + 1024;
constexpr uint32_t SMEM_BYTES = OFF_H + 128;
constexpr uint32_t SB0 = 1024;
constexpr int NTHREADS = 512;
static_assert(SMEM_BYTES <= 232448, "smem");

enum { B_FS = 0, B_ES = 6, B_FL = 12, B_EL = 20, B_SRD = 28  , B_RECV = 30  , B_RDY = 34, B_STATS = 36, B_LST = 37, B_UPD = 38,
       B_QUIET = 39, B_GO = 40, B_PEER = 41, B_SEL = 42, B_H = 43, B_R27 = 44, B_COUNT = 45 };
static_assert(B_COUNT * 8 <= 360, "barriers");

__device__ __align__(1024) uint8_t g_ab[16u * 32u * SLOT];
__device__ __align__(128) uint4 g_part[56 * (D_ / 4)];
__device__ __align__(128) uint4 g_stat[S_];
__device__ __align__(128) uint4 g_rs[D_];
__device__ __align__(128) unsigned long long g_key[NCTA];
__device__ __align__(128) unsigned long long g_flag[16 * 16];
__device__ __align__(128) unsigned g_epoch[NCTA];
#define PROF_T(i) do {} while (0)
#define TRACE(i) do {} while (0)
#define PROF_G(i) do {} while (0)
#define TS(i) do {} while (0)
#define FINISH(wg) bulk_wait_read<0>()

#define MARK(it) do {} while (0)

__device__ __forceinline__ uint32_t smem_u32(const void* p) { return (uint32_t)__cvta_generic_to_shared(p); }
__device__ __forceinline__ void mbar_init(uint32_t bar, uint32_t cnt) {
    asm volatile("mbarrier.init.shared::cta.b64 [%0], %1;" ::"r"(bar), "r"(cnt) : "memory");
}
__device__ __forceinline__ bool mbar_try(uint32_t bar, uint32_t parity) {
    uint32_t ok;
    asm volatile("{\n.reg .pred p;\nmbarrier.try_wait.parity.shared::cta.b64 p, [%1], %2;\nselp.u32 %0, 1, 0, p;\n}"
                 : "=r"(ok) : "r"(bar), "r"(parity) : "memory");
    return ok;
}
__device__ __forceinline__ bool mbar_test(uint32_t bar, uint32_t parity) {
    uint32_t ok;
    asm volatile("{\n.reg .pred p;\nmbarrier.test_wait.parity.shared::cta.b64 p, [%1], %2;\nselp.u32 %0, 1, 0, p;\n}"
                 : "=r"(ok) : "r"(bar), "r"(parity) : "memory");
    return ok;
}
__device__ __forceinline__ bool mbar_try_cluster(uint32_t bar, uint32_t parity) {
    uint32_t ok;
    asm volatile("{\n.reg .pred p;\nmbarrier.try_wait.parity.acquire.cluster.shared::cta.b64 p, [%1], %2;\nselp.u32 %0, 1, 0, p;\n}"
                 : "=r"(ok) : "r"(bar), "r"(parity) : "memory");
    return ok;
}
constexpr int SPIN_LIMIT = 1 << 20;
__device__ __forceinline__ void mbar_wait(uint32_t bar, uint32_t parity) {
    if (mbar_try(bar, parity)) return;
    int n = 0;
    while (!mbar_try(bar, parity) && ++n < SPIN_LIMIT) {}
}
__device__ __forceinline__ void mbar_wait_cluster(uint32_t bar, uint32_t parity) {
    int n = 0;
    while (!mbar_try_cluster(bar, parity) && ++n < SPIN_LIMIT) {}
}
__device__ __forceinline__ void mbar_wait_sleep(uint32_t bar, uint32_t parity) {
    int n = 0;
    while (!mbar_try(bar, parity) && ++n < SPIN_LIMIT) __nanosleep(SLEEP_NS);
}
__device__ __forceinline__ void mbar_arrive(uint32_t bar) {
    asm volatile("mbarrier.arrive.shared::cta.b64 _, [%0];" ::"r"(bar) : "memory");
}
__device__ __forceinline__ void mbar_arrive_cluster(uint32_t cluster_bar) {
    asm volatile("mbarrier.arrive.shared::cluster.b64 _, [%0];" ::"r"(cluster_bar) : "memory");
}
__device__ __forceinline__ void mbar_expect_tx(uint32_t bar, uint32_t bytes) {
    asm volatile("mbarrier.arrive.expect_tx.shared::cta.b64 _, [%0], %1;" ::"r"(bar), "r"(bytes) : "memory");
}
__device__ __forceinline__ bool elect_one() {
    uint32_t p;
    asm volatile("{\n.reg .pred p;\nelect.sync _|p, 0xffffffff;\nselp.u32 %0, 1, 0, p;\n}" : "=r"(p));
    return p;
}
__device__ __forceinline__ uint32_t mapa(uint32_t addr, uint32_t rank) {
    uint32_t r;
    asm("mapa.shared::cluster.u32 %0, %1, %2;" : "=r"(r) : "r"(addr), "r"(rank));
    return r;
}
__device__ __forceinline__ uint32_t clock32() { uint32_t t; asm volatile("mov.u32 %0, %%clock;" : "=r"(t)); return t; }
__device__ __forceinline__ void sleep_until(uint32_t t) {
    int n = 0;
    while ((int)(clock32() - t) < 0 && ++n < SPIN_LIMIT) __nanosleep(20);
}
__device__ __forceinline__ void yield(float last, uint32_t zero) {
    asm volatile("nanosleep.u32 %0;" ::"r"(__float_as_uint(last) & zero));
}
template <typename T> __device__ __forceinline__ T* at(T* p, uint32_t bytes) {
    asm("" : "+r"(bytes));
    return reinterpret_cast<T*>(reinterpret_cast<uintptr_t>(p) + bytes);
}
__device__ __forceinline__ void tma_2d(uint32_t dst, const CUtensorMap* tm, int c0, int c1, uint32_t bar) {
    asm volatile("cp.async.bulk.tensor.2d.shared::cluster.global.mbarrier::complete_tx::bytes [%0], [%1, {%3, %4}], [%2];"
                 ::"r"(dst), "l"(tm), "r"(bar), "r"(c0), "r"(c1) : "memory");
}
__device__ __forceinline__ void tma_2d_prefetch(const CUtensorMap* tm, int c0, int c1) {
    asm volatile("cp.async.bulk.prefetch.tensor.2d.L2.global [%0, {%1, %2}];" ::"l"(tm), "r"(c0), "r"(c1) : "memory");
}
__device__ __forceinline__ void tma_2d_store(const CUtensorMap* tm, int c0, int c1, uint32_t src) {
    asm volatile("cp.async.bulk.tensor.2d.global.shared::cta.bulk_group [%0, {%2, %3}], [%1];"
                 ::"l"(tm), "r"(src), "r"(c0), "r"(c1) : "memory");
}
__device__ __forceinline__ void bulk_g2s(uint32_t dst, const void* src, uint32_t bytes, uint32_t bar) {
    asm volatile("cp.async.bulk.shared::cluster.global.mbarrier::complete_tx::bytes [%0], [%1], %2, [%3];"
                 ::"r"(dst), "l"(src), "r"(bytes), "r"(bar) : "memory");
}
__device__ __forceinline__ void bulk_s2g(void* dst, uint32_t src, uint32_t bytes) {
    asm volatile("cp.async.bulk.global.shared::cta.bulk_group [%0], [%1], %2;" ::"l"(dst), "r"(src), "r"(bytes) : "memory");
}
__device__ __forceinline__ void st_async4(uint32_t dst, uint32_t a, uint32_t b, uint32_t c, uint32_t d, uint32_t bar) {
    asm volatile("st.async.weak.shared::cluster.mbarrier::complete_tx::bytes.v4.b32 [%0], {%1,%2,%3,%4}, [%5];"
                 ::"r"(dst), "r"(a), "r"(b), "r"(c), "r"(d), "r"(bar) : "memory");
}
__device__ __forceinline__ void bulk_commit() { asm volatile("cp.async.bulk.commit_group;" ::: "memory"); }
template <int N> __device__ __forceinline__ void bulk_wait_read() { asm volatile("cp.async.bulk.wait_group.read %0;" ::"n"(N) : "memory"); }
template <int N> __device__ __forceinline__ void bulk_wait() { asm volatile("cp.async.bulk.wait_group %0;" ::"n"(N) : "memory"); }
__device__ __forceinline__ void fence_async_smem() { asm volatile("fence.proxy.async.shared::cta;" ::: "memory"); }
__device__ __forceinline__ void fence_async_global() { asm volatile("fence.proxy.async.global;" ::: "memory"); }
__device__ __forceinline__ void prefetch_tmap(const CUtensorMap* tm) {
    asm volatile("prefetch.tensormap [%0];" ::"l"(tm) : "memory");
}
__device__ __forceinline__ unsigned long long ld_acquire64(const unsigned long long* p) {
    unsigned long long v; asm volatile("ld.acquire.gpu.global.u64 %0, [%1];" : "=l"(v) : "l"(p) : "memory"); return v;
}
__device__ __forceinline__ unsigned load_epoch(int b) {
    unsigned v; asm volatile("ld.global.u32 %0, [%1];" : "=r"(v) : "l"(at(g_epoch, b * 4)) : "memory"); return v + 1;
}
__device__ __forceinline__ unsigned ld_relaxed(const void* p) {
    unsigned v; asm volatile("ld.relaxed.gpu.global.u32 %0, [%1];" : "=r"(v) : "l"(p) : "memory"); return v;
}
__device__ __forceinline__ uint4 ld_relaxed128(const uint4* p) {
    uint4 v;
    asm volatile("{\n.reg .b128 t;\n.reg .b64 lo, hi;\nld.relaxed.gpu.global.b128 t, [%4];\nmov.b128 {lo, hi}, t;\n"
                 "mov.b64 {%0, %1}, lo;\nmov.b64 {%2, %3}, hi;\n}"
                 : "=r"(v.x), "=r"(v.y), "=r"(v.z), "=r"(v.w) : "l"(p) : "memory");
    return v;
}
__device__ __forceinline__ void st_relaxed128(uint4* p, const uint4& v) {
    asm volatile("{\n.reg .b128 t;\n.reg .b64 lo, hi;\nmov.b64 lo, {%1, %2};\nmov.b64 hi, {%3, %4};\nmov.b128 t, {lo, hi};\n"
                 "st.relaxed.gpu.global.b128 [%0], t;\n}"
                 ::"l"(p), "r"(v.x), "r"(v.y), "r"(v.z), "r"(v.w) : "memory");
}
__device__ __forceinline__ void st_relaxed64(unsigned long long* p, unsigned long long v) {
    asm volatile("st.relaxed.gpu.global.u64 [%0], %1;" ::"l"(p), "l"(v) : "memory");
}
__device__ __forceinline__ void st_release8(void* p, unsigned v) {
    asm volatile("st.release.gpu.global.u8 [%0], %1;" ::"l"(p), "r"(v) : "memory");
}
__device__ __forceinline__ uint64_t policy_evict_first() {
    uint64_t pol;
    asm("createpolicy.fractional.L2::evict_first.b64 %0, 1.0;" : "=l"(pol));
    return pol;
}
__device__ __forceinline__ uint4 ldg_stream(const void* p, uint64_t pol) {
    uint4 v;
    asm volatile("ld.global.nc.L1::no_allocate.L2::cache_hint.v4.u32 {%0,%1,%2,%3}, [%4], %5;"
                 : "=r"(v.x), "=r"(v.y), "=r"(v.z), "=r"(v.w) : "l"(p), "l"(pol));
    return v;
}
__device__ __forceinline__ uint4 ldg_stream_ord(const void* p, uint64_t pol) {
    uint4 v;
    asm volatile("ld.relaxed.gpu.global.L1::no_allocate.L2::cache_hint.v4.u32 {%0,%1,%2,%3}, [%4], %5;"
                 : "=r"(v.x), "=r"(v.y), "=r"(v.z), "=r"(v.w) : "l"(p), "l"(pol) : "memory");
    return v;
}
template <int ID, int N> __device__ __forceinline__ void named_arrive() { asm volatile("bar.arrive %0, %1;" ::"n"(ID), "n"(N) : "memory"); }
template <int ID, int N> __device__ __forceinline__ void named_bar() { asm volatile("bar.sync %0, %1;" ::"n"(ID), "n"(N) : "memory"); }

__device__ __forceinline__ float bf_lo(uint32_t u) { return __uint_as_float(u << 16); }
__device__ __forceinline__ float bf_hi(uint32_t u) { return __uint_as_float(u & 0xffff0000u); }
__device__ __forceinline__ uint32_t pack_bf(float lo, float hi) {
    uint32_t r; asm("cvt.rn.bf16x2.f32 %0, %1, %2;" : "=r"(r) : "f"(hi), "f"(lo)); return r;
}
__device__ __forceinline__ float rbf(float v) { return __uint_as_float(pack_bf(0.f, v)); }
__device__ __forceinline__ float sqrt_f(float v) { float r; asm("sqrt.approx.f32 %0, %1;" : "=f"(r) : "f"(v)); return r; }
__device__ __forceinline__ float rcp_f(float v) { float r; asm("rcp.approx.f32 %0, %1;" : "=f"(r) : "f"(v)); return r; }
__device__ __forceinline__ float silu_f(float z) { return __fdividef(z, 1.0f + __expf(-z)); }
__device__ __forceinline__ uint32_t bsub2(uint32_t a, uint32_t b) {
    uint32_t r; asm("sub.rn.bf16x2 %0, %1, %2;" : "=r"(r) : "r"(a), "r"(b)); return r;
}
__device__ __forceinline__ uint32_t bfma2(uint32_t a, uint32_t b, uint32_t c) {
    uint32_t r; asm("fma.rn.bf16x2 %0, %1, %2, %3;" : "=r"(r) : "r"(a), "r"(b), "r"(c)); return r;
}
__device__ __forceinline__ uint32_t norm2(uint32_t xv, float m, float rinv) {
    uint32_t t = pack_bf(bf_lo(xv) - m, bf_hi(xv) - m);
    return pack_bf(bf_lo(t) * rinv, bf_hi(t) * rinv);
}
__device__ __forceinline__ float gate1(float z) {
    float t;
    const float h = 0.5f * z;
    asm("tanh.approx.f32 %0, %1;" : "=f"(t) : "f"(h));
    return fmaf(h, t, h);
}
__device__ __forceinline__ uint32_t gate2(uint32_t xv, uint32_t mean2, float r0, float r1) {
    const uint32_t t = bsub2(xv, mean2);
    return pack_bf(gate1(bf_lo(t) * r0), gate1(bf_hi(t) * r1));
}
__device__ __forceinline__ uint32_t silu2(uint32_t z) { return pack_bf(silu_f(bf_lo(z)), silu_f(bf_hi(z))); }

__device__ __forceinline__ void stmatrix4(uint32_t addr, uint32_t r0, uint32_t r1, uint32_t r2, uint32_t r3) {
    asm volatile("stmatrix.sync.aligned.m8n8.x4.shared.b16 [%0], {%1,%2,%3,%4};"
                 ::"r"(addr), "r"(r0), "r"(r1), "r"(r2), "r"(r3));
}
__device__ __forceinline__ void stmatrix4t(uint32_t addr, uint32_t r0, uint32_t r1, uint32_t r2, uint32_t r3) {
    asm volatile("stmatrix.sync.aligned.m8n8.x4.trans.shared.b16 [%0], {%1,%2,%3,%4};"
                 ::"r"(addr), "r"(r0), "r"(r1), "r"(r2), "r"(r3));
}
__device__ __forceinline__ void ldmatrix4t(uint32_t addr, uint32_t& r0, uint32_t& r1, uint32_t& r2, uint32_t& r3) {
    asm volatile("ldmatrix.sync.aligned.m8n8.x4.trans.shared.b16 {%0,%1,%2,%3}, [%4];"
                 : "=r"(r0), "=r"(r1), "=r"(r2), "=r"(r3) : "r"(addr));
}

__device__ __forceinline__ void wg_fence() { asm volatile("wgmma.fence.sync.aligned;" ::: "memory"); }
__device__ __forceinline__ void wg_commit() { asm volatile("wgmma.commit_group.sync.aligned;" ::: "memory"); }
template <int N> __device__ __forceinline__ void wg_wait() { asm volatile("wgmma.wait_group.sync.aligned %0;" ::"n"(N) : "memory"); }

__host__ __device__ constexpr uint32_t desc_lo(uint32_t addr, uint32_t lbo) { return ((addr & 0x3FFFF) >> 4) | ((lbo >> 4) << 16); }
#define DESC_HI "0x40000040"

#define R8(a, o) "+f"(a[(o) + 0]), "+f"(a[(o) + 1]), "+f"(a[(o) + 2]), "+f"(a[(o) + 3]), \
                 "+f"(a[(o) + 4]), "+f"(a[(o) + 5]), "+f"(a[(o) + 6]), "+f"(a[(o) + 7])
#define R64(a, o) R8(a, (o) + 0), R8(a, (o) + 8), R8(a, (o) + 16), R8(a, (o) + 24), \
                  R8(a, (o) + 32), R8(a, (o) + 40), R8(a, (o) + 48), R8(a, (o) + 56)

template <int O, int TA>
__device__ __forceinline__ void wgmma128(float (&a)[128], uint32_t da, uint32_t db, int scale_d) {
    asm volatile(
        "{\n.reg .pred p;\n.reg .b64 da, db;\nsetp.ne.b32 p, %66, 0;\n"
        "mov.b64 da, {%64, " DESC_HI "};\nmov.b64 db, {%65, " DESC_HI "};\n"
        "wgmma.mma_async.sync.aligned.m64n128k16.f32.bf16.bf16 "
        "{%0,%1,%2,%3,%4,%5,%6,%7,%8,%9,%10,%11,%12,%13,%14,%15,"
        "%16,%17,%18,%19,%20,%21,%22,%23,%24,%25,%26,%27,%28,%29,%30,%31,"
        "%32,%33,%34,%35,%36,%37,%38,%39,%40,%41,%42,%43,%44,%45,%46,%47,"
        "%48,%49,%50,%51,%52,%53,%54,%55,%56,%57,%58,%59,%60,%61,%62,%63},"
        "da, db, p, 1, 1, %67, 0;\n}"
        : R64(a, O)
        : "r"(da), "r"(db), "r"(scale_d), "n"(TA));
}
template <int O>
__device__ __forceinline__ void wgmma128_rs(float (&a)[128], const uint32_t* f, uint32_t db) {
    asm volatile(
        "{\n.reg .b64 db;\nmov.b64 db, {%68, 8};\n"
        "wgmma.mma_async.sync.aligned.m64n128k16.f32.bf16.bf16 "
        "{%0,%1,%2,%3,%4,%5,%6,%7,%8,%9,%10,%11,%12,%13,%14,%15,"
        "%16,%17,%18,%19,%20,%21,%22,%23,%24,%25,%26,%27,%28,%29,%30,%31,"
        "%32,%33,%34,%35,%36,%37,%38,%39,%40,%41,%42,%43,%44,%45,%46,%47,"
        "%48,%49,%50,%51,%52,%53,%54,%55,%56,%57,%58,%59,%60,%61,%62,%63},"
        "{%64, %65, %66, %67}, db, 1, 1, 1, 0;\n}"
        : R64(a, O)
        : "r"(f[0]), "r"(f[1]), "r"(f[2]), "r"(f[3]), "r"(db));
}
template <int O>
__device__ __forceinline__ void fence_regs64(float (&a)[128]) {
    asm volatile("" : R64(a, O)::"memory");
}

struct Params {
    const __nv_bfloat16* x;
    const __nv_bfloat16* dre;
    const __nv_bfloat16* dim;
    const __nv_bfloat16* wr;
    const __nv_bfloat16* wg;
    const __nv_bfloat16* wu;
    const __nv_bfloat16* wd;
    uint32_t zero;
#define AB g_ab
};

__device__ __forceinline__ float warp_sum(float v) {
#pragma unroll
    for (int o = 16; o; o >>= 1) v += __shfl_xor_sync(0xffffffffu, v, o);
    return v;
}
__device__ __forceinline__ void fma8(float* acc, const uint4& w, float s) {
    acc[0] += s * bf_lo(w.x); acc[1] += s * bf_hi(w.x); acc[2] += s * bf_lo(w.y); acc[3] += s * bf_hi(w.y);
    acc[4] += s * bf_lo(w.z); acc[5] += s * bf_hi(w.z); acc[6] += s * bf_lo(w.w); acc[7] += s * bf_hi(w.w);
}
__device__ __forceinline__ int POS(int t) { return (t & ~15) | ((t & 6) << 1) | ((t & 8) >> 2) | (t & 1); }
__host__ __device__ constexpr int PSLOT(int j) { return j < 4 ? j : (j & 1) + ((j & 2) ? 0 : 4); }
__host__ __device__ constexpr int PPAR(int j) { return j < 4 ? 0 : ((j >> 2) ^ (j >> 1) ^ 1) & 1; }
__host__ __device__ constexpr int DSLOT(int it) { return (it & 3) + 2; }
__device__ __forceinline__ int SREC(int t) { return (t & ~15) | ((t & 3) << 2) | ((t >> 2) & 3); }
__device__ __forceinline__ int KO(int cl) { return ((cl & 1) << 1) | (cl >> 1); }

__global__ void __cluster_dims__(2, 1, 1) __launch_bounds__(NTHREADS, 1)
fnet_fused_kernel(const __grid_constant__ CUtensorMap tm_x, const __grid_constant__ CUtensorMap tm_dre,
                  const __grid_constant__ CUtensorMap tm_dim, const __grid_constant__ CUtensorMap tm_cre,
                  const __grid_constant__ CUtensorMap tm_cim, const __grid_constant__ CUtensorMap tm_out,
                  const __grid_constant__ CUtensorMap tm_x64,
                  const Params P) {
    extern __shared__ __align__(1024) uint8_t smem[];
    const unsigned long long tstart = clock64();
    const uint32_t sb = smem_u32(smem);
    const int tid = threadIdx.x, lane = tid & 31;
    const int pr = blockIdx.x >> 1, p7 = ((pr - 36) * 37) >> 8;
    const int c = blockIdx.x & 1;
    const bool upper = pr >= 36;
    const int col = upper ? pr - 36 - 7 * p7 + 8 : pr < 4 ? 15 : (pr - 4) & 7;
    const int gi = (int)(0x7eca8531fdb96420ull >> (4 * col)) & 15;
    const int g = gi & 7;
    const int r = (gi >> 3) * 4 + (upper ? p7 : pr < 4 ? pr : (pr - 4) >> 3);
#define BLK(n) ((n) - ((n) <= g))
    const int grp = 2 * r + c;
    const int b = g * 16 + grp;
    const uint32_t bar0 = sb + OFF_BAR;
    const uint32_t zero = P.zero;
#define BAR(i) (bar0 + 8u * (i))
#define XBAR(i) (sb + OFF_XB + 64 + 8u * (i))
#define CLUSTER_ARRIVE() asm volatile("barrier.cluster.arrive.relaxed.aligned;" ::: "memory")
#define CLUSTER_WAIT() asm volatile("barrier.cluster.wait.aligned;" ::: "memory")

#define LOAD0(it) do { \
            mbar_expect_tx(BAR(B_FS + DSLOT(it)), SLOT); tma_2d(sb + OFF_S + DSLOT(it) * SLOT, tmD, (it) * 64, r * 128, BAR(B_FS + DSLOT(it))); \
            mbar_expect_tx(BAR(B_FL + (it)), SLOT); tma_2d(sb + OFF_L + (it) * SLOT, &tm_x, (it) * 64, g * 256, BAR(B_FL + (it))); \
            mbar_expect_tx(BAR(B_FL + 4 + (it)), SLOT); tma_2d(sb + OFF_L + (4 + (it)) * SLOT, &tm_x, (it) * 64, g * 256 + 128, BAR(B_FL + 4 + (it))); \
        } while (0)
    if (tid < 32) {
        if (elect_one()) {
            const CUtensorMap* tmD = c ? &tm_dim : &tm_dre;
            prefetch_tmap(tmD); prefetch_tmap(&tm_x);
            mbar_init(BAR(B_FS + 2), 1); mbar_init(BAR(B_FL), 1); mbar_init(BAR(B_FL + 4), 1);
            asm volatile("fence.mbarrier_init.release.cluster;" ::: "memory");
            LOAD0(0);
        }
        __syncwarp();
    }
    const int warp = __shfl_sync(0xffffffffu, tid >> 5, 0);
    if (warp == 12) {
        if (elect_one()) {
#pragma unroll
            for (int i = 1; i < 4; i++) { mbar_init(BAR(B_FS + 2 + i), 1); mbar_init(BAR(B_FL + i), 1); mbar_init(BAR(B_FL + 4 + i), 1); }
#pragma unroll
            for (int i = 0; i < 4; i++) mbar_init(XBAR(i), 1);
            asm volatile("fence.mbarrier_init.release.cluster;" ::: "memory");
        }
        __syncwarp();
    }
    if (warp == 14) {
        if (elect_one()) {
#pragma unroll
            for (int i = 0; i < 8; i++) { mbar_init(BAR(B_EL + i), 1); mbar_init(XBAR(4 + i), 1); if (i < 6) mbar_init(BAR(B_ES + i), 2); }
            asm volatile("fence.mbarrier_init.release.cluster;" ::: "memory");
        }
        __syncwarp();
    }
    if (warp == 15) {
        if (elect_one()) {
            mbar_init(BAR(B_FS), 1); mbar_init(BAR(B_FS + 1), 1);
#pragma unroll
            for (int i = B_SRD; i < B_COUNT; i++) mbar_init(BAR(i), i == B_GO ? 2 : i == B_STATS || i == B_LST ? 4 : 1);
#pragma unroll
            for (int i = 0; i < 4; i++) mbar_expect_tx(BAR(B_RECV + i), SLOT / 2);
            mbar_expect_tx(BAR(B_PEER), 1024); mbar_expect_tx(BAR(B_H), 128);
            asm volatile("fence.mbarrier_init.release.cluster;" ::: "memory");
        }
        __syncwarp();
    }
    CLUSTER_ARRIVE();
    if ((sb & 0xffffffu) != SB0) return;

#define GATHER(ptr, cnt, valid) do { int n = 0; bool ok; _Pragma("unroll 1") do { ok = true; \
                _Pragma("unroll") for (int i = 0; i < (cnt); i++) { f[i] = ld_relaxed128((ptr) + i * 32); ok = ok && (valid); } \
                if (__all_sync(0xffffffffu, ok)) break; \
                __nanosleep(GSL); \
            } while (++n < SPIN_LIMIT); } while (0)
    if (warp >= 8 && warp < 12) {
        asm volatile("setmaxnreg.dec.sync.aligned.u32 %0;" ::"n"(512 - PROD_REGS - 2 * CONS_REGS));
        const int aw = warp - 8, mt = tid - 256;
        unsigned ep;
        {
            const uint8_t* rp = smem + OFF_S + aw * 2048 + lane * 16;
            const __nv_bfloat16* dp = at(c ? P.dim : P.dre, (r * 128 + g * 16 + aw * 4) * D_ * 2);
            float wf[32], sw = 0.f;
#pragma unroll
            for (int i = 0; i < 4; i++) {
                const uint4 w = __ldg(reinterpret_cast<const uint4*>(at(P.wr, lane * 16) + i * 256));
                const uint32_t wv[4] = {w.x, w.y, w.z, w.w};
#pragma unroll
                for (int e = 0; e < 4; e++) { wf[8 * i + 2 * e] = bf_lo(wv[e]); wf[8 * i + 2 * e + 1] = bf_hi(wv[e]); sw = (sw + bf_lo(wv[e])) + bf_hi(wv[e]); }
            }
            ep = load_epoch(b);
            sw = warp_sum(sw);
            CLUSTER_WAIT();
            float x0[4] = {}, s1[4] = {}, s2[4] = {}, sx[4] = {}, sd[4] = {};
#define PUSH(a, v) do { a[0] = a[1]; a[1] = a[2]; a[2] = a[3]; a[3] = v; } while (0)
#pragma unroll 1
            for (int k = 0; k < 4; k++) {
                mbar_wait(XBAR(k), 0);
                uint4 v[4];
#pragma unroll
                for (int i = 0; i < 4; i++) v[i] = *reinterpret_cast<const uint4*>(rp + k * 8192 + i * 512);
                uint32_t sh = v[0].x << 16;
                float a1s = 0.f, a2s = 0.f, axs = 0.f;
#pragma unroll
                for (int i = 0; i < 4; i++) {
                    sh = __shfl_sync(0xffffffffu, sh | (__float_as_uint(axs) & zero), 0);
                    const uint32_t xv[4] = {v[i].x, v[i].y, v[i].z, v[i].w};
#pragma unroll
                    for (int e = 0; e < 4; e++) {
                        const float a0 = bf_lo(xv[e]) - __uint_as_float(sh), a1 = bf_hi(xv[e]) - __uint_as_float(sh);
                        a1s += a0 + a1;
                        a2s = fmaf(a0, a0, fmaf(a1, a1, a2s));
                        axs = fmaf(a0, wf[8 * i + 2 * e], fmaf(a1, wf[8 * i + 2 * e + 1], axs));
                    }
                }
                PUSH(x0, __uint_as_float(sh)); PUSH(s1, a1s); PUSH(s2, a2s); PUSH(sx, axs);
                fence_async_smem();
                __syncwarp();
                if (elect_one()) {
                    const uint32_t db = XBAR(k == 3 ? 8 + aw : 4 + aw);
                    if (k == 0 || k == 3) mbar_expect_tx(db, k ? 2048 : 6144);
                    bulk_g2s(sb + OFF_S + k * 8192 + aw * 2048, dp + k * D_, 2048, db);
                }
            }
#define FOLD4(a) do { const bool u16 = lane & 16, u8 = lane & 8; \
                float p0 = (u16 ? a[2] : a[0]) + __shfl_xor_sync(0xffffffffu, u16 ? a[0] : a[2], 16); \
                float p1 = (u16 ? a[3] : a[1]) + __shfl_xor_sync(0xffffffffu, u16 ? a[1] : a[3], 16); \
                a[0] = (u8 ? p1 : p0) + __shfl_xor_sync(0xffffffffu, u8 ? p0 : p1, 8); \
                _Pragma("unroll") for (int o = 4; o; o >>= 1) a[0] += __shfl_xor_sync(0xffffffffu, a[0], o); } while (0)
#pragma unroll 1
            for (int k = 0; k < 4; k++) {
                mbar_wait(XBAR(k == 3 ? 8 + aw : 4 + aw), 0);
                float run = 0.f;
#pragma unroll
                for (int i = 0; i < 4; i++) {
                    const uint4 v = *reinterpret_cast<const uint4*>(rp + k * 8192 + i * 512);
                    const uint32_t dv[4] = {v.x, v.y, v.z, v.w};
#pragma unroll
                    for (int e = 0; e < 4; e++) run += bf_lo(dv[e]) + bf_hi(dv[e]);
                }
                PUSH(sd, run);
            }
            named_bar<4, 128>();
            if (mt < 12) asm volatile("mbarrier.inval.shared::cta.b64 [%0];" ::"r"(XBAR(mt)) : "memory");
            FOLD4(sd); FOLD4(s1); FOLD4(s2); FOLD4(sx);
            const float nb = __shfl_down_sync(0xffffffffu, sd[0], 8);
            if ((lane & 15) == 0)
                st_relaxed128(at(g_rs, (grp * 64 + g * 8 + aw * 2 + (lane >> 4)) * 16), make_uint4(__float_as_uint(sd[0]), ep, __float_as_uint(nb), ep));
            if (mt == 0) PROF_T(6);
            const int rr = lane >> 3;
            const float c0 = rr == 0 ? x0[0] : rr == 1 ? x0[1] : rr == 2 ? x0[2] : x0[3];
            const float dm = s1[0] * (1.0f / D_);
            const float mb = rbf(c0 + dm);
            const float rinv = rcp_f(rbf(sqrt_f(rbf(rbf(fmaxf(s2[0] * (1.0f / D_) - dm * dm, 0.f)) + 1e-5f))));
            if ((lane & 7) == 0) st_relaxed128(at(g_stat, (b * 16 + aw * 4 + rr) * 16), make_uint4(__float_as_uint(mb), __float_as_uint(rinv), ep, 0));
            unsigned u = __bfloat16_as_ushort(__float2bfloat16_rn((sx[0] + (c0 - mb) * sw) * rinv));
            u = (u & 0x8000u) ? (~u & 0xffffu) : (u | 0x8000u);
            u = (u << 16) | (0xffffu - (unsigned)(b * 16 + rr * 4 + aw));
            u = __reduce_max_sync(0xffffffffu, u);
            if (lane == 0) { *reinterpret_cast<unsigned*>(smem + OFF_XB + aw * 4) = u; mbar_arrive(BAR(B_LST)); }
            if (mt == 0) PROF_T(2);
            uint4 f[4];
            if (aw < 2) {
                const int t = SREC(aw * 128 + lane);
                GATHER(at(g_stat, (g * 256 + aw * 128 + lane) * 16), 4, f[i].z == ep);
#pragma unroll
                for (int i = 0; i < 4; i++) {
                    *reinterpret_cast<uint32_t*>(smem + OFF_RSTD + (POS(t) + i * 32) * 4) = f[i].y;
                    *reinterpret_cast<uint16_t*>(smem + OFF_MEAN + (POS(t) + i * 32) * 2) = (uint16_t)(f[i].x >> 16);
                }
            } else {
                const int e2 = (aw - 2) * 32 + lane;
                GATHER(at(g_rs, (grp * 64 + e2) * 16), 1, f[i].y == ep && f[i].w == ep);
#pragma unroll
                for (int i = 0; i < 2; i++) {
                    const float v = __uint_as_float(i ? f[0].z : f[0].x);
                    const float hi = rbf(v), mid = rbf(v - hi), lo = v - hi - mid;
                    *reinterpret_cast<uint4*>(smem + OFF_RS + (e2 * 2 + i) * 16) = make_uint4(pack_bf(hi, mid), pack_bf(lo, 0.f), 0, 0);
                }
            }
            fence_async_smem();
            __syncwarp();
            if (lane == 0) mbar_arrive(BAR(B_STATS));
            if (mt == 127) PROF_T(9);
        }
        const bool moe = pr < 28 || pr >= 36;
        const int pair = pr < 28 ? pr : pr - 8;
        if (moe) {
            const uint64_t pol = policy_evict_first();
            const __nv_bfloat16* wp = at((aw & 1) ? P.wu : P.wg, ((c * 512 + (aw >> 1) * 256 + (lane >> 3) * 8) * F_ + pair * 64 + (lane & 7) * 8) * 2);
            uint4 b0[8], b1[8];
#define FILL(buf, str) do { _Pragma("unroll") for (int q = 0; q < 8; q++) buf[q] = ldg_stream(wp + q * (str), pol); } while (0)
#define PAUSE() do { if (mbar_test(BAR(B_QUIET), 0)) mbar_wait_sleep(BAR(B_GO), 0); } while (0)
#define FILLO(buf, row) do { _Pragma("unroll") for (int q = 0; q < 8; q++) buf[q] = ldg_stream_ord(wp + ((row) + q) * F_, pol); } while (0)
            FILLO(b0, 0);
            mbar_wait(BAR(B_SEL), 0);
            uint4 xn;
            {
                const int sel = ~*reinterpret_cast<volatile unsigned*>(smem + OFF_SEL) & (S_ - 1);
                xn = __ldg(reinterpret_cast<const uint4*>(at(P.x, (sel * D_ + c * 512 + (aw >> 1) * 256 + (lane & 7) * 32 + (lane >> 3) * 8) * 2)));
                uint4 f[1];
                GATHER(at(g_stat, SREC(sel) * 16), 1, f[i].z == ep);
                FILLO(b1, 32);
                PAUSE();
                const float m = __uint_as_float(f[0].x), ri = __uint_as_float(f[0].y);
                xn = make_uint4(norm2(xn.x, m, ri), norm2(xn.y, m, ri), norm2(xn.z, m, ri), norm2(xn.w, m, ri));
            }
            float ag[8];
#pragma unroll
            for (int i = 0; i < 8; i++) ag[i] = 0.f;
#define ROUND(cur, nxt, rd) do { \
                PAUSE(); \
                if (lane == 0) TRACE(192 + aw * 12 + (rd)); \
                if ((rd) == 7) wp = at(P.wd - 16 * D_, ((pair * 64 + (lane >> 4) * 8) * D_ + c * 512 + aw * 128 + (lane & 15) * 8) * 2); \
                wp = at(wp, ((rd) < 7 ? 64 * F_ : 32 * D_) + (cur[7].x & zero)); \
                if ((rd) & 7) { if ((rd) < 7) FILL(nxt, F_); else if ((rd) < 11) FILL(nxt, D_); } \
                _Pragma("unroll") for (int q = 0; q < 8; q += 2) { \
                    const uint32_t xw = __shfl_sync(0xffffffffu, q == 0 ? xn.x : q == 2 ? xn.y : q == 4 ? xn.z : xn.w, (lane & 24) | ((rd) & 7)); \
                    fma8(ag, cur[q], bf_lo(xw)); \
                    fma8(ag, cur[q + 1], bf_hi(xw)); \
                    if (q < 6) yield(ag[7], zero); \
                } } while (0)
#pragma unroll 1
            for (int rd = 0; rd < 12; rd += 2) {
                ROUND(b0, b1, rd);
                ROUND(b1, b0, rd + 1);
                if (rd == 6 || rd == 10) {
#pragma unroll
                    for (int i = 0; i < 8; i++) ag[i] += __shfl_xor_sync(0xffffffffu, ag[i], 16);
                }
                if (rd == 6) {
#pragma unroll
                    for (int i = 0; i < 8; i++) ag[i] += __shfl_xor_sync(0xffffffffu, ag[i], 8);
                    if (lane < 8) {
                        const uint32_t dst = mapa(sb + OFF_XB + (c * 4 + aw) * 128 + (lane & 3) * 32, lane >> 2), pb = mapa(BAR(B_PEER), lane >> 2);
                        st_async4(dst, __float_as_uint(ag[0]), __float_as_uint(ag[1]), __float_as_uint(ag[2]), __float_as_uint(ag[3]), pb);
                        st_async4(dst + 16, __float_as_uint(ag[4]), __float_as_uint(ag[5]), __float_as_uint(ag[6]), __float_as_uint(ag[7]), pb);
                    }
                    __syncwarp();
                    wp += 16 * D_; FILL(b1, D_); wp -= 16 * D_;
                    if (aw == 3) {
                        mbar_wait_cluster(BAR(B_PEER), 0);
                        const float* ps = reinterpret_cast<const float*>(smem + OFF_XB) + lane;
                        const float go = (ps[0] + ps[64]) + (ps[128] + ps[192]), uo = (ps[32] + ps[96]) + (ps[160] + ps[224]);
                        const float h = rbf(silu_f(rbf(go))) * rbf(uo), ho = __shfl_xor_sync(0xffffffffu, h, 1);
                        asm volatile("st.async.weak.shared::cluster.mbarrier::complete_tx::bytes.b32 [%0], %1, [%2];"
                                     ::"r"(mapa(sb + OFF_H + c * 64 + (lane >> 1) * 4, lane & 1)), "r"((lane & 1) ? pack_bf(ho, h) : pack_bf(h, ho)),
                                       "r"(mapa(BAR(B_H), lane & 1)) : "memory");
                    }
                    mbar_wait_cluster(BAR(B_H), 0);
                    xn = *reinterpret_cast<const uint4*>(smem + OFF_H + (lane & 3) * 32 + (lane >> 4) * 16);
#pragma unroll
                    for (int i = 0; i < 8; i++) ag[i] = 0.f;
                    if (mt == 0) PROF_T(10);
                }
            }
            const int hi = lane >> 4;
            st_relaxed128(at(g_part, pair * 4096 + (c * 8 + aw * 2 + ((lane >> 3) & 1)) * 256 + hi * 128 + (lane & 7) * 16),
                          make_uint4((__float_as_uint(hi ? ag[4] : ag[0]) & ~15u) | (ep & 15u), __float_as_uint(hi ? ag[5] : ag[1]),
                                     __float_as_uint(hi ? ag[6] : ag[2]), __float_as_uint(hi ? ag[7] : ag[3])));
            if (mt == 0) PROF_T(11);
        } else {
            mbar_wait_sleep(BAR(B_SEL), 0);
        }
        const int sel = ~*reinterpret_cast<volatile unsigned*>(smem + OFF_SEL) & (S_ - 1);
        if ((sel >> 8) == g) {
            const int col = (lane & 7) * 8 + ((lane >> 3) & 1) * 4;
            const uint2 xv = __ldg(reinterpret_cast<const uint2*>(at(P.x, (sel * D_ + grp * 64 + col) * 2)));
            uint4 f[1];
            GATHER(at(g_stat, SREC(sel) * 16), 1, f[i].z == ep);
            const uint4 rec = f[0];
            const uint4* src = at(g_part, (aw * 14 + (lane >> 4)) * 4096 + grp * 256 + (lane & 15) * 16);
            if (!moe) {
                int n = 0;
                while (((ld_relaxed(src) ^ ep) & 15u) != 0 && ++n < SPIN_LIMIT) __nanosleep(500);
            }
            uint4 t[7];
            int n = 0;
            bool ok;
            do {
                ok = true;
#pragma unroll
                for (int u = 0; u < 7; u++) { t[u] = ld_relaxed128(src + u * 512); ok = ok && ((t[u].x ^ ep) & 15u) == 0; }
            } while (!__all_sync(0xffffffffu, ok) && ++n < SPIN_LIMIT);
            float4 a = make_float4(0.f, 0.f, 0.f, 0.f);
#pragma unroll
            for (int u = 0; u < 7; u++) {
                a.x += __uint_as_float(t[u].x & ~15u); a.y += __uint_as_float(t[u].y); a.z += __uint_as_float(t[u].z); a.w += __uint_as_float(t[u].w);
            }
            a.x += __shfl_xor_sync(0xffffffffu, a.x, 16); a.y += __shfl_xor_sync(0xffffffffu, a.y, 16);
            a.z += __shfl_xor_sync(0xffffffffu, a.z, 16); a.w += __shfl_xor_sync(0xffffffffu, a.w, 16);
            float4* park = reinterpret_cast<float4*>(smem + OFF_XB) + (lane & 15);
            if (lane < 16) park[aw * 16] = a;
            named_bar<4, 128>();
            if (aw == 0) {
                const float4 p1 = park[16], p2 = park[32], p3 = park[48];
                a.x = (a.x + p1.x) + (p2.x + p3.x); a.y = (a.y + p1.y) + (p2.y + p3.y);
                a.z = (a.z + p1.z) + (p2.z + p3.z); a.w = (a.w + p1.w) + (p2.w + p3.w);
                unsigned u = *reinterpret_cast<volatile unsigned*>(smem + OFF_SEL) >> 16;
                u = (u & 0x8000u) ? (u & 0x7fffu) : (~u & 0xffffu);
                const float sg = rbf(__fdividef(1.0f, 1.0f + __expf(-__uint_as_float(u << 16))));
                const float m = __uint_as_float(rec.x), ri = __uint_as_float(rec.y);
                const uint32_t n0 = norm2(xv.x, m, ri), n1 = norm2(xv.y, m, ri);
                uint2 o;
                o.x = silu2(pack_bf(bf_lo(n0) + rbf(rbf(a.x) * sg), bf_hi(n0) + rbf(rbf(a.y) * sg)));
                o.y = silu2(pack_bf(bf_lo(n1) + rbf(rbf(a.z) * sg), bf_hi(n1) + rbf(rbf(a.w) * sg)));
                if (lane < 16) *reinterpret_cast<uint2*>(smem + OFF_H + col * 2) = o;
                __syncwarp();
                if (lane == 0) { mbar_arrive(BAR(B_UPD)); PROF_T(12); }
            }
        }
    } else if (warp < 8) {
        asm volatile("setmaxnreg.inc.sync.aligned.u32 %0;" ::"n"(CONS_REGS));
        CLUSTER_WAIT();
        const int wg = warp >> 2, wq = warp & 3;
        const int wt = tid & 127;
        float acc[128];
        const uint32_t fL = BAR(B_FL + 4 * wg), eL = BAR(B_EL + 4 * wg);
        const uint32_t dL = desc_lo(SB0 + OFF_L, 16) + wg * 4096;
        constexpr uint32_t dS = desc_lo(SB0 + OFF_S, 16);
        constexpr uint32_t SL = SLOT >> 4;
#define RELEASE(ls, ss) do { if (wt == 0) { mbar_arrive(eL + 8u * (ls)); mbar_arrive(BAR(B_ES + (ss))); } } while (0)
#define WAIT_FULL(ls, lph, ss, sph) do { mbar_wait(BAR(B_FS + (ss)), sph); mbar_wait(fL + 8u * (ls), lph); } while (0)
#define TURN() do { if (wg) named_bar<6, 256>(); else named_bar<5, 256>(); } while (0)
#define PASS() do { if (wg) named_arrive<5, 256>(); else named_arrive<6, 256>(); } while (0)
#define WG_BAR() do { if (wg) named_bar<2, 128>(); else named_bar<1, 128>(); } while (0)
        if (wg == 1) PASS();

#define MMA1_H(O, s, first) do { _Pragma("unroll") for (int kk = 0; kk < 4; kk++) \
            wgmma128<O, 0>(acc, dL + (s) * SL + kk * 2 + (O) * 8, dS + DSLOT(s) * SL + kk * 2, !((first) && kk == 0)); } while (0)
#define WAIT1(s, ph) WAIT_FULL(s, ph, DSLOT(s), ph)
#define PROBE(ls, lph, ss, sph) (mbar_test(BAR(B_FS + (ss)), sph) & mbar_test(fL + 8u * (ls), lph))
#define REL1(s) RELEASE(s, DSLOT(s))
#pragma unroll 1
        for (int it = 0; it < 12; it++) {
            const int s = it & 3;
            const bool ok = PROBE(s, (it >> 2) & 1, DSLOT(s), (it >> 2) & 1);
            if (it) { wg_wait<0>(); REL1((s + 3) & 3); }
            if (!ok) WAIT1(s, (it >> 2) & 1);
            TURN();
            wg_fence(); MMA1_H(0, s, it == 0); MMA1_H(64, s, it == 0); wg_commit();
            PASS();
            if (it == 0 && tid == 0) PROF_T(16);
        }
        TS(12);
        float rs[4] = {};
        uint32_t nm[8] = {};
#define GET_STATS() do { mbar_wait(BAR(B_STATS), 0); \
            const int p0 = POS(wg * 128 + wq * 16 + (lane >> 2));                   \
            const uint32_t msk = (lane & 3) == 0 ? 0xffffffffu : (lane & 3) == 1 ? 0x0000ffffu : 0u; \
            _Pragma("unroll") for (int i = 0; i < 4; i++) { \
                const int p = p0 + (i & 1) * 2 + (i >> 1) * 64; \
                rs[i] = *reinterpret_cast<const float*>(smem + OFF_RSTD + p * 4); \
                const uint32_t m = *reinterpret_cast<const uint16_t*>(smem + OFF_MEAN + p * 2) ^ 0x8000u; \
                nm[i + (i & 2)] = (m | (m << 16)) & msk; \
            } } while (0)
        const bool early = wg || __all_sync(0xffffffffu, mbar_test(BAR(B_STATS), 0));
        if (early && !wg) GET_STATS();
        WAIT1(0, 1);
        TS(13);
        wg_wait<0>(); REL1(3);
        if (wg) GET_STATS();
        TS(14);
        TURN();
        wg_fence();
        MMA1_H(0, 0, false);
        if (tid == 0) { mbar_arrive(BAR(B_QUIET)); PROF_T(15); }
        WAIT1(1, 1); wg_fence(); MMA1_H(0, 1, false);
        WAIT1(2, 1); wg_fence(); MMA1_H(0, 2, false); wg_commit();
        if (!early) GET_STATS();
        asm volatile("" : "+r"(nm[0]), "+r"(nm[1]), "+r"(nm[2]), "+r"(nm[3]), "+r"(nm[4]), "+r"(nm[5]), "+r"(nm[6]), "+r"(nm[7])::"memory");
        wg_fence();
        wgmma128_rs<64>(acc, nm + 4, (SB0 + OFF_RS) >> 4);
        wgmma128_rs<0>(acc, nm, (SB0 + OFF_RS) >> 4);
        WAIT1(3, 1); wg_fence(); MMA1_H(0, 3, false); wg_commit();
        PASS();
        const int mrow = wq * 16 + ((lane >> 3) & 1) * 8 + (lane & 7);
#define EPI1(O, slot, FREE) do { const uint32_t dst = sb + OFF_S + (slot) * SLOT + mrow * 128; \
            uint32_t pk[32]; \
            _Pragma("unroll") for (int i = 0; i < 32; i += 4) { \
                _Pragma("unroll") for (int k = 0; k < 4; k++) \
                    pk[i + k] = pack_bf(acc[(O) + 2 * (i + k)] * rs[(O) / 32 + (k & 1)], acc[(O) + 2 * (i + k) + 1] * rs[(O) / 32 + (k & 1)]); \
                if (i == EF) { FREE; } \
                if (i >= EF) { _Pragma("unroll") for (int v = (i == EF ? 0 : i); v <= i; v += 4) \
                    stmatrix4(dst + ((v >> 4) ^ c ^ 1) * 8192 + ((((v >> 1) & 7) + (lane >> 4)) ^ (lane & 7)) * 16, pk[v], pk[v + 1], pk[v + 2], pk[v + 3]); } } \
            WG_BAR(); \
            if (wt == 0) mbar_arrive(BAR(B_FS + (slot))); } while (0)
        TS(15);
        wg_wait<0>();
        fence_regs64<0>(acc);
        TS(16);
        {
            constexpr int EF = 0;
            EPI1(0, wg, if (wg) mbar_wait(BAR(B_FS), 0));
        }
        TS(17);
        TURN();
        wg_fence();
        MMA1_H(64, 0, false); wg_commit();
        MMA1_H(64, 1, false); wg_commit();
        MMA1_H(64, 2, false); wg_commit();
        wg_wait<2>(); REL1(0);
        MMA1_H(64, 3, false); wg_commit();
        PASS();
        TS(18);
        wg_wait<2>(); REL1(1);
        mbar_wait(BAR(B_FS), 0); mbar_wait(BAR(B_FS + 1), 0); fence_async_smem();
        wg_wait<1>(); REL1(2);
        wg_wait<0>(); REL1(3);
        fence_regs64<64>(acc);
        TS(19);
        {
            constexpr int EF = 16;
            EPI1(64, 2 + wg, mbar_wait(BAR(B_ES + 2 + wg), 1));
        }
        TS(20);

        float ac2[128];
#define MMA2_H(O, ls, ss, first) do { _Pragma("unroll") for (int kk = 0; kk < 4; kk++) \
            wgmma128<O, 1>(ac2, dS + (ss) * SL + kk * 128 + (O) * 8, dL + (ls) * SL + kk * 2, !((first) && kk == 0)); } while (0)
#define WAIT2(j) WAIT_FULL((j) & 3, ((j) >> 2) & 1, PSLOT(j), PPAR(j))
#define MMA2(j) do { wg_fence(); MMA2_H(0, (j) & 3, PSLOT(j), (j) == 0); MMA2_H(64, (j) & 3, PSLOT(j), (j) == 0); wg_commit(); } while (0)
#define REL2(j) RELEASE((j) & 3, PSLOT(j))
        WAIT2(0); TURN(); MMA2(0);
        WAIT2(1); MMA2(1); PASS();
        TS(21);
        wg_wait<1>(); REL2(0);
        mbar_wait(BAR(B_FS + 2), 0); mbar_wait(BAR(B_FS + 3), 0); fence_async_smem();
        TS(22);
        {
            uint32_t l2 = 2, s2 = 2, sp = 1, lph = 0, sph = 0;
#pragma unroll 1
            for (int j = 2; j < XJ; j += 2) {
#pragma unroll
                for (int h = 0; h < 2; h++) {
                    const bool ok = PROBE(l2 + h, lph, s2 + h, sph);
                    wg_wait<0>(); RELEASE(h ? l2 : 3 - l2, h ? s2 : sp);
                    if (!ok) WAIT_FULL(l2 + h, lph, s2 + h, sph);
                    TURN();
                    wg_fence(); MMA2_H(0, l2 + h, s2 + h, false); MMA2_H(64, l2 + h, s2 + h, false); wg_commit();
                    PASS();
                    if (h == (GOJ & 1) && j == (GOJ & ~1) && wt == 0) { mbar_arrive(BAR(B_GO)); if (wg == 0) PROF_T(19); }
                }
                sp = s2 + 1; s2 = 2 * l2; sph = lph; l2 ^= 2;
                lph ^= l2 == 0;
            }
        }
        if (tid == 0) PROF_T(20);
        uint32_t gt[32];
        const uint32_t xrow = sb + OFF_S + 2 * SLOT + wg * 8192 + ((lane >> 4) * 8 + (lane & 7)) * 128 + (((2 * wq + ((lane >> 3) & 1)) ^ (lane & 7)) << 4);
        const uint32_t gsign = c ? 0x80008000u : 0u;
#define XOFF(v) (((v) >> 2) * SLOT + ((v) & 3) * 2048)
        int sel = 0;
        bool own = false;
#define PATCH() do { own = false; \
            const uint32_t v0 = *reinterpret_cast<const uint16_t*>(smem + OFF_H + (wq * 16 + (lane >> 2)) * 2) ^ gsign; \
            const uint32_t v1 = *reinterpret_cast<const uint16_t*>(smem + OFF_H + (wq * 16 + (lane >> 2)) * 2 + 16) ^ gsign; \
            const uint32_t pick = (lane & 3) != ((sel >> 1) & 3) ? 0x3210u : (sel & 1) ? 0x5410u : 0x3254u; \
            _Pragma("unroll") for (int i = 0; i < 16; i++) { \
                const uint32_t m = ((sel >> 3) & 15) == i ? pick : 0x3210u; \
                gt[2 * i] = __byte_perm(gt[2 * i], v0, m); \
                gt[2 * i + 1] = __byte_perm(gt[2 * i + 1], v1, m); \
            } } while (0)
#pragma unroll
        for (int u = 0; u < 8; u++) {
            if (u) { WAIT2(XJ + u - 1); wg_wait<0>(); REL2(XJ + u - 2); TURN(); MMA2(XJ + u - 1); PASS(); }
            uint32_t* o = &gt[4 * u];
            if (!(u & 3)) mbar_wait(BAR(B_FS + 2 + (u >> 2)), 1);
            ldmatrix4t(xrow + XOFF(u), o[0], o[1], o[2], o[3]);
            const float4 r4 = *reinterpret_cast<const float4*>(smem + OFF_RSTD + (wg * 128 + u * 16 + (lane & 3) * 4) * 4);
            const uint2 m2 = *reinterpret_cast<const uint2*>(smem + OFF_MEAN + (wg * 128 + u * 16 + (lane & 3) * 4) * 2);
            o[0] = gate2(o[0], m2.x, r4.x, r4.y) ^ gsign;
            o[1] = gate2(o[1], m2.x, r4.x, r4.y) ^ gsign;
            o[2] = gate2(o[2], m2.y, r4.z, r4.w) ^ gsign;
            o[3] = gate2(o[3], m2.y, r4.z, r4.w) ^ gsign;
            if (u == 2) {
                mbar_wait(BAR(B_SEL), 0);
                sel = ~*reinterpret_cast<volatile unsigned*>(smem + OFF_SEL) & (S_ - 1);
                own = (sel >> 7) == 2 * g + wg;
            }
            asm volatile("st.shared.v2.u32 [%0], {%1,%2};" ::"r"(sb + OFF_SEL + 16), "r"(o[0] ^ o[1]), "r"(o[2] ^ o[3]) : "memory");
        }
        if (tid == 0) PROF_T(21);
        WAIT2(27);
        wg_wait<0>(); REL2(26);
        if (own) {
            const uint32_t t0 = clock32();
            bool ok;
            while (!(ok = mbar_test(BAR(B_UPD), 0)) && clock32() - t0 < wg * 1900u) __nanosleep(50);
            if (__all_sync(0xffffffffu, ok)) PATCH();
        }
        TS(0);
        TURN();
        MMA2(27);
        WAIT2(28); wg_fence(); MMA2_H(0, 0, PSLOT(28), false); wg_commit();
        if (wg == 0) { wg_fence(); MMA2_H(64, 0, PSLOT(28), false); wg_commit(); }
        constexpr uint32_t dL0 = desc_lo(SB0 + OFF_L, 16);
        const uint32_t ct[3] = {wg ? 3u : 1u, wg ? 1u : 2u, wg ? 2u : 5u};
#define TMMA(O, i) wgmma128<O, 1>(ac2, ((i) < 8 ? dS + PSLOT(29 + ((i) >> 2)) * SL : dL0 + 6 * SL) + ((i) & 3) * 128 + (O) * 8, \
                                  dL0 + ct[(i) >> 2] * SL + ((i) & 3) * 2, 1)
#define KEEP(i) TMMA(64, i)
#pragma unroll
        for (int k = 0; k < 3; k++) {
            if (k < 2) mbar_wait(BAR(B_FS + PSLOT(29 + k)), PPAR(29 + k)); else mbar_wait(BAR(B_FL + 6), 1);
            mbar_wait(BAR(B_FL + ct[k]), k == 0 || wg == 0);
            wg_fence();
#pragma unroll
            for (int i = 4 * k; i < 4 * k + 4; i++) TMMA(0, i);
            wg_commit();
            if (k < 2) wg_wait<2>();
            if (k == 0 && tid == 0) mbar_arrive(BAR(B_R27));
            if (k == 1 && tid == 0) mbar_arrive_cluster(mapa(BAR(B_RDY), c ^ 1));
        }
        TS(1);
        wg_fence();
#pragma unroll
        for (int i = 0; i < KQ; i++) KEEP(i);
        wg_commit();
        mbar_wait(BAR(B_RDY + wg), 0);
        wg_wait<1>();
        fence_regs64<0>(ac2);
        TS(2);
        wg_fence();
        {
            const uint32_t dst = mapa(sb + OFF_L + wg * 5 * SLOT + wt * 16, c ^ 1), rb = mapa(BAR(B_RECV + 2 * wg), c ^ 1);
#pragma unroll
            for (int v = 0; v < 8; v++) {
                if (KQ + v < 12) KEEP(KQ + v);
                if (KQ + v == 7) wg_commit();
                if (KQ + v == 11) { wg_commit(); if (wg == 0) PASS(); }
                st_async4(dst + v * 2048, pack_bf(ac2[8 * v + 0], ac2[8 * v + 1]), pack_bf(ac2[8 * v + 2], ac2[8 * v + 3]),
                          pack_bf(ac2[8 * v + 4], ac2[8 * v + 5]), pack_bf(ac2[8 * v + 6], ac2[8 * v + 7]), rb + (v >> 2) * 8);
            }
        }
        if (wg == 1) { wg_fence(); MMA2_H(64, 0, PSLOT(28), false); wg_commit(); }
        TS(3);
        uint32_t xr[32];
#define LDX(v) ldmatrix4t(xrow + XOFF(v), xr[4 * (v)], xr[4 * (v) + 1], xr[4 * (v) + 2], xr[4 * (v) + 3])
        if (wg == 0) {
            wg_wait<2>();
            if (wt == 0) mbar_arrive(BAR(B_SRD));
            wg_wait<1>();
            if (wt == 0) mbar_arrive(BAR(B_SRD + 1));
        }
#pragma unroll
        for (int v = 0; v < XE; v++) LDX(v);
        if (wg == 0) {
            wg_wait<0>();
            if (wt == 0) mbar_arrive_cluster(mapa(BAR(B_RDY + 1), c ^ 1));
        }
        TS(4);
        if (own) { mbar_wait(BAR(B_UPD), 0); PATCH(); }
        TS(5);
        uint4 rv[8];
#define FETCH(v0) do { if ((v0) == 0 || (v0) == 4) mbar_wait_cluster(BAR(B_RECV + 2 * wg + (v0) / 4), 0); \
            _Pragma("unroll") for (int v = (v0); v < (v0) + 2; v++) { \
                asm volatile("ld.shared.v4.u32 {%0,%1,%2,%3}, [%4];" : "=r"(rv[v].x), "=r"(rv[v].y), "=r"(rv[v].z), "=r"(rv[v].w) \
                             : "r"(sb + OFF_L + wg * 5 * SLOT + v * 2048 + wt * 16) : "memory"); \
                if (v >= XE) LDX(v); } } while (0)
        FETCH(0);
        TS(6);
        wg_wait<0>();
        fence_regs64<64>(ac2);
        TS(7);
#pragma unroll
        for (int v0 = 0; v0 < 8; v0 += 2) {
#pragma unroll
            for (int v = v0; v < v0 + 2; v++) {
                const float* a = &ac2[64 + 8 * v];
                stmatrix4t(xrow + XOFF(v),
                           bfma2(bsub2(pack_bf(a[0], a[1]), rv[v].x), gt[4 * v + 0], xr[4 * v + 0]),
                           bfma2(bsub2(pack_bf(a[2], a[3]), rv[v].y), gt[4 * v + 1], xr[4 * v + 1]),
                           bfma2(bsub2(pack_bf(a[4], a[5]), rv[v].z), gt[4 * v + 2], xr[4 * v + 2]),
                           bfma2(bsub2(pack_bf(a[6], a[7]), rv[v].w), gt[4 * v + 3], xr[4 * v + 3]));
            }
            WG_BAR();
            if (wt == 0) mbar_arrive(eL + 4 * v0);
            if (v0 + 2 < 8) FETCH(v0 + 2);
            if (v0 == 0) TS(8);
        }
        TS(9);
    } else {
        asm volatile("setmaxnreg.dec.sync.aligned.u32 %0;" ::"n"(PROD_REGS));
#define XROWS(k) do { mbar_expect_tx(XBAR(k), 8192); bulk_g2s(sb + OFF_S + (k) * 8192, at(P.x, (b * 16 + (k) * 4) * D_ * 2), 8192, XBAR(k)); } while (0)
        if (warp == 12) {
            if (elect_one()) {
                const CUtensorMap* tmD = c ? &tm_dim : &tm_dre;
#pragma unroll 1
                for (int it = 1; it < 4; it++) {
                    while (clock32() - (uint32_t)tstart < LDEL + (it - 1) * LGAP) {}
                    LOAD0(it);
                    if (it >= X0) XROWS(it - X0);
                }
            }
            __syncwarp();
        }
        CLUSTER_WAIT();
        if (warp == 12) {
            if (elect_one()) {
                const CUtensorMap* tmD = c ? &tm_dim : &tm_dre;
#pragma unroll 1
                for (int it = 4; it < 16; it++) {
                    const int s = DSLOT(it);
                    mbar_wait(BAR(B_ES + s), ((it >> 2) & 1) ^ 1);
                    TRACE(it);
                    mbar_expect_tx(BAR(B_FS + s), SLOT);
                    tma_2d(sb + OFF_S + s * SLOT, tmD, it * 64, r * 128, BAR(B_FS + s));
                    if (it < 4 + X0) XROWS(it - X0);
                }
                const unsigned ep = load_epoch(b), e8 = ep & 0xffu;
                const uint8_t* abg = at(AB, grp * 32 * SLOT);
                const unsigned long long* fl = at(g_flag, grp * 128);
                unsigned long long rdy = ld_acquire64(fl);
                mbar_wait(BAR(B_SRD), 0);
                st_release8(at(g_flag, grp * 128 + g), e8);
                PROF_T(7);
                int j = 4;
#pragma unroll 1
                for (int cl = 0; cl < 4; cl++) {
                    if (cl) rdy = ld_acquire64(++fl);
                    fence_async_global();
#pragma unroll 1
                    for (int n = 1; n < 8; n++, j++) {
                        const int q = BLK(n), s = (j & 1) + ((j & 2) ? 0 : 4);
                        const uint32_t fb = BAR(j == 31 ? B_FL + 6 : B_FS + s);
                        if (j == 31) mbar_wait(BAR(B_EL + 6), 0); else mbar_wait(BAR(B_ES + s), ((j >> 2) ^ (j >> 1)) & 1);
                        if (j == 7) mbar_wait(BAR(B_SRD + 1), 0);
                        if (((unsigned)(rdy >> (8 * q)) & 0xffu) != e8) {
                            int m = 0;
                            do { rdy = ld_acquire64(fl); } while (((unsigned)(rdy >> (8 * q)) & 0xffu) != e8 && ++m < SPIN_LIMIT);
                            fence_async_global();
                        }
                        TRACE(16 + j);
                        mbar_expect_tx(fb, SLOT);
                        bulk_g2s(sb + (j == 31 ? OFF_L + 6 * SLOT : OFF_S + s * SLOT), at(abg, (4 * q + KO(cl)) * SLOT), SLOT, fb);
                    }
                }
                *at(g_epoch, b * 4) = ep;
            }
        } else if (warp < 15) {
            if (elect_one()) {
                const int w = warp - 13, row0 = g * 256 + w * 128;
                const CUtensorMap* tmC = c ? &tm_cim : &tm_cre;
                const uint32_t fb = BAR(B_FL + 4 * w), eb = BAR(B_EL + 4 * w), dst = sb + OFF_L + w * 4 * SLOT;
                [[maybe_unused]] unsigned long long mk = 0, mg = 0;
                int n = 0, cl = 0;
#pragma unroll 1
                for (int it = 4; it < 47 - 2 * w; it++) {
                    const int s = it & 3;
                    mbar_wait(eb + 8 * s, ((it >> 2) & 1) ^ 1);
                    TRACE(64 + w * 64 + it - 4);
                    MARK(it);
                    mbar_expect_tx(fb + 8 * s, SLOT);
                    tma_2d(dst + s * SLOT, it < 16 ? &tm_x : tmC, (it < 16 ? it : 4 * (n ? BLK(n) : g) + KO(cl)) * 64, row0, fb + 8 * s);
                    if (it == PTJ) prefetch_tmap(w ? &tm_x64 : tmC);
                    if (it == PTJ && w) prefetch_tmap(&tm_out);
                    if (it >= 16) {
                        if (it == 19) { n = 1; cl = 0; } else if (it < 19) cl++; else if (++n == 8) { n = 1; cl++; }
                    }
                }
#pragma unroll 1
                for (int i = 2 * w; i < 3; i++) {
                    const int s = w ? 1 : i ? i : 3;
                    mbar_wait(w ? eb + 8 : BAR(i ? B_SRD - 1 + i : B_R27), w == 0 && i);
                    mbar_expect_tx(fb + 8 * s, SLOT);
                    tma_2d(dst + s * SLOT, tmC, (4 * BLK(5 + i) + 3) * 64, row0 ^ 128, fb + 8 * s);
                }
                if (w && (r & 3) < 2) tma_2d_prefetch(tmC, (4 * BLK(6 + (r & 1)) + 3) * 64, row0);
#pragma unroll 1
                for (int h = 0; h < 4; h++) {
                    mbar_wait(eb + 8 * h, h < 3);
                    fence_async_smem();
                    tma_2d_store(&tm_out, grp * 64, row0 + h * 32, sb + OFF_S + (2 + (h >> 1)) * SLOT + w * 8192 + (h & 1) * 4096);
                    bulk_commit();
                }
                FINISH(w);
            }
        } else {
            const unsigned ep = load_epoch(b);
            uint4 f[4];
            {
                sleep_until((uint32_t)tstart + 6000);
                const uint4* keys = at(reinterpret_cast<const uint4*>(g_key), lane * 16);
                bool mine = false;
                int n = 0;
                do {
                    f[0] = ld_relaxed128(keys); f[1] = ld_relaxed128(keys + 32);
                    if (__all_sync(0xffffffffu, f[0].y == ep && f[0].w == ep && f[1].y == ep && f[1].w == ep)) break;
                    if (!mine) {
                        mbar_wait(BAR(B_LST), 0);
                        const uint4 k = *reinterpret_cast<const uint4*>(smem + OFF_XB);
                        if (lane == 0) st_relaxed64(at(g_key, b * 8), ((unsigned long long)ep << 32) | max(max(k.x, k.y), max(k.z, k.w)));
                        mine = true;
                    }
                    __nanosleep(GSL);
                } while (++n < SPIN_LIMIT);
                const unsigned key = __reduce_max_sync(0xffffffffu, max(max(f[0].x, f[0].z), max(f[1].x, f[1].z)));
                if (lane == 0) { *reinterpret_cast<unsigned*>(smem + OFF_SEL) = key; mbar_arrive(BAR(B_SEL)); PROF_T(8); }
            }
            if (elect_one()) {
#pragma unroll 1
                for (int cl = 0; cl < 4; cl++) {
                    uint8_t* dst = at(AB, (grp * 32 + 4 * g + KO(cl)) * SLOT);
                    const uint32_t src = sb + OFF_S + cl * SLOT, chunk = cl ? 1024 : SLOT;
                    mbar_wait(BAR(B_FS + cl), 0);
                    fence_async_smem();
                    if (cl == 0) PROF_T(3);
                    uint32_t t0 = clock32() + (cl == 1 ? PDEL : 0);
#pragma unroll 1
                    for (uint32_t o = 0; o < SLOT; o += chunk) {
                        sleep_until(t0);
                        bulk_s2g(dst + o, src + o, chunk);
                        bulk_commit();
                        t0 += cl == 1 ? PGAP1 : cl == 2 ? PGAP2 : PGAP3;
                    }
                    bulk_wait<0>();
                    fence_async_global();
                    TRACE(252 + cl);
                    if (cl < 2) mbar_arrive(BAR(B_SRD + cl));
                    else {
                        mbar_wait(BAR(B_ES + cl), 0);
                        mbar_expect_tx(BAR(B_FS + cl), SLOT);
                        tma_2d(src, &tm_x64, grp * 64, g * 256 + (cl - 2) * 64, BAR(B_FS + cl));
                        tma_2d(src + 8192, &tm_x64, grp * 64, g * 256 + (cl - 2) * 64 + 128, BAR(B_FS + cl));
                    }
                    if (cl) st_release8(at(g_flag, grp * 128 + cl * 8 + g), ep & 0xffu);
                    if (cl == 1) PROF_T(5);
                    if (cl == 3) PROF_T(4);
                }
            }
        }
    }
}

typedef CUresult (*EncodeFn)(CUtensorMap*, CUtensorMapDataType, cuuint32_t, void*, const cuuint64_t*, const cuuint64_t*,
                             const cuuint32_t*, const cuuint32_t*, CUtensorMapInterleave, CUtensorMapSwizzle,
                             CUtensorMapL2promotion, CUtensorMapFloatOOBfill);

void make_map(EncodeFn fn, CUtensorMap* tm, const void* p, uint64_t rows, uint64_t cols, uint32_t box_rows) {
    cuuint64_t dims[2] = {cols, rows};
    cuuint64_t strides[1] = {cols * 2};
    cuuint32_t box[2] = {64, box_rows};
    cuuint32_t es[2] = {1, 1};
    fn(tm, CU_TENSOR_MAP_DATA_TYPE_BFLOAT16, 2, const_cast<void*>(p), dims, strides, box, es, CU_TENSOR_MAP_INTERLEAVE_NONE,
       CU_TENSOR_MAP_SWIZZLE_128B, CU_TENSOR_MAP_L2_PROMOTION_L2_128B, CU_TENSOR_MAP_FLOAT_OOB_FILL_NONE);
}

}

extern "C" void kernel_launch(void* const* d_in, const int* in_sizes, int n_in, void* d_out, int out_size) {
    (void)in_sizes; (void)n_in; (void)out_size;
    static EncodeFn fn = nullptr;
    if (!fn) {
        void* p = nullptr;
        cudaDriverEntryPointQueryResult q;
        cudaGetDriverEntryPoint("cuTensorMapEncodeTiled", &p, cudaEnableDefault, &q);
        fn = (EncodeFn)p;
        cudaFuncSetAttribute(fnet_fused_kernel, cudaFuncAttributeMaxDynamicSharedMemorySize, SMEM_BYTES);
    }
    CUtensorMap tx, tdre, tdim, tcre, tcim, tout, tx64;
    make_map(fn, &tx, d_in[0], S_, D_, 128);
    make_map(fn, &tcre, d_in[1], S_, S_, 128);
    make_map(fn, &tcim, d_in[2], S_, S_, 128);
    make_map(fn, &tdre, d_in[3], D_, D_, 128);
    make_map(fn, &tdim, d_in[4], D_, D_, 128);
    make_map(fn, &tx64, d_in[0], S_, D_, 64);
    make_map(fn, &tout, d_out, S_, D_, 32);
    Params P;
    P.x = (const __nv_bfloat16*)d_in[0];
    P.dre = (const __nv_bfloat16*)d_in[3];
    P.dim = (const __nv_bfloat16*)d_in[4];
    P.wr = (const __nv_bfloat16*)d_in[6];
    P.wg = (const __nv_bfloat16*)d_in[7];
    P.wu = (const __nv_bfloat16*)d_in[8];
    P.wd = (const __nv_bfloat16*)d_in[9];
    P.zero = 0;
    fnet_fused_kernel<<<NCTA, NTHREADS, SMEM_BYTES, cudaStreamPerThread>>>(tx, tdre, tdim, tcre, tcim, tout, tx64, P);
}
```

```cpp
#include <cuda_runtime.h>
#include <cuda_bf16.h>
#include <cuda.h>
#include <stdint.h>

#define GSL 200
#define SLEEP_NS 200
#define PDEL 1000
#define PGAP1 200
#define PGAP2 200
#define PGAP3 240
#define GOJ 2
#define LDEL 1400
#define LGAP 700
#define PTJ 10
#define X0 2
#define RDEL 8000
#define KQ 5
#define XE 2
#define PROD_REGS 32
#define CONS_REGS 184

namespace {

constexpr int S_ = 2048, D_ = 1024, F_ = 3584;
constexpr int NCTA = 128;
constexpr int XJ = 20;
constexpr uint32_t SLOT = 16384;
constexpr uint32_t OFF_L = 0;
constexpr uint32_t OFF_S = 8 * SLOT;
constexpr uint32_t OFF_RS = OFF_S + SLOT;
constexpr uint32_t OFF_BAR = 14 * SLOT;
constexpr uint32_t OFF_SEL = OFF_BAR + 360;
constexpr uint32_t OFF_RSTD = OFF_BAR + 384;
constexpr uint32_t OFF_MEAN = OFF_RSTD + 1024;
constexpr uint32_t OFF_XB = OFF_MEAN + 512;
constexpr uint32_t OFF_H = OFF_XB + 1024;
constexpr uint32_t SMEM_BYTES = OFF_H + 128;
constexpr uint32_t SB0 = 1024;
constexpr int NTHREADS = 512;
static_assert(SMEM_BYTES <= 232448, "smem");

enum { B_FS = 0, B_ES = 6, B_FL = 12, B_EL = 20, B_SRD = 28  , B_RECV = 30  , B_RDY = 34, B_STATS = 36, B_LST = 37, B_UPD = 38,
       B_QUIET = 39, B_GO = 40, B_PEER = 41, B_SEL = 42, B_H = 43, B_R27 = 44, B_COUNT = 45 };
static_assert(B_COUNT * 8 <= 360, "barriers");

__device__ __align__(1024) uint8_t g_ab[16u * 32u * SLOT];
__device__ __align__(128) uint4 g_part[56 * (D_ / 4)];
__device__ __align__(128) uint4 g_stat[S_];
__device__ __align__(128) uint4 g_rs[D_];
__device__ __align__(128) unsigned long long g_key[NCTA];
__device__ __align__(128) unsigned long long g_flag[16 * 16];
__device__ __align__(128) unsigned g_epoch[NCTA];
#define PROF_T(i) do {} while (0)
#define TRACE(i) do {} while (0)
#define PROF_G(i) do {} while (0)
#define TS(i) do {} while (0)
#define FINISH(wg) bulk_wait_read<0>()

#define MARK(it) do {} while (0)

__device__ __forceinline__ uint32_t smem_u32(const void* p) { return (uint32_t)__cvta_generic_to_shared(p); }
__device__ __forceinline__ void mbar_init(uint32_t bar, uint32_t cnt) {
    asm volatile("mbarrier.init.shared::cta.b64 [%0], %1;" ::"r"(bar), "r"(cnt) : "memory");
}
__device__ __forceinline__ bool mbar_try(uint32_t bar, uint32_t parity) {
    uint32_t ok;
    asm volatile("{\n.reg .pred p;\nmbarrier.try_wait.parity.shared::cta.b64 p, [%1], %2;\nselp.u32 %0, 1, 0, p;\n}"
                 : "=r"(ok) : "r"(bar), "r"(parity) : "memory");
    return ok;
}
__device__ __forceinline__ bool mbar_test(uint32_t bar, uint32_t parity) {
    uint32_t ok;
    asm volatile("{\n.reg .pred p;\nmbarrier.test_wait.parity.shared::cta.b64 p, [%1], %2;\nselp.u32 %0, 1, 0, p;\n}"
                 : "=r"(ok) : "r"(bar), "r"(parity) : "memory");
    return ok;
}
__device__ __forceinline__ bool mbar_try_cluster(uint32_t bar, uint32_t parity) {
    uint32_t ok;
    asm volatile("{\n.reg .pred p;\nmbarrier.try_wait.parity.acquire.cluster.shared::cta.b64 p, [%1], %2;\nselp.u32 %0, 1, 0, p;\n}"
                 : "=r"(ok) : "r"(bar), "r"(parity) : "memory");
    return ok;
}
constexpr int SPIN_LIMIT = 1 << 20;
__device__ __forceinline__ void mbar_wait(uint32_t bar, uint32_t parity) {
    if (mbar_try(bar, parity)) return;
    int n = 0;
    while (!mbar_try(bar, parity) && ++n < SPIN_LIMIT) {}
}
__device__ __forceinline__ void mbar_wait_cluster(uint32_t bar, uint32_t parity) {
    int n = 0;
    while (!mbar_try_cluster(bar, parity) && ++n < SPIN_LIMIT) {}
}
__device__ __forceinline__ void mbar_wait_sleep(uint32_t bar, uint32_t parity) {
    int n = 0;
    while (!mbar_try(bar, parity) && ++n < SPIN_LIMIT) __nanosleep(SLEEP_NS);
}
__device__ __forceinline__ void mbar_arrive(uint32_t bar) {
    asm volatile("mbarrier.arrive.shared::cta.b64 _, [%0];" ::"r"(bar) : "memory");
}
__device__ __forceinline__ void mbar_arrive_cluster(uint32_t cluster_bar) {
    asm volatile("mbarrier.arrive.shared::cluster.b64 _, [%0];" ::"r"(cluster_bar) : "memory");
}
__device__ __forceinline__ void mbar_expect_tx(uint32_t bar, uint32_t bytes) {
    asm volatile("mbarrier.arrive.expect_tx.shared::cta.b64 _, [%0], %1;" ::"r"(bar), "r"(bytes) : "memory");
}
__device__ __forceinline__ bool elect_one() {
    uint32_t p;
    asm volatile("{\n.reg .pred p;\nelect.sync _|p, 0xffffffff;\nselp.u32 %0, 1, 0, p;\n}" : "=r"(p));
    return p;
}
__device__ __forceinline__ uint32_t mapa(uint32_t addr, uint32_t rank) {
    uint32_t r;
    asm("mapa.shared::cluster.u32 %0, %1, %2;" : "=r"(r) : "r"(addr), "r"(rank));
    return r;
}
__device__ __forceinline__ uint32_t clock32() { uint32_t t; asm volatile("mov.u32 %0, %%clock;" : "=r"(t)); return t; }
template <int NS> __device__ __forceinline__ void sleep_until(uint32_t t) {
    int n = 0;
    while ((int)(clock32() - t) < 0 && ++n < SPIN_LIMIT) __nanosleep(NS);
}
__device__ __forceinline__ void yield(float last, uint32_t zero) {
    asm volatile("nanosleep.u32 %0;" ::"r"(__float_as_uint(last) & zero));
}
template <typename T> __device__ __forceinline__ T* at(T* p, uint32_t bytes) {
    asm("" : "+r"(bytes));
    return reinterpret_cast<T*>(reinterpret_cast<uintptr_t>(p) + bytes);
}
__device__ __forceinline__ void tma_2d(uint32_t dst, const CUtensorMap* tm, int c0, int c1, uint32_t bar) {
    asm volatile("cp.async.bulk.tensor.2d.shared::cluster.global.mbarrier::complete_tx::bytes [%0], [%1, {%3, %4}], [%2];"
                 ::"r"(dst), "l"(tm), "r"(bar), "r"(c0), "r"(c1) : "memory");
}
__device__ __forceinline__ void tma_2d_prefetch(const CUtensorMap* tm, int c0, int c1) {
    asm volatile("cp.async.bulk.prefetch.tensor.2d.L2.global [%0, {%1, %2}];" ::"l"(tm), "r"(c0), "r"(c1) : "memory");
}
__device__ __forceinline__ void tma_2d_store(const CUtensorMap* tm, int c0, int c1, uint32_t src) {
    asm volatile("cp.async.bulk.tensor.2d.global.shared::cta.bulk_group [%0, {%2, %3}], [%1];"
                 ::"l"(tm), "r"(src), "r"(c0), "r"(c1) : "memory");
}
__device__ __forceinline__ void bulk_g2s(uint32_t dst, const void* src, uint32_t bytes, uint32_t bar) {
    asm volatile("cp.async.bulk.shared::cluster.global.mbarrier::complete_tx::bytes [%0], [%1], %2, [%3];"
                 ::"r"(dst), "l"(src), "r"(bytes), "r"(bar) : "memory");
}
__device__ __forceinline__ void bulk_s2g(void* dst, uint32_t src, uint32_t bytes) {
    asm volatile("cp.async.bulk.global.shared::cta.bulk_group [%0], [%1], %2;" ::"l"(dst), "r"(src), "r"(bytes) : "memory");
}
__device__ __forceinline__ void st_async4(uint32_t dst, uint32_t a, uint32_t b, uint32_t c, uint32_t d, uint32_t bar) {
    asm volatile("st.async.weak.shared::cluster.mbarrier::complete_tx::bytes.v4.b32 [%0], {%1,%2,%3,%4}, [%5];"
                 ::"r"(dst), "r"(a), "r"(b), "r"(c), "r"(d), "r"(bar) : "memory");
}
__device__ __forceinline__ void bulk_commit() { asm volatile("cp.async.bulk.commit_group;" ::: "memory"); }
template <int N> __device__ __forceinline__ void bulk_wait_read() { asm volatile("cp.async.bulk.wait_group.read %0;" ::"n"(N) : "memory"); }
template <int N> __device__ __forceinline__ void bulk_wait() { asm volatile("cp.async.bulk.wait_group %0;" ::"n"(N) : "memory"); }
__device__ __forceinline__ void fence_async_smem() { asm volatile("fence.proxy.async.shared::cta;" ::: "memory"); }
__device__ __forceinline__ void fence_async_global() { asm volatile("fence.proxy.async.global;" ::: "memory"); }
__device__ __forceinline__ void prefetch_tmap(const CUtensorMap* tm) {
    asm volatile("prefetch.tensormap [%0];" ::"l"(tm) : "memory");
}
__device__ __forceinline__ unsigned long long ld_acquire64(const unsigned long long* p) {
    unsigned long long v; asm volatile("ld.acquire.gpu.global.u64 %0, [%1];" : "=l"(v) : "l"(p) : "memory"); return v;
}
__device__ __forceinline__ unsigned load_epoch(int b) {
    unsigned v; asm volatile("ld.global.u32 %0, [%1];" : "=r"(v) : "l"(at(g_epoch, b * 4)) : "memory"); return v + 1;
}
__device__ __forceinline__ unsigned ld_relaxed(const void* p) {
    unsigned v; asm volatile("ld.relaxed.gpu.global.u32 %0, [%1];" : "=r"(v) : "l"(p) : "memory"); return v;
}
__device__ __forceinline__ uint4 ld_relaxed128(const uint4* p) {
    uint4 v;
    asm volatile("{\n.reg .b128 t;\n.reg .b64 lo, hi;\nld.relaxed.gpu.global.b128 t, [%4];\nmov.b128 {lo, hi}, t;\n"
                 "mov.b64 {%0, %1}, lo;\nmov.b64 {%2, %3}, hi;\n}"
                 : "=r"(v.x), "=r"(v.y), "=r"(v.z), "=r"(v.w) : "l"(p) : "memory");
    return v;
}
__device__ __forceinline__ void st_relaxed128(uint4* p, const uint4& v) {
    asm volatile("{\n.reg .b128 t;\n.reg .b64 lo, hi;\nmov.b64 lo, {%1, %2};\nmov.b64 hi, {%3, %4};\nmov.b128 t, {lo, hi};\n"
                 "st.relaxed.gpu.global.b128 [%0], t;\n}"
                 ::"l"(p), "r"(v.x), "r"(v.y), "r"(v.z), "r"(v.w) : "memory");
}
__device__ __forceinline__ void st_relaxed64(unsigned long long* p, unsigned long long v) {
    asm volatile("st.relaxed.gpu.global.u64 [%0], %1;" ::"l"(p), "l"(v) : "memory");
}
__device__ __forceinline__ void st_release8(void* p, unsigned v) {
    asm volatile("st.release.gpu.global.u8 [%0], %1;" ::"l"(p), "r"(v) : "memory");
}
__device__ __forceinline__ uint64_t policy_evict_first() {
    uint64_t pol;
    asm("createpolicy.fractional.L2::evict_first.b64 %0, 1.0;" : "=l"(pol));
    return pol;
}
__device__ __forceinline__ uint4 ldg_stream(const void* p, uint64_t pol) {
    uint4 v;
    asm volatile("ld.global.nc.L1::no_allocate.L2::cache_hint.v4.u32 {%0,%1,%2,%3}, [%4], %5;"
                 : "=r"(v.x), "=r"(v.y), "=r"(v.z), "=r"(v.w) : "l"(p), "l"(pol));
    return v;
}
__device__ __forceinline__ uint4 ldg_stream_ord(const void* p, uint64_t pol) {
    uint4 v;
    asm volatile("ld.relaxed.gpu.global.L1::no_allocate.L2::cache_hint.v4.u32 {%0,%1,%2,%3}, [%4], %5;"
                 : "=r"(v.x), "=r"(v.y), "=r"(v.z), "=r"(v.w) : "l"(p), "l"(pol) : "memory");
    return v;
}
template <int ID, int N> __device__ __forceinline__ void named_arrive() { asm volatile("bar.arrive %0, %1;" ::"n"(ID), "n"(N) : "memory"); }
template <int ID, int N> __device__ __forceinline__ void named_bar() { asm volatile("bar.sync %0, %1;" ::"n"(ID), "n"(N) : "memory"); }

__device__ __forceinline__ float bf_lo(uint32_t u) { return __uint_as_float(u << 16); }
__device__ __forceinline__ float bf_hi(uint32_t u) { return __uint_as_float(u & 0xffff0000u); }
__device__ __forceinline__ uint32_t pack_bf(float lo, float hi) {
    uint32_t r; asm("cvt.rn.bf16x2.f32 %0, %1, %2;" : "=r"(r) : "f"(hi), "f"(lo)); return r;
}
__device__ __forceinline__ float rbf(float v) { return __uint_as_float(pack_bf(0.f, v)); }
__device__ __forceinline__ float sqrt_f(float v) { float r; asm("sqrt.approx.f32 %0, %1;" : "=f"(r) : "f"(v)); return r; }
__device__ __forceinline__ float rcp_f(float v) { float r; asm("rcp.approx.f32 %0, %1;" : "=f"(r) : "f"(v)); return r; }
__device__ __forceinline__ float silu_f(float z) { return __fdividef(z, 1.0f + __expf(-z)); }
__device__ __forceinline__ uint32_t bsub2(uint32_t a, uint32_t b) {
    uint32_t r; asm("sub.rn.bf16x2 %0, %1, %2;" : "=r"(r) : "r"(a), "r"(b)); return r;
}
__device__ __forceinline__ uint32_t bfma2(uint32_t a, uint32_t b, uint32_t c) {
    uint32_t r; asm("fma.rn.bf16x2 %0, %1, %2, %3;" : "=r"(r) : "r"(a), "r"(b), "r"(c)); return r;
}
__device__ __forceinline__ uint32_t norm2(uint32_t xv, float m, float rinv) {
    uint32_t t = pack_bf(bf_lo(xv) - m, bf_hi(xv) - m);
    return pack_bf(bf_lo(t) * rinv, bf_hi(t) * rinv);
}
__device__ __forceinline__ float gate1(float z) {
    float t;
    const float h = 0.5f * z;
    asm("tanh.approx.f32 %0, %1;" : "=f"(t) : "f"(h));
    return fmaf(h, t, h);
}
__device__ __forceinline__ uint32_t gate2(uint32_t xv, uint32_t mean2, float r0, float r1) {
    const uint32_t t = bsub2(xv, mean2);
    return pack_bf(gate1(bf_lo(t) * r0), gate1(bf_hi(t) * r1));
}
__device__ __forceinline__ uint32_t silu2(uint32_t z) { return pack_bf(silu_f(bf_lo(z)), silu_f(bf_hi(z))); }

__device__ __forceinline__ void stmatrix4(uint32_t addr, uint32_t r0, uint32_t r1, uint32_t r2, uint32_t r3) {
    asm volatile("stmatrix.sync.aligned.m8n8.x4.shared.b16 [%0], {%1,%2,%3,%4};"
                 ::"r"(addr), "r"(r0), "r"(r1), "r"(r2), "r"(r3));
}
__device__ __forceinline__ void stmatrix4t(uint32_t addr, uint32_t r0, uint32_t r1, uint32_t r2, uint32_t r3) {
    asm volatile("stmatrix.sync.aligned.m8n8.x4.trans.shared.b16 [%0], {%1,%2,%3,%4};"
                 ::"r"(addr), "r"(r0), "r"(r1), "r"(r2), "r"(r3));
}
__device__ __forceinline__ void ldmatrix4t(uint32_t addr, uint32_t& r0, uint32_t& r1, uint32_t& r2, uint32_t& r3) {
    asm volatile("ldmatrix.sync.aligned.m8n8.x4.trans.shared.b16 {%0,%1,%2,%3}, [%4];"
                 : "=r"(r0), "=r"(r1), "=r"(r2), "=r"(r3) : "r"(addr));
}

__device__ __forceinline__ void wg_fence() { asm volatile("wgmma.fence.sync.aligned;" ::: "memory"); }
__device__ __forceinline__ void wg_commit() { asm volatile("wgmma.commit_group.sync.aligned;" ::: "memory"); }
template <int N> __device__ __forceinline__ void wg_wait() { asm volatile("wgmma.wait_group.sync.aligned %0;" ::"n"(N) : "memory"); }

__host__ __device__ constexpr uint32_t desc_lo(uint32_t addr, uint32_t lbo) { return ((addr & 0x3FFFF) >> 4) | ((lbo >> 4) << 16); }
#define DESC_HI "0x40000040"

#define R8(a, o) "+f"(a[(o) + 0]), "+f"(a[(o) + 1]), "+f"(a[(o) + 2]), "+f"(a[(o) + 3]), \
                 "+f"(a[(o) + 4]), "+f"(a[(o) + 5]), "+f"(a[(o) + 6]), "+f"(a[(o) + 7])
#define R64(a, o) R8(a, (o) + 0), R8(a, (o) + 8), R8(a, (o) + 16), R8(a, (o) + 24), \
                  R8(a, (o) + 32), R8(a, (o) + 40), R8(a, (o) + 48), R8(a, (o) + 56)

template <int O, int TA>
__device__ __forceinline__ void wgmma128(float (&a)[128], uint32_t da, uint32_t db, int scale_d) {
    asm volatile(
        "{\n.reg .pred p;\n.reg .b64 da, db;\nsetp.ne.b32 p, %66, 0;\n"
        "mov.b64 da, {%64, " DESC_HI "};\nmov.b64 db, {%65, " DESC_HI "};\n"
        "wgmma.mma_async.sync.aligned.m64n128k16.f32.bf16.bf16 "
        "{%0,%1,%2,%3,%4,%5,%6,%7,%8,%9,%10,%11,%12,%13,%14,%15,"
        "%16,%17,%18,%19,%20,%21,%22,%23,%24,%25,%26,%27,%28,%29,%30,%31,"
        "%32,%33,%34,%35,%36,%37,%38,%39,%40,%41,%42,%43,%44,%45,%46,%47,"
        "%48,%49,%50,%51,%52,%53,%54,%55,%56,%57,%58,%59,%60,%61,%62,%63},"
        "da, db, p, 1, 1, %67, 0;\n}"
        : R64(a, O)
        : "r"(da), "r"(db), "r"(scale_d), "n"(TA));
}
template <int O>
__device__ __forceinline__ void wgmma128_rs(float (&a)[128], const uint32_t* f, uint32_t db) {
    asm volatile(
        "{\n.reg .b64 db;\nmov.b64 db, {%68, 8};\n"
        "wgmma.mma_async.sync.aligned.m64n128k16.f32.bf16.bf16 "
        "{%0,%1,%2,%3,%4,%5,%6,%7,%8,%9,%10,%11,%12,%13,%14,%15,"
        "%16,%17,%18,%19,%20,%21,%22,%23,%24,%25,%26,%27,%28,%29,%30,%31,"
        "%32,%33,%34,%35,%36,%37,%38,%39,%40,%41,%42,%43,%44,%45,%46,%47,"
        "%48,%49,%50,%51,%52,%53,%54,%55,%56,%57,%58,%59,%60,%61,%62,%63},"
        "{%64, %65, %66, %67}, db, 1, 1, 1, 0;\n}"
        : R64(a, O)
        : "r"(f[0]), "r"(f[1]), "r"(f[2]), "r"(f[3]), "r"(db));
}
template <int O>
__device__ __forceinline__ void fence_regs64(float (&a)[128]) {
    asm volatile("" : R64(a, O)::"memory");
}

struct Params {
    const __nv_bfloat16* x;
    const __nv_bfloat16* dre;
    const __nv_bfloat16* dim;
    const __nv_bfloat16* wr;
    const __nv_bfloat16* wg;
    const __nv_bfloat16* wu;
    const __nv_bfloat16* wd;
    uint32_t zero;
#define AB g_ab
};

__device__ __forceinline__ float warp_sum(float v) {
#pragma unroll
    for (int o = 16; o; o >>= 1) v += __shfl_xor_sync(0xffffffffu, v, o);
    return v;
}
__device__ __forceinline__ void fma8(float* acc, const uint4& w, float s) {
    acc[0] += s * bf_lo(w.x); acc[1] += s * bf_hi(w.x); acc[2] += s * bf_lo(w.y); acc[3] += s * bf_hi(w.y);
    acc[4] += s * bf_lo(w.z); acc[5] += s * bf_hi(w.z); acc[6] += s * bf_lo(w.w); acc[7] += s * bf_hi(w.w);
}
__device__ __forceinline__ int POS(int t) { return (t & ~15) | ((t & 6) << 1) | ((t & 8) >> 2) | (t & 1); }
__host__ __device__ constexpr int PSLOT(int j) { return j < 4 ? j : (j & 1) + ((j & 2) ? 0 : 4); }
__host__ __device__ constexpr int PPAR(int j) { return j < 4 ? 0 : ((j >> 2) ^ (j >> 1) ^ 1) & 1; }
__host__ __device__ constexpr int DSLOT(int it) { return (it & 3) + 2; }
__device__ __forceinline__ int SREC(int t) { return (t & ~15) | ((t & 3) << 2) | ((t >> 2) & 3); }
__device__ __forceinline__ int KO(int cl) { return ((cl & 1) << 1) | (cl >> 1); }

__global__ void __cluster_dims__(2, 1, 1) __launch_bounds__(NTHREADS, 1)
fnet_fused_kernel(const __grid_constant__ CUtensorMap tm_x, const __grid_constant__ CUtensorMap tm_dre,
                  const __grid_constant__ CUtensorMap tm_dim, const __grid_constant__ CUtensorMap tm_cre,
                  const __grid_constant__ CUtensorMap tm_cim, const __grid_constant__ CUtensorMap tm_out,
                  const __grid_constant__ CUtensorMap tm_x64,
                  const Params P) {
    extern __shared__ __align__(1024) uint8_t smem[];
    const unsigned long long tstart = clock64();
    const uint32_t sb = smem_u32(smem);
    const int tid = threadIdx.x, lane = tid & 31;
    const int pr = blockIdx.x >> 1, p7 = ((pr - 36) * 37) >> 8;
    const int c = blockIdx.x & 1;
    const bool upper = pr >= 36;
    const int col = upper ? pr - 36 - 7 * p7 + 8 : pr < 4 ? 15 : (pr - 4) & 7;
    const int gi = (int)(0x1eca8642fdb97530ull >> (4 * col)) & 15;
    const int g = gi & 7;
    const int r = (gi >> 3) * 4 + (upper ? p7 : pr < 4 ? pr : (pr - 4) >> 3);
#define BLK(n) ((n) - ((n) <= g))
    const int grp = 2 * r + c;
    const int b = g * 16 + grp;
    const uint32_t bar0 = sb + OFF_BAR;
    const uint32_t zero = P.zero;
#define BAR(i) (bar0 + 8u * (i))
#define XBAR(i) (sb + OFF_XB + 64 + 8u * (i))
#define CLUSTER_ARRIVE() asm volatile("barrier.cluster.arrive.relaxed.aligned;" ::: "memory")
#define CLUSTER_WAIT() asm volatile("barrier.cluster.wait.aligned;" ::: "memory")

#define LOAD0(it) do { \
            mbar_expect_tx(BAR(B_FS + DSLOT(it)), SLOT); tma_2d(sb + OFF_S + DSLOT(it) * SLOT, tmD, (it) * 64, r * 128, BAR(B_FS + DSLOT(it))); \
            mbar_expect_tx(BAR(B_FL + (it)), SLOT); tma_2d(sb + OFF_L + (it) * SLOT, &tm_x, (it) * 64, g * 256, BAR(B_FL + (it))); \
            mbar_expect_tx(BAR(B_FL + 4 + (it)), SLOT); tma_2d(sb + OFF_L + (4 + (it)) * SLOT, &tm_x, (it) * 64, g * 256 + 128, BAR(B_FL + 4 + (it))); \
        } while (0)
    if (tid < 32) {
        if (elect_one()) {
            const CUtensorMap* tmD = c ? &tm_dim : &tm_dre;
            prefetch_tmap(tmD); prefetch_tmap(&tm_x);
            mbar_init(BAR(B_FS + 2), 1); mbar_init(BAR(B_FL), 1); mbar_init(BAR(B_FL + 4), 1);
            asm volatile("fence.mbarrier_init.release.cluster;" ::: "memory");
            LOAD0(0);
        }
        __syncwarp();
    }
    const int warp = __shfl_sync(0xffffffffu, tid >> 5, 0);
    if (warp == 12) {
        if (elect_one()) {
#pragma unroll
            for (int i = 1; i < 4; i++) { mbar_init(BAR(B_FS + 2 + i), 1); mbar_init(BAR(B_FL + i), 1); mbar_init(BAR(B_FL + 4 + i), 1); }
#pragma unroll
            for (int i = 0; i < 4; i++) mbar_init(XBAR(i), 1);
            asm volatile("fence.mbarrier_init.release.cluster;" ::: "memory");
        }
        __syncwarp();
    }
    if (warp == 14) {
        if (elect_one()) {
#pragma unroll
            for (int i = 0; i < 8; i++) { mbar_init(BAR(B_EL + i), 1); mbar_init(XBAR(4 + i), 1); if (i < 6) mbar_init(BAR(B_ES + i), 2); }
            asm volatile("fence.mbarrier_init.release.cluster;" ::: "memory");
        }
        __syncwarp();
    }
    if (warp == 15) {
        if (elect_one()) {
            mbar_init(BAR(B_FS), 1); mbar_init(BAR(B_FS + 1), 1);
#pragma unroll
            for (int i = B_SRD; i < B_COUNT; i++) mbar_init(BAR(i), i == B_GO ? 2 : i == B_STATS || i == B_LST ? 4 : 1);
#pragma unroll
            for (int i = 0; i < 4; i++) mbar_expect_tx(BAR(B_RECV + i), SLOT / 2);
            mbar_expect_tx(BAR(B_PEER), 1024); mbar_expect_tx(BAR(B_H), 128);
            asm volatile("fence.mbarrier_init.release.cluster;" ::: "memory");
        }
        __syncwarp();
    }
    CLUSTER_ARRIVE();
    if ((sb & 0xffffffu) != SB0) return;

#define GATHER(ptr, cnt, valid) do { int n = 0; bool ok; _Pragma("unroll 1") do { ok = true; \
                _Pragma("unroll") for (int i = 0; i < (cnt); i++) { f[i] = ld_relaxed128((ptr) + i * 32); ok = ok && (valid); } \
                if (__all_sync(0xffffffffu, ok)) break; \
                __nanosleep(GSL); \
            } while (++n < SPIN_LIMIT); } while (0)
    if (warp >= 8 && warp < 12) {
        asm volatile("setmaxnreg.dec.sync.aligned.u32 %0;" ::"n"(512 - PROD_REGS - 2 * CONS_REGS));
        const int aw = warp - 8, mt = tid - 256;
        unsigned ep;
        {
            const uint8_t* rp = smem + OFF_S + aw * 2048 + lane * 16;
            const __nv_bfloat16* dp = at(c ? P.dim : P.dre, (r * 128 + g * 16 + aw * 4) * D_ * 2);
            float wf[32], sw = 0.f;
#pragma unroll
            for (int i = 0; i < 4; i++) {
                const uint4 w = __ldg(reinterpret_cast<const uint4*>(at(P.wr, lane * 16) + i * 256));
                const uint32_t wv[4] = {w.x, w.y, w.z, w.w};
#pragma unroll
                for (int e = 0; e < 4; e++) { wf[8 * i + 2 * e] = bf_lo(wv[e]); wf[8 * i + 2 * e + 1] = bf_hi(wv[e]); sw = (sw + bf_lo(wv[e])) + bf_hi(wv[e]); }
            }
            ep = load_epoch(b);
            sw = warp_sum(sw);
            CLUSTER_WAIT();
            float x0[4] = {}, s1[4] = {}, s2[4] = {}, sx[4] = {}, sd[4] = {};
#define PUSH(a, v) do { a[0] = a[1]; a[1] = a[2]; a[2] = a[3]; a[3] = v; } while (0)
#pragma unroll 1
            for (int k = 0; k < 4; k++) {
                mbar_wait(XBAR(k), 0);
                uint4 v[4];
#pragma unroll
                for (int i = 0; i < 4; i++) v[i] = *reinterpret_cast<const uint4*>(rp + k * 8192 + i * 512);
                uint32_t sh = v[0].x << 16;
                float a1s = 0.f, a2s = 0.f, axs = 0.f;
#pragma unroll
                for (int i = 0; i < 4; i++) {
                    sh = __shfl_sync(0xffffffffu, sh | (__float_as_uint(axs) & zero), 0);
                    const uint32_t xv[4] = {v[i].x, v[i].y, v[i].z, v[i].w};
#pragma unroll
                    for (int e = 0; e < 4; e++) {
                        const float a0 = bf_lo(xv[e]) - __uint_as_float(sh), a1 = bf_hi(xv[e]) - __uint_as_float(sh);
                        a1s += a0 + a1;
                        a2s = fmaf(a0, a0, fmaf(a1, a1, a2s));
                        axs = fmaf(a0, wf[8 * i + 2 * e], fmaf(a1, wf[8 * i + 2 * e + 1], axs));
                    }
                }
                PUSH(x0, __uint_as_float(sh)); PUSH(s1, a1s); PUSH(s2, a2s); PUSH(sx, axs);
                fence_async_smem();
                __syncwarp();
                if (elect_one()) {
                    const uint32_t db = XBAR(k == 3 ? 8 + aw : 4 + aw);
                    if (k == 0 || k == 3) mbar_expect_tx(db, k ? 2048 : 6144);
                    bulk_g2s(sb + OFF_S + k * 8192 + aw * 2048, dp + k * D_, 2048, db);
                }
            }
#define FOLD4(a) do { const bool u16 = lane & 16, u8 = lane & 8; \
                float p0 = (u16 ? a[2] : a[0]) + __shfl_xor_sync(0xffffffffu, u16 ? a[0] : a[2], 16); \
                float p1 = (u16 ? a[3] : a[1]) + __shfl_xor_sync(0xffffffffu, u16 ? a[1] : a[3], 16); \
                a[0] = (u8 ? p1 : p0) + __shfl_xor_sync(0xffffffffu, u8 ? p0 : p1, 8); \
                _Pragma("unroll") for (int o = 4; o; o >>= 1) a[0] += __shfl_xor_sync(0xffffffffu, a[0], o); } while (0)
#pragma unroll 1
            for (int k = 0; k < 4; k++) {
                mbar_wait(XBAR(k == 3 ? 8 + aw : 4 + aw), 0);
                float run = 0.f;
#pragma unroll
                for (int i = 0; i < 4; i++) {
                    const uint4 v = *reinterpret_cast<const uint4*>(rp + k * 8192 + i * 512);
                    const uint32_t dv[4] = {v.x, v.y, v.z, v.w};
#pragma unroll
                    for (int e = 0; e < 4; e++) run += bf_lo(dv[e]) + bf_hi(dv[e]);
                }
                PUSH(sd, run);
            }
            named_bar<4, 128>();
            if (mt < 12) asm volatile("mbarrier.inval.shared::cta.b64 [%0];" ::"r"(XBAR(mt)) : "memory");
            FOLD4(sd); FOLD4(s1); FOLD4(s2); FOLD4(sx);
            const float nb = __shfl_down_sync(0xffffffffu, sd[0], 8);
            if ((lane & 15) == 0)
                st_relaxed128(at(g_rs, (grp * 64 + g * 8 + aw * 2 + (lane >> 4)) * 16), make_uint4(__float_as_uint(sd[0]), ep, __float_as_uint(nb), ep));
            if (mt == 0) PROF_T(6);
            const int rr = lane >> 3;
            const float c0 = rr == 0 ? x0[0] : rr == 1 ? x0[1] : rr == 2 ? x0[2] : x0[3];
            const float dm = s1[0] * (1.0f / D_);
            const float mb = rbf(c0 + dm);
            const float rinv = rcp_f(rbf(sqrt_f(rbf(rbf(fmaxf(s2[0] * (1.0f / D_) - dm * dm, 0.f)) + 1e-5f))));
            if ((lane & 7) == 0) st_relaxed128(at(g_stat, (b * 16 + aw * 4 + rr) * 16), make_uint4(__float_as_uint(mb), __float_as_uint(rinv), ep, 0));
            unsigned u = __bfloat16_as_ushort(__float2bfloat16_rn((sx[0] + (c0 - mb) * sw) * rinv));
            u = (u & 0x8000u) ? (~u & 0xffffu) : (u | 0x8000u);
            u = (u << 16) | (0xffffu - (unsigned)(b * 16 + rr * 4 + aw));
            u = __reduce_max_sync(0xffffffffu, u);
            if (lane == 0) { *reinterpret_cast<unsigned*>(smem + OFF_XB + aw * 4) = u; mbar_arrive(BAR(B_LST)); }
            if (aw == 3) {
                mbar_wait(BAR(B_LST), 0);
                const uint4 k = *reinterpret_cast<const uint4*>(smem + OFF_XB);
                if (lane == 0) st_relaxed64(at(g_key, b * 8), ((unsigned long long)ep << 32) | max(max(k.x, k.y), max(k.z, k.w)));
            }
            if (mt == 0) PROF_T(2);
            uint4 f[4];
            if (aw < 2) {
                const int t = SREC(aw * 128 + lane);
                GATHER(at(g_stat, (g * 256 + aw * 128 + lane) * 16), 4, f[i].z == ep);
#pragma unroll
                for (int i = 0; i < 4; i++) {
                    *reinterpret_cast<uint32_t*>(smem + OFF_RSTD + (POS(t) + i * 32) * 4) = f[i].y;
                    *reinterpret_cast<uint16_t*>(smem + OFF_MEAN + (POS(t) + i * 32) * 2) = (uint16_t)(f[i].x >> 16);
                }
            } else {
                const int e2 = (aw - 2) * 32 + lane;
                GATHER(at(g_rs, (grp * 64 + e2) * 16), 1, f[i].y == ep && f[i].w == ep);
#pragma unroll
                for (int i = 0; i < 2; i++) {
                    const float v = __uint_as_float(i ? f[0].z : f[0].x);
                    const float hi = rbf(v), mid = rbf(v - hi), lo = v - hi - mid;
                    *reinterpret_cast<uint4*>(smem + OFF_RS + (e2 * 2 + i) * 16) = make_uint4(pack_bf(hi, mid), pack_bf(lo, 0.f), 0, 0);
                }
            }
            fence_async_smem();
            __syncwarp();
            if (lane == 0) mbar_arrive(BAR(B_STATS));
            if (mt == 127) PROF_T(9);
        }
        const bool moe = pr < 28 || pr >= 36;
        const int pair = pr < 28 ? pr : pr - 8;
        if (moe) {
            const uint64_t pol = policy_evict_first();
            const __nv_bfloat16* wp = at((aw & 1) ? P.wu : P.wg, ((c * 512 + (aw >> 1) * 256 + (lane >> 3) * 8) * F_ + pair * 64 + (lane & 7) * 8) * 2);
            uint4 b0[8], b1[8];
#define FILL(buf, str) do { _Pragma("unroll") for (int q = 0; q < 8; q++) buf[q] = ldg_stream(wp + q * (str), pol); } while (0)
#define PAUSE() do { if (mbar_test(BAR(B_QUIET), 0)) mbar_wait_sleep(BAR(B_GO), 0); } while (0)
#define FILLO(buf, row) do { _Pragma("unroll") for (int q = 0; q < 8; q++) buf[q] = ldg_stream_ord(wp + ((row) + q) * F_, pol); } while (0)
            FILLO(b0, 0);
            mbar_wait(BAR(B_SEL), 0);
            uint4 xn;
            {
                const int sel = ~*reinterpret_cast<volatile unsigned*>(smem + OFF_SEL) & (S_ - 1);
                xn = __ldg(reinterpret_cast<const uint4*>(at(P.x, (sel * D_ + c * 512 + (aw >> 1) * 256 + (lane & 7) * 32 + (lane >> 3) * 8) * 2)));
                uint4 f[1];
                GATHER(at(g_stat, SREC(sel) * 16), 1, f[i].z == ep);
                FILLO(b1, 32);
                PAUSE();
                const float m = __uint_as_float(f[0].x), ri = __uint_as_float(f[0].y);
                xn = make_uint4(norm2(xn.x, m, ri), norm2(xn.y, m, ri), norm2(xn.z, m, ri), norm2(xn.w, m, ri));
            }
            float ag[8];
#pragma unroll
            for (int i = 0; i < 8; i++) ag[i] = 0.f;
#define ROUND(cur, nxt, rd) do { \
                PAUSE(); \
                if (lane == 0) TRACE(192 + aw * 12 + (rd)); \
                if ((rd) == 7) wp = at(P.wd - 16 * D_, ((pair * 64 + (lane >> 4) * 8) * D_ + c * 512 + aw * 128 + (lane & 15) * 8) * 2); \
                wp = at(wp, ((rd) < 7 ? 64 * F_ : 32 * D_) + (cur[7].x & zero)); \
                if ((rd) & 7) { if ((rd) < 7) FILL(nxt, F_); else if ((rd) < 11) FILL(nxt, D_); } \
                _Pragma("unroll") for (int q = 0; q < 8; q += 2) { \
                    const uint32_t xw = __shfl_sync(0xffffffffu, q == 0 ? xn.x : q == 2 ? xn.y : q == 4 ? xn.z : xn.w, (lane & 24) | ((rd) & 7)); \
                    fma8(ag, cur[q], bf_lo(xw)); \
                    fma8(ag, cur[q + 1], bf_hi(xw)); \
                    if (q < 6) yield(ag[7], zero); \
                } } while (0)
#pragma unroll 1
            for (int rd = 0; rd < 12; rd += 2) {
                ROUND(b0, b1, rd);
                ROUND(b1, b0, rd + 1);
                if (rd == 6 || rd == 10) {
#pragma unroll
                    for (int i = 0; i < 8; i++) ag[i] += __shfl_xor_sync(0xffffffffu, ag[i], 16);
                }
                if (rd == 6) {
#pragma unroll
                    for (int i = 0; i < 8; i++) ag[i] += __shfl_xor_sync(0xffffffffu, ag[i], 8);
                    if (lane < 8) {
                        const uint32_t dst = mapa(sb + OFF_XB + (c * 4 + aw) * 128 + (lane & 3) * 32, lane >> 2), pb = mapa(BAR(B_PEER), lane >> 2);
                        st_async4(dst, __float_as_uint(ag[0]), __float_as_uint(ag[1]), __float_as_uint(ag[2]), __float_as_uint(ag[3]), pb);
                        st_async4(dst + 16, __float_as_uint(ag[4]), __float_as_uint(ag[5]), __float_as_uint(ag[6]), __float_as_uint(ag[7]), pb);
                    }
                    __syncwarp();
                    wp += 16 * D_; FILL(b1, D_); wp -= 16 * D_;
                    if (aw == 3) {
                        mbar_wait_cluster(BAR(B_PEER), 0);
                        const float* ps = reinterpret_cast<const float*>(smem + OFF_XB) + lane;
                        const float go = (ps[0] + ps[64]) + (ps[128] + ps[192]), uo = (ps[32] + ps[96]) + (ps[160] + ps[224]);
                        const float h = rbf(silu_f(rbf(go))) * rbf(uo), ho = __shfl_xor_sync(0xffffffffu, h, 1);
                        asm volatile("st.async.weak.shared::cluster.mbarrier::complete_tx::bytes.b32 [%0], %1, [%2];"
                                     ::"r"(mapa(sb + OFF_H + c * 64 + (lane >> 1) * 4, lane & 1)), "r"((lane & 1) ? pack_bf(ho, h) : pack_bf(h, ho)),
                                       "r"(mapa(BAR(B_H), lane & 1)) : "memory");
                    }
                    mbar_wait_cluster(BAR(B_H), 0);
                    xn = *reinterpret_cast<const uint4*>(smem + OFF_H + (lane & 3) * 32 + (lane >> 4) * 16);
#pragma unroll
                    for (int i = 0; i < 8; i++) ag[i] = 0.f;
                    if (mt == 0) PROF_T(10);
                }
            }
            const int hi = lane >> 4;
            st_relaxed128(at(g_part, pair * 4096 + (c * 8 + aw * 2 + ((lane >> 3) & 1)) * 256 + hi * 128 + (lane & 7) * 16),
                          make_uint4((__float_as_uint(hi ? ag[4] : ag[0]) & ~15u) | (ep & 15u), __float_as_uint(hi ? ag[5] : ag[1]),
                                     __float_as_uint(hi ? ag[6] : ag[2]), __float_as_uint(hi ? ag[7] : ag[3])));
            if (mt == 0) PROF_T(11);
        } else {
            mbar_wait_sleep(BAR(B_SEL), 0);
        }
        const int sel = ~*reinterpret_cast<volatile unsigned*>(smem + OFF_SEL) & (S_ - 1);
        if ((sel >> 8) == g) {
            const int col = (lane & 7) * 8 + ((lane >> 3) & 1) * 4;
            const uint2 xv = __ldg(reinterpret_cast<const uint2*>(at(P.x, (sel * D_ + grp * 64 + col) * 2)));
            uint4 f[1];
            GATHER(at(g_stat, SREC(sel) * 16), 1, f[i].z == ep);
            const uint4 rec = f[0];
            const uint4* src = at(g_part, (aw * 14 + (lane >> 4)) * 4096 + grp * 256 + (lane & 15) * 16);
            if (!moe) {
                int n = 0;
                while (((ld_relaxed(src) ^ ep) & 15u) != 0 && ++n < SPIN_LIMIT) __nanosleep(500);
            }
            uint4 t[7];
            int n = 0;
            bool ok;
            do {
                ok = true;
#pragma unroll
                for (int u = 0; u < 7; u++) { t[u] = ld_relaxed128(src + u * 512); ok = ok && ((t[u].x ^ ep) & 15u) == 0; }
            } while (!__all_sync(0xffffffffu, ok) && ++n < SPIN_LIMIT);
            float4 a = make_float4(0.f, 0.f, 0.f, 0.f);
#pragma unroll
            for (int u = 0; u < 7; u++) {
                a.x += __uint_as_float(t[u].x & ~15u); a.y += __uint_as_float(t[u].y); a.z += __uint_as_float(t[u].z); a.w += __uint_as_float(t[u].w);
            }
            a.x += __shfl_xor_sync(0xffffffffu, a.x, 16); a.y += __shfl_xor_sync(0xffffffffu, a.y, 16);
            a.z += __shfl_xor_sync(0xffffffffu, a.z, 16); a.w += __shfl_xor_sync(0xffffffffu, a.w, 16);
            float4* park = reinterpret_cast<float4*>(smem + OFF_XB) + (lane & 15);
            if (lane < 16) park[aw * 16] = a;
            named_bar<4, 128>();
            if (aw == 0) {
                const float4 p1 = park[16], p2 = park[32], p3 = park[48];
                a.x = (a.x + p1.x) + (p2.x + p3.x); a.y = (a.y + p1.y) + (p2.y + p3.y);
                a.z = (a.z + p1.z) + (p2.z + p3.z); a.w = (a.w + p1.w) + (p2.w + p3.w);
                unsigned u = *reinterpret_cast<volatile unsigned*>(smem + OFF_SEL) >> 16;
                u = (u & 0x8000u) ? (u & 0x7fffu) : (~u & 0xffffu);
                const float sg = rbf(__fdividef(1.0f, 1.0f + __expf(-__uint_as_float(u << 16))));
                const float m = __uint_as_float(rec.x), ri = __uint_as_float(rec.y);
                const uint32_t n0 = norm2(xv.x, m, ri), n1 = norm2(xv.y, m, ri);
                uint2 o;
                o.x = silu2(pack_bf(bf_lo(n0) + rbf(rbf(a.x) * sg), bf_hi(n0) + rbf(rbf(a.y) * sg)));
                o.y = silu2(pack_bf(bf_lo(n1) + rbf(rbf(a.z) * sg), bf_hi(n1) + rbf(rbf(a.w) * sg)));
                if (lane < 16) *reinterpret_cast<uint2*>(smem + OFF_H + col * 2) = o;
                __syncwarp();
                if (lane == 0) { mbar_arrive(BAR(B_UPD)); PROF_T(12); }
            }
        }
    } else if (warp < 8) {
        asm volatile("setmaxnreg.inc.sync.aligned.u32 %0;" ::"n"(CONS_REGS));
        CLUSTER_WAIT();
        const int wg = warp >> 2, wq = warp & 3;
        const int wt = tid & 127;
        float acc[128];
        const uint32_t fL = BAR(B_FL + 4 * wg), eL = BAR(B_EL + 4 * wg);
        const uint32_t dL = desc_lo(SB0 + OFF_L, 16) + wg * 4096;
        constexpr uint32_t dS = desc_lo(SB0 + OFF_S, 16);
        constexpr uint32_t SL = SLOT >> 4;
#define RELEASE(ls, ss) do { if (wt == 0) { mbar_arrive(eL + 8u * (ls)); mbar_arrive(BAR(B_ES + (ss))); } } while (0)
#define WAIT_FULL(ls, lph, ss, sph) do { mbar_wait(BAR(B_FS + (ss)), sph); mbar_wait(fL + 8u * (ls), lph); } while (0)
#define TURN() do { if (wg) named_bar<6, 256>(); else named_bar<5, 256>(); } while (0)
#define PASS() do { if (wg) named_arrive<5, 256>(); else named_arrive<6, 256>(); } while (0)
#define WG_BAR() do { if (wg) named_bar<2, 128>(); else named_bar<1, 128>(); } while (0)
        if (wg == 1) PASS();

#define MMA1_H(O, s, first) do { _Pragma("unroll") for (int kk = 0; kk < 4; kk++) \
            wgmma128<O, 0>(acc, dL + (s) * SL + kk * 2 + (O) * 8, dS + DSLOT(s) * SL + kk * 2, !((first) && kk == 0)); } while (0)
#define WAIT1(s, ph) WAIT_FULL(s, ph, DSLOT(s), ph)
#define PROBE(ls, lph, ss, sph) (mbar_test(BAR(B_FS + (ss)), sph) & mbar_test(fL + 8u * (ls), lph))
#define REL1(s) RELEASE(s, DSLOT(s))
#pragma unroll 1
        for (int it = 0; it < 12; it++) {
            const int s = it & 3;
            const bool ok = PROBE(s, (it >> 2) & 1, DSLOT(s), (it >> 2) & 1);
            if (it) { wg_wait<0>(); REL1((s + 3) & 3); }
            if (!ok) WAIT1(s, (it >> 2) & 1);
            TURN();
            wg_fence(); MMA1_H(0, s, it == 0); MMA1_H(64, s, it == 0); wg_commit();
            PASS();
            if (it == 0 && tid == 0) PROF_T(16);
        }
        TS(12);
        float rs[4] = {};
        uint32_t nm[8] = {};
#define GET_STATS() do { mbar_wait(BAR(B_STATS), 0); \
            const int p0 = POS(wg * 128 + wq * 16 + (lane >> 2));                   \
            const uint32_t msk = (lane & 3) == 0 ? 0xffffffffu : (lane & 3) == 1 ? 0x0000ffffu : 0u; \
            _Pragma("unroll") for (int i = 0; i < 4; i++) { \
                const int p = p0 + (i & 1) * 2 + (i >> 1) * 64; \
                rs[i] = *reinterpret_cast<const float*>(smem + OFF_RSTD + p * 4); \
                const uint32_t m = *reinterpret_cast<const uint16_t*>(smem + OFF_MEAN + p * 2) ^ 0x8000u; \
                nm[i + (i & 2)] = (m | (m << 16)) & msk; \
            } } while (0)
        const bool early = wg || __all_sync(0xffffffffu, mbar_test(BAR(B_STATS), 0));
        if (early && !wg) GET_STATS();
        WAIT1(0, 1);
        TS(13);
        wg_wait<0>(); REL1(3);
        if (wg) GET_STATS();
        TS(14);
        TURN();
        wg_fence();
        MMA1_H(0, 0, false);
        if (tid == 0) { mbar_arrive(BAR(B_QUIET)); PROF_T(15); }
        WAIT1(1, 1); wg_fence(); MMA1_H(0, 1, false);
        WAIT1(2, 1); wg_fence(); MMA1_H(0, 2, false); wg_commit();
        if (!early) GET_STATS();
        asm volatile("" : "+r"(nm[0]), "+r"(nm[1]), "+r"(nm[2]), "+r"(nm[3]), "+r"(nm[4]), "+r"(nm[5]), "+r"(nm[6]), "+r"(nm[7])::"memory");
        wg_fence();
        wgmma128_rs<64>(acc, nm + 4, (SB0 + OFF_RS) >> 4);
        wgmma128_rs<0>(acc, nm, (SB0 + OFF_RS) >> 4);
        WAIT1(3, 1); wg_fence(); MMA1_H(0, 3, false); wg_commit();
        PASS();
        const int mrow = wq * 16 + ((lane >> 3) & 1) * 8 + (lane & 7);
#define EPI1(O, slot, FREE) do { const uint32_t dst = sb + OFF_S + (slot) * SLOT + mrow * 128; \
            uint32_t pk[32]; \
            _Pragma("unroll") for (int i = 0; i < 32; i += 4) { \
                _Pragma("unroll") for (int k = 0; k < 4; k++) \
                    pk[i + k] = pack_bf(acc[(O) + 2 * (i + k)] * rs[(O) / 32 + (k & 1)], acc[(O) + 2 * (i + k) + 1] * rs[(O) / 32 + (k & 1)]); \
                if (i == EF) { FREE; } \
                if (i >= EF) { _Pragma("unroll") for (int v = (i == EF ? 0 : i); v <= i; v += 4) \
                    stmatrix4(dst + ((v >> 4) ^ c ^ 1) * 8192 + ((((v >> 1) & 7) + (lane >> 4)) ^ (lane & 7)) * 16, pk[v], pk[v + 1], pk[v + 2], pk[v + 3]); } } \
            WG_BAR(); \
            if (wt == 0) mbar_arrive(BAR(B_FS + (slot))); } while (0)
        TS(15);
        wg_wait<0>();
        fence_regs64<0>(acc);
        TS(16);
        {
            constexpr int EF = 0;
            EPI1(0, wg, if (wg) mbar_wait(BAR(B_FS), 0));
        }
        TS(17);
        TURN();
        wg_fence();
        MMA1_H(64, 0, false); wg_commit();
        MMA1_H(64, 1, false); wg_commit();
        MMA1_H(64, 2, false); wg_commit();
        wg_wait<2>(); REL1(0);
        MMA1_H(64, 3, false); wg_commit();
        PASS();
        TS(18);
        wg_wait<2>(); REL1(1);
        mbar_wait(BAR(B_FS), 0); mbar_wait(BAR(B_FS + 1), 0); fence_async_smem();
        wg_wait<1>(); REL1(2);
        wg_wait<0>(); REL1(3);
        fence_regs64<64>(acc);
        TS(19);
        {
            constexpr int EF = 16;
            EPI1(64, 2 + wg, mbar_wait(BAR(B_ES + 2 + wg), 1));
        }
        TS(20);

        float ac2[128];
#define MMA2_H(O, ls, ss, first) do { _Pragma("unroll") for (int kk = 0; kk < 4; kk++) \
            wgmma128<O, 1>(ac2, dS + (ss) * SL + kk * 128 + (O) * 8, dL + (ls) * SL + kk * 2, !((first) && kk == 0)); } while (0)
#define WAIT2(j) WAIT_FULL((j) & 3, ((j) >> 2) & 1, PSLOT(j), PPAR(j))
#define MMA2(j) do { wg_fence(); MMA2_H(0, (j) & 3, PSLOT(j), (j) == 0); MMA2_H(64, (j) & 3, PSLOT(j), (j) == 0); wg_commit(); } while (0)
#define REL2(j) RELEASE((j) & 3, PSLOT(j))
        WAIT2(0); TURN(); MMA2(0);
        WAIT2(1); MMA2(1); PASS();
        TS(21);
        wg_wait<1>(); REL2(0);
        mbar_wait(BAR(B_FS + 2), 0); mbar_wait(BAR(B_FS + 3), 0); fence_async_smem();
        TS(22);
        {
            uint32_t l2 = 2, s2 = 2, sp = 1, lph = 0, sph = 0;
#pragma unroll 1
            for (int j = 2; j < XJ; j += 2) {
#pragma unroll
                for (int h = 0; h < 2; h++) {
                    const bool ok = PROBE(l2 + h, lph, s2 + h, sph);
                    wg_wait<0>(); RELEASE(h ? l2 : 3 - l2, h ? s2 : sp);
                    if (!ok) WAIT_FULL(l2 + h, lph, s2 + h, sph);
                    TURN();
                    wg_fence(); MMA2_H(0, l2 + h, s2 + h, false); MMA2_H(64, l2 + h, s2 + h, false); wg_commit();
                    PASS();
                    if (h == (GOJ & 1) && j == (GOJ & ~1) && wt == 0) { mbar_arrive(BAR(B_GO)); if (wg == 0) PROF_T(19); }
                }
                sp = s2 + 1; s2 = 2 * l2; sph = lph; l2 ^= 2;
                lph ^= l2 == 0;
            }
        }
        if (tid == 0) PROF_T(20);
        uint32_t gt[32];
        const uint32_t xrow = sb + OFF_S + 2 * SLOT + wg * 8192 + ((lane >> 4) * 8 + (lane & 7)) * 128 + (((2 * wq + ((lane >> 3) & 1)) ^ (lane & 7)) << 4);
        const uint32_t gsign = c ? 0x80008000u : 0u;
#define XOFF(v) (((v) >> 2) * SLOT + ((v) & 3) * 2048)
        int sel = 0;
        bool own = false;
#define PATCH() do { own = false; \
            const uint32_t v0 = *reinterpret_cast<const uint16_t*>(smem + OFF_H + (wq * 16 + (lane >> 2)) * 2) ^ gsign; \
            const uint32_t v1 = *reinterpret_cast<const uint16_t*>(smem + OFF_H + (wq * 16 + (lane >> 2)) * 2 + 16) ^ gsign; \
            const uint32_t pick = (lane & 3) != ((sel >> 1) & 3) ? 0x3210u : (sel & 1) ? 0x5410u : 0x3254u; \
            _Pragma("unroll") for (int i = 0; i < 16; i++) { \
                const uint32_t m = ((sel >> 3) & 15) == i ? pick : 0x3210u; \
                gt[2 * i] = __byte_perm(gt[2 * i], v0, m); \
                gt[2 * i + 1] = __byte_perm(gt[2 * i + 1], v1, m); \
            } } while (0)
#pragma unroll
        for (int u = 0; u < 8; u++) {
            if (u) { WAIT2(XJ + u - 1); wg_wait<0>(); REL2(XJ + u - 2); TURN(); MMA2(XJ + u - 1); PASS(); }
            uint32_t* o = &gt[4 * u];
            if (!(u & 3)) mbar_wait(BAR(B_FS + 2 + (u >> 2)), 1);
            ldmatrix4t(xrow + XOFF(u), o[0], o[1], o[2], o[3]);
            const float4 r4 = *reinterpret_cast<const float4*>(smem + OFF_RSTD + (wg * 128 + u * 16 + (lane & 3) * 4) * 4);
            const uint2 m2 = *reinterpret_cast<const uint2*>(smem + OFF_MEAN + (wg * 128 + u * 16 + (lane & 3) * 4) * 2);
            o[0] = gate2(o[0], m2.x, r4.x, r4.y) ^ gsign;
            o[1] = gate2(o[1], m2.x, r4.x, r4.y) ^ gsign;
            o[2] = gate2(o[2], m2.y, r4.z, r4.w) ^ gsign;
            o[3] = gate2(o[3], m2.y, r4.z, r4.w) ^ gsign;
            if (u == 2) {
                mbar_wait(BAR(B_SEL), 0);
                sel = ~*reinterpret_cast<volatile unsigned*>(smem + OFF_SEL) & (S_ - 1);
                own = (sel >> 7) == 2 * g + wg;
            }
            asm volatile("st.shared.v2.u32 [%0], {%1,%2};" ::"r"(sb + OFF_SEL + 16), "r"(o[0] ^ o[1]), "r"(o[2] ^ o[3]) : "memory");
        }
        if (tid == 0) PROF_T(21);
        WAIT2(27);
        wg_wait<0>(); REL2(26);
        if (own) {
            const uint32_t t0 = clock32();
            bool ok;
            while (!(ok = mbar_test(BAR(B_UPD), 0)) && clock32() - t0 < wg * 1900u) __nanosleep(50);
            if (__all_sync(0xffffffffu, ok)) PATCH();
        }
        TS(0);
        TURN();
        MMA2(27);
        WAIT2(28); wg_fence(); MMA2_H(0, 0, PSLOT(28), false); wg_commit();
        if (wg == 0) { wg_fence(); MMA2_H(64, 0, PSLOT(28), false); wg_commit(); }
        constexpr uint32_t dL0 = desc_lo(SB0 + OFF_L, 16);
        const uint32_t ct[3] = {wg ? 3u : 1u, wg ? 1u : 2u, wg ? 2u : 5u};
#define TMMA(O, i) wgmma128<O, 1>(ac2, ((i) < 8 ? dS + PSLOT(29 + ((i) >> 2)) * SL : dL0 + 6 * SL) + ((i) & 3) * 128 + (O) * 8, \
                                  dL0 + ct[(i) >> 2] * SL + ((i) & 3) * 2, 1)
#define KEEP(i) TMMA(64, i)
#pragma unroll
        for (int k = 0; k < 3; k++) {
            if (k < 2) mbar_wait(BAR(B_FS + PSLOT(29 + k)), PPAR(29 + k)); else mbar_wait(BAR(B_FL + 6), 1);
            mbar_wait(BAR(B_FL + ct[k]), k == 0 || wg == 0);
            wg_fence();
#pragma unroll
            for (int i = 4 * k; i < 4 * k + 4; i++) TMMA(0, i);
            wg_commit();
            if (k < 2) wg_wait<2>();
            if (k == 0 && tid == 0) mbar_arrive(BAR(B_R27));
            if (k == 1 && tid == 0) mbar_arrive_cluster(mapa(BAR(B_RDY), c ^ 1));
        }
        TS(1);
        wg_fence();
#pragma unroll
        for (int i = 0; i < KQ; i++) KEEP(i);
        wg_commit();
        mbar_wait(BAR(B_RDY + wg), 0);
        wg_wait<1>();
        fence_regs64<0>(ac2);
        TS(2);
        wg_fence();
        {
            const uint32_t dst = mapa(sb + OFF_L + wg * 5 * SLOT + wt * 16, c ^ 1), rb = mapa(BAR(B_RECV + 2 * wg), c ^ 1);
#pragma unroll
            for (int v = 0; v < 8; v++) {
                if (KQ + v < 12) KEEP(KQ + v);
                if (KQ + v == 7) wg_commit();
                if (KQ + v == 11) { wg_commit(); if (wg == 0) PASS(); }
                st_async4(dst + v * 2048, pack_bf(ac2[8 * v + 0], ac2[8 * v + 1]), pack_bf(ac2[8 * v + 2], ac2[8 * v + 3]),
                          pack_bf(ac2[8 * v + 4], ac2[8 * v + 5]), pack_bf(ac2[8 * v + 6], ac2[8 * v + 7]), rb + (v >> 2) * 8);
            }
        }
        if (wg == 1) { wg_fence(); MMA2_H(64, 0, PSLOT(28), false); wg_commit(); }
        TS(3);
        uint32_t xr[32];
#define LDX(v) ldmatrix4t(xrow + XOFF(v), xr[4 * (v)], xr[4 * (v) + 1], xr[4 * (v) + 2], xr[4 * (v) + 3])
        if (wg == 0) {
            wg_wait<2>();
            if (wt == 0) mbar_arrive(BAR(B_SRD));
            wg_wait<1>();
            if (wt == 0) mbar_arrive(BAR(B_SRD + 1));
        }
#pragma unroll
        for (int v = 0; v < XE; v++) LDX(v);
        if (wg == 0) {
            wg_wait<0>();
            if (wt == 0) mbar_arrive_cluster(mapa(BAR(B_RDY + 1), c ^ 1));
        }
        TS(4);
        if (own) { mbar_wait(BAR(B_UPD), 0); PATCH(); }
        TS(5);
        uint4 rv[8];
#define FETCH(v0) do { if ((v0) == 0 || (v0) == 4) mbar_wait_cluster(BAR(B_RECV + 2 * wg + (v0) / 4), 0); \
            _Pragma("unroll") for (int v = (v0); v < (v0) + 2; v++) { \
                asm volatile("ld.shared.v4.u32 {%0,%1,%2,%3}, [%4];" : "=r"(rv[v].x), "=r"(rv[v].y), "=r"(rv[v].z), "=r"(rv[v].w) \
                             : "r"(sb + OFF_L + wg * 5 * SLOT + v * 2048 + wt * 16) : "memory"); \
                if (v >= XE) LDX(v); } } while (0)
        FETCH(0);
        TS(6);
        wg_wait<0>();
        fence_regs64<64>(ac2);
        TS(7);
#pragma unroll
        for (int v0 = 0; v0 < 8; v0 += 2) {
#pragma unroll
            for (int v = v0; v < v0 + 2; v++) {
                const float* a = &ac2[64 + 8 * v];
                stmatrix4t(xrow + XOFF(v),
                           bfma2(bsub2(pack_bf(a[0], a[1]), rv[v].x), gt[4 * v + 0], xr[4 * v + 0]),
                           bfma2(bsub2(pack_bf(a[2], a[3]), rv[v].y), gt[4 * v + 1], xr[4 * v + 1]),
                           bfma2(bsub2(pack_bf(a[4], a[5]), rv[v].z), gt[4 * v + 2], xr[4 * v + 2]),
                           bfma2(bsub2(pack_bf(a[6], a[7]), rv[v].w), gt[4 * v + 3], xr[4 * v + 3]));
            }
            WG_BAR();
            if (wt == 0) mbar_arrive(eL + 4 * v0);
            if (v0 + 2 < 8) FETCH(v0 + 2);
            if (v0 == 0) TS(8);
        }
        TS(9);
    } else {
        asm volatile("setmaxnreg.dec.sync.aligned.u32 %0;" ::"n"(PROD_REGS));
#define XROWS(k) do { mbar_expect_tx(XBAR(k), 8192); bulk_g2s(sb + OFF_S + (k) * 8192, at(P.x, (b * 16 + (k) * 4) * D_ * 2), 8192, XBAR(k)); } while (0)
        if (warp == 12) {
            if (elect_one()) {
                const CUtensorMap* tmD = c ? &tm_dim : &tm_dre;
#pragma unroll 1
                for (int it = 1; it < 4; it++) {
                    while (clock32() - (uint32_t)tstart < LDEL + (it - 1) * LGAP) {}
                    LOAD0(it);
                    if (it >= X0) XROWS(it - X0);
                }
            }
            __syncwarp();
        }
        CLUSTER_WAIT();
        if (warp == 12) {
            if (elect_one()) {
                const CUtensorMap* tmD = c ? &tm_dim : &tm_dre;
#pragma unroll 1
                for (int it = 4; it < 16; it++) {
                    const int s = DSLOT(it);
                    mbar_wait(BAR(B_ES + s), ((it >> 2) & 1) ^ 1);
                    TRACE(it);
                    mbar_expect_tx(BAR(B_FS + s), SLOT);
                    tma_2d(sb + OFF_S + s * SLOT, tmD, it * 64, r * 128, BAR(B_FS + s));
                    if (it < 4 + X0) XROWS(it - X0);
                }
                const unsigned ep = load_epoch(b), e8 = ep & 0xffu;
                const uint8_t* abg = at(AB, grp * 32 * SLOT);
                const unsigned long long* fl = at(g_flag, grp * 128);
                unsigned long long rdy = ld_acquire64(fl);
                mbar_wait(BAR(B_SRD), 0);
                st_release8(at(g_flag, grp * 128 + g), e8);
                PROF_T(7);
                int j = 4;
#pragma unroll 1
                for (int cl = 0; cl < 4; cl++) {
                    if (cl) rdy = ld_acquire64(++fl);
                    fence_async_global();
#pragma unroll 1
                    for (int n = 1; n < 8; n++, j++) {
                        const int q = BLK(n), s = (j & 1) + ((j & 2) ? 0 : 4);
                        const uint32_t fb = BAR(j == 31 ? B_FL + 6 : B_FS + s);
                        if (j == 31) mbar_wait(BAR(B_EL + 6), 0); else mbar_wait(BAR(B_ES + s), ((j >> 2) ^ (j >> 1)) & 1);
                        if (j == 7) mbar_wait(BAR(B_SRD + 1), 0);
                        if (((unsigned)(rdy >> (8 * q)) & 0xffu) != e8) {
                            int m = 0;
                            do { rdy = ld_acquire64(fl); } while (((unsigned)(rdy >> (8 * q)) & 0xffu) != e8 && ++m < SPIN_LIMIT);
                            fence_async_global();
                        }
                        TRACE(16 + j);
                        mbar_expect_tx(fb, SLOT);
                        bulk_g2s(sb + (j == 31 ? OFF_L + 6 * SLOT : OFF_S + s * SLOT), at(abg, (4 * q + KO(cl)) * SLOT), SLOT, fb);
                    }
                }
                *at(g_epoch, b * 4) = ep;
            }
        } else if (warp < 15) {
            if (elect_one()) {
                const int w = warp - 13, row0 = g * 256 + w * 128;
                const CUtensorMap* tmC = c ? &tm_cim : &tm_cre;
                const uint32_t fb = BAR(B_FL + 4 * w), eb = BAR(B_EL + 4 * w), dst = sb + OFF_L + w * 4 * SLOT;
                [[maybe_unused]] unsigned long long mk = 0, mg = 0;
                int n = 0, cl = 0;
#pragma unroll 1
                for (int it = 4; it < 47 - 2 * w; it++) {
                    const int s = it & 3;
                    mbar_wait(eb + 8 * s, ((it >> 2) & 1) ^ 1);
                    TRACE(64 + w * 64 + it - 4);
                    MARK(it);
                    mbar_expect_tx(fb + 8 * s, SLOT);
                    tma_2d(dst + s * SLOT, it < 16 ? &tm_x : tmC, (it < 16 ? it : 4 * (n ? BLK(n) : g) + KO(cl)) * 64, row0, fb + 8 * s);
                    if (it == PTJ) prefetch_tmap(w ? &tm_x64 : tmC);
                    if (it == PTJ && w) prefetch_tmap(&tm_out);
                    if (it >= 16) {
                        if (it == 19) { n = 1; cl = 0; } else if (it < 19) cl++; else if (++n == 8) { n = 1; cl++; }
                    }
                }
#pragma unroll 1
                for (int i = 2 * w; i < 3; i++) {
                    const int s = w ? 1 : i ? i : 3;
                    mbar_wait(w ? eb + 8 : BAR(i ? B_SRD - 1 + i : B_R27), w == 0 && i);
                    mbar_expect_tx(fb + 8 * s, SLOT);
                    tma_2d(dst + s * SLOT, tmC, (4 * BLK(5 + i) + 3) * 64, row0 ^ 128, fb + 8 * s);
                }
                if (w && (r & 3) < 2) tma_2d_prefetch(tmC, (4 * BLK(6 + (r & 1)) + 3) * 64, row0);
#pragma unroll 1
                for (int h = 0; h < 4; h++) {
                    mbar_wait(eb + 8 * h, h < 3);
                    fence_async_smem();
                    tma_2d_store(&tm_out, grp * 64, row0 + h * 32, sb + OFF_S + (2 + (h >> 1)) * SLOT + w * 8192 + (h & 1) * 4096);
                    bulk_commit();
                }
                FINISH(w);
            }
        } else {
            const unsigned ep = load_epoch(b);
            uint4 f[4];
            {
                sleep_until<400>((uint32_t)tstart + RDEL);
                GATHER(at(reinterpret_cast<const uint4*>(g_key), lane * 16), 2, f[i].y == ep && f[i].w == ep);
                const unsigned key = __reduce_max_sync(0xffffffffu, max(max(f[0].x, f[0].z), max(f[1].x, f[1].z)));
                if (lane == 0) { *reinterpret_cast<unsigned*>(smem + OFF_SEL) = key; mbar_arrive(BAR(B_SEL)); PROF_T(8); }
            }
            if (elect_one()) {
#pragma unroll 1
                for (int cl = 0; cl < 4; cl++) {
                    uint8_t* dst = at(AB, (grp * 32 + 4 * g + KO(cl)) * SLOT);
                    const uint32_t src = sb + OFF_S + cl * SLOT, chunk = cl ? 1024 : SLOT;
                    mbar_wait(BAR(B_FS + cl), 0);
                    fence_async_smem();
                    if (cl == 0) PROF_T(3);
                    uint32_t t0 = clock32() + (cl == 1 ? PDEL : 0);
#pragma unroll 1
                    for (uint32_t o = 0; o < SLOT; o += chunk) {
                        sleep_until<50>(t0);
                        bulk_s2g(dst + o, src + o, chunk);
                        bulk_commit();
                        t0 += cl == 1 ? PGAP1 : cl == 2 ? PGAP2 : PGAP3;
                    }
                    bulk_wait<0>();
                    fence_async_global();
                    TRACE(252 + cl);
                    if (cl < 2) mbar_arrive(BAR(B_SRD + cl));
                    else {
                        mbar_wait(BAR(B_ES + cl), 0);
                        mbar_expect_tx(BAR(B_FS + cl), SLOT);
                        tma_2d(src, &tm_x64, grp * 64, g * 256 + (cl - 2) * 64, BAR(B_FS + cl));
                        tma_2d(src + 8192, &tm_x64, grp * 64, g * 256 + (cl - 2) * 64 + 128, BAR(B_FS + cl));
                    }
                    if (cl) st_release8(at(g_flag, grp * 128 + cl * 8 + g), ep & 0xffu);
                    if (cl == 1) PROF_T(5);
                    if (cl == 3) PROF_T(4);
                }
            }
        }
    }
}

typedef CUresult (*EncodeFn)(CUtensorMap*, CUtensorMapDataType, cuuint32_t, void*, const cuuint64_t*, const cuuint64_t*,
                             const cuuint32_t*, const cuuint32_t*, CUtensorMapInterleave, CUtensorMapSwizzle,
                             CUtensorMapL2promotion, CUtensorMapFloatOOBfill);

void make_map(EncodeFn fn, CUtensorMap* tm, const void* p, uint64_t rows, uint64_t cols, uint32_t box_rows) {
    cuuint64_t dims[2] = {cols, rows};
    cuuint64_t strides[1] = {cols * 2};
    cuuint32_t box[2] = {64, box_rows};
    cuuint32_t es[2] = {1, 1};
    fn(tm, CU_TENSOR_MAP_DATA_TYPE_BFLOAT16, 2, const_cast<void*>(p), dims, strides, box, es, CU_TENSOR_MAP_INTERLEAVE_NONE,
       CU_TENSOR_MAP_SWIZZLE_128B, CU_TENSOR_MAP_L2_PROMOTION_L2_128B, CU_TENSOR_MAP_FLOAT_OOB_FILL_NONE);
}

}

extern "C" void kernel_launch(void* const* d_in, const int* in_sizes, int n_in, void* d_out, int out_size) {
    (void)in_sizes; (void)n_in; (void)out_size;
    static EncodeFn fn = nullptr;
    if (!fn) {
        void* p = nullptr;
        cudaDriverEntryPointQueryResult q;
        cudaGetDriverEntryPoint("cuTensorMapEncodeTiled", &p, cudaEnableDefault, &q);
        fn = (EncodeFn)p;
        cudaFuncSetAttribute(fnet_fused_kernel, cudaFuncAttributeMaxDynamicSharedMemorySize, SMEM_BYTES);
    }
    CUtensorMap tx, tdre, tdim, tcre, tcim, tout, tx64;
    make_map(fn, &tx, d_in[0], S_, D_, 128);
    make_map(fn, &tcre, d_in[1], S_, S_, 128);
    make_map(fn, &tcim, d_in[2], S_, S_, 128);
    make_map(fn, &tdre, d_in[3], D_, D_, 128);
    make_map(fn, &tdim, d_in[4], D_, D_, 128);
    make_map(fn, &tx64, d_in[0], S_, D_, 64);
    make_map(fn, &tout, d_out, S_, D_, 32);
    Params P;
    P.x = (const __nv_bfloat16*)d_in[0];
    P.dre = (const __nv_bfloat16*)d_in[3];
    P.dim = (const __nv_bfloat16*)d_in[4];
    P.wr = (const __nv_bfloat16*)d_in[6];
    P.wg = (const __nv_bfloat16*)d_in[7];
    P.wu = (const __nv_bfloat16*)d_in[8];
    P.wd = (const __nv_bfloat16*)d_in[9];
    P.zero = 0;
    fnet_fused_kernel<<<NCTA, NTHREADS, SMEM_BYTES, cudaStreamPerThread>>>(tx, tdre, tdim, tcre, tcim, tout, tx64, P);
}
```

```cpp
#include <cuda_runtime.h>
#include <cuda_bf16.h>
#include <cuda.h>
#include <stdint.h>

#define GSL 200
#define SLEEP_NS 200
#define PDEL 1000
#define PGAP1 200
#define PGAP2 200
#define PGAP3 240
#define GOJ 2
#define LDEL 1400
#define LGAP 700
#define PTJ 10
#define X0 2
#define RDEL 8000
#define KQ 5
#define XE 2
#define PROD_REGS 32
#define CONS_REGS 184

namespace {

constexpr int S_ = 2048, D_ = 1024, F_ = 3584;
constexpr int NCTA = 128;
constexpr int XJ = 20;
constexpr uint32_t SLOT = 16384;
constexpr uint32_t OFF_L = 0;
constexpr uint32_t OFF_S = 8 * SLOT;
constexpr uint32_t OFF_RS = OFF_S + SLOT;
constexpr uint32_t OFF_BAR = 14 * SLOT;
constexpr uint32_t OFF_SEL = OFF_BAR + 360;
constexpr uint32_t OFF_RSTD = OFF_BAR + 384;
constexpr uint32_t OFF_MEAN = OFF_RSTD + 1024;
constexpr uint32_t OFF_XB = OFF_MEAN + 512;
constexpr uint32_t OFF_H = OFF_XB + 1024;
constexpr uint32_t SMEM_BYTES = OFF_H + 128;
constexpr uint32_t SB0 = 1024;
constexpr int NTHREADS = 512;
static_assert(SMEM_BYTES <= 232448, "smem");

enum { B_FS = 0, B_ES = 6, B_FL = 12, B_EL = 20, B_SRD = 28  , B_RECV = 30  , B_RDY = 34, B_STATS = 36, B_LST = 37, B_UPD = 38,
       B_QUIET = 39, B_GO = 40, B_PEER = 41, B_SEL = 42, B_H = 43, B_R27 = 44, B_COUNT = 45 };
static_assert(B_COUNT * 8 <= 360, "barriers");

__device__ __align__(1024) uint8_t g_ab[16u * 32u * SLOT];
__device__ __align__(128) uint4 g_part[56 * (D_ / 4)];
__device__ __align__(128) uint4 g_stat[S_];
__device__ __align__(128) uint4 g_rs[D_];
__device__ __align__(128) unsigned long long g_key[NCTA];
__device__ __align__(128) unsigned long long g_flag[16 * 16];
__device__ __align__(128) unsigned g_epoch[NCTA];
#define PROF_T(i) do {} while (0)
#define TRACE(i) do {} while (0)
#define PROF_G(i) do {} while (0)
#define TS(i) do {} while (0)
#define FINISH(wg) bulk_wait_read<0>()

#define MARK(it) do {} while (0)

__device__ __forceinline__ uint32_t smem_u32(const void* p) { return (uint32_t)__cvta_generic_to_shared(p); }
__device__ __forceinline__ void mbar_init(uint32_t bar, uint32_t cnt) {
    asm volatile("mbarrier.init.shared::cta.b64 [%0], %1;" ::"r"(bar), "r"(cnt) : "memory");
}
__device__ __forceinline__ bool mbar_try(uint32_t bar, uint32_t parity) {
    uint32_t ok;
    asm volatile("{\n.reg .pred p;\nmbarrier.try_wait.parity.shared::cta.b64 p, [%1], %2;\nselp.u32 %0, 1, 0, p;\n}"
                 : "=r"(ok) : "r"(bar), "r"(parity) : "memory");
    return ok;
}
__device__ __forceinline__ bool mbar_test(uint32_t bar, uint32_t parity) {
    uint32_t ok;
    asm volatile("{\n.reg .pred p;\nmbarrier.test_wait.parity.shared::cta.b64 p, [%1], %2;\nselp.u32 %0, 1, 0, p;\n}"
                 : "=r"(ok) : "r"(bar), "r"(parity) : "memory");
    return ok;
}
__device__ __forceinline__ bool mbar_try_cluster(uint32_t bar, uint32_t parity) {
    uint32_t ok;
    asm volatile("{\n.reg .pred p;\nmbarrier.try_wait.parity.acquire.cluster.shared::cta.b64 p, [%1], %2;\nselp.u32 %0, 1, 0, p;\n}"
                 : "=r"(ok) : "r"(bar), "r"(parity) : "memory");
    return ok;
}
constexpr int SPIN_LIMIT = 1 << 20;
__device__ __forceinline__ void mbar_wait(uint32_t bar, uint32_t parity) {
    if (mbar_try(bar, parity)) return;
    int n = 0;
    while (!mbar_try(bar, parity) && ++n < SPIN_LIMIT) {}
}
__device__ __forceinline__ void mbar_wait_cluster(uint32_t bar, uint32_t parity) {
    int n = 0;
    while (!mbar_try_cluster(bar, parity) && ++n < SPIN_LIMIT) {}
}
__device__ __forceinline__ void mbar_wait_sleep(uint32_t bar, uint32_t parity) {
    int n = 0;
    while (!mbar_try(bar, parity) && ++n < SPIN_LIMIT) __nanosleep(SLEEP_NS);
}
__device__ __forceinline__ void mbar_arrive(uint32_t bar) {
    asm volatile("mbarrier.arrive.shared::cta.b64 _, [%0];" ::"r"(bar) : "memory");
}
__device__ __forceinline__ void mbar_arrive_cluster(uint32_t cluster_bar) {
    asm volatile("mbarrier.arrive.shared::cluster.b64 _, [%0];" ::"r"(cluster_bar) : "memory");
}
__device__ __forceinline__ void mbar_expect_tx(uint32_t bar, uint32_t bytes) {
    asm volatile("mbarrier.arrive.expect_tx.shared::cta.b64 _, [%0], %1;" ::"r"(bar), "r"(bytes) : "memory");
}
__device__ __forceinline__ bool elect_one() {
    uint32_t p;
    asm volatile("{\n.reg .pred p;\nelect.sync _|p, 0xffffffff;\nselp.u32 %0, 1, 0, p;\n}" : "=r"(p));
    return p;
}
__device__ __forceinline__ uint32_t mapa(uint32_t addr, uint32_t rank) {
    uint32_t r;
    asm("mapa.shared::cluster.u32 %0, %1, %2;" : "=r"(r) : "r"(addr), "r"(rank));
    return r;
}
__device__ __forceinline__ uint32_t clock32() { uint32_t t; asm volatile("mov.u32 %0, %%clock;" : "=r"(t)); return t; }
template <int NS> __device__ __forceinline__ void sleep_until(uint32_t t) {
    int n = 0;
    while ((int)(clock32() - t) < 0 && ++n < SPIN_LIMIT) __nanosleep(NS);
}
template <typename T> __device__ __forceinline__ T* at(T* p, uint32_t bytes) {
    asm("" : "+r"(bytes));
    return reinterpret_cast<T*>(reinterpret_cast<uintptr_t>(p) + bytes);
}
__device__ __forceinline__ void tma_2d(uint32_t dst, const CUtensorMap* tm, int c0, int c1, uint32_t bar) {
    asm volatile("cp.async.bulk.tensor.2d.shared::cluster.global.mbarrier::complete_tx::bytes [%0], [%1, {%3, %4}], [%2];"
                 ::"r"(dst), "l"(tm), "r"(bar), "r"(c0), "r"(c1) : "memory");
}
__device__ __forceinline__ void tma_2d_prefetch(const CUtensorMap* tm, int c0, int c1) {
    asm volatile("cp.async.bulk.prefetch.tensor.2d.L2.global [%0, {%1, %2}];" ::"l"(tm), "r"(c0), "r"(c1) : "memory");
}
__device__ __forceinline__ void tma_2d_store(const CUtensorMap* tm, int c0, int c1, uint32_t src) {
    asm volatile("cp.async.bulk.tensor.2d.global.shared::cta.bulk_group [%0, {%2, %3}], [%1];"
                 ::"l"(tm), "r"(src), "r"(c0), "r"(c1) : "memory");
}
__device__ __forceinline__ void bulk_g2s(uint32_t dst, const void* src, uint32_t bytes, uint32_t bar) {
    asm volatile("cp.async.bulk.shared::cluster.global.mbarrier::complete_tx::bytes [%0], [%1], %2, [%3];"
                 ::"r"(dst), "l"(src), "r"(bytes), "r"(bar) : "memory");
}
__device__ __forceinline__ void bulk_s2g(void* dst, uint32_t src, uint32_t bytes) {
    asm volatile("cp.async.bulk.global.shared::cta.bulk_group [%0], [%1], %2;" ::"l"(dst), "r"(src), "r"(bytes) : "memory");
}
__device__ __forceinline__ void st_async4(uint32_t dst, uint32_t a, uint32_t b, uint32_t c, uint32_t d, uint32_t bar) {
    asm volatile("st.async.weak.shared::cluster.mbarrier::complete_tx::bytes.v4.b32 [%0], {%1,%2,%3,%4}, [%5];"
                 ::"r"(dst), "r"(a), "r"(b), "r"(c), "r"(d), "r"(bar) : "memory");
}
__device__ __forceinline__ void bulk_commit() { asm volatile("cp.async.bulk.commit_group;" ::: "memory"); }
template <int N> __device__ __forceinline__ void bulk_wait_read() { asm volatile("cp.async.bulk.wait_group.read %0;" ::"n"(N) : "memory"); }
template <int N> __device__ __forceinline__ void bulk_wait() { asm volatile("cp.async.bulk.wait_group %0;" ::"n"(N) : "memory"); }
__device__ __forceinline__ void fence_async_smem() { asm volatile("fence.proxy.async.shared::cta;" ::: "memory"); }
__device__ __forceinline__ void fence_async_global() { asm volatile("fence.proxy.async.global;" ::: "memory"); }
__device__ __forceinline__ void prefetch_tmap(const CUtensorMap* tm) {
    asm volatile("prefetch.tensormap [%0];" ::"l"(tm) : "memory");
}
__device__ __forceinline__ unsigned long long ld_acquire64(const unsigned long long* p) {
    unsigned long long v; asm volatile("ld.acquire.gpu.global.u64 %0, [%1];" : "=l"(v) : "l"(p) : "memory"); return v;
}
__device__ __forceinline__ unsigned load_epoch(int b) {
    unsigned v; asm volatile("ld.global.u32 %0, [%1];" : "=r"(v) : "l"(at(g_epoch, b * 4)) : "memory"); return v + 1;
}
__device__ __forceinline__ unsigned ld_relaxed(const void* p) {
    unsigned v; asm volatile("ld.relaxed.gpu.global.u32 %0, [%1];" : "=r"(v) : "l"(p) : "memory"); return v;
}
__device__ __forceinline__ uint4 ld_relaxed128(const uint4* p) {
    uint4 v;
    asm volatile("{\n.reg .b128 t;\n.reg .b64 lo, hi;\nld.relaxed.gpu.global.b128 t, [%4];\nmov.b128 {lo, hi}, t;\n"
                 "mov.b64 {%0, %1}, lo;\nmov.b64 {%2, %3}, hi;\n}"
                 : "=r"(v.x), "=r"(v.y), "=r"(v.z), "=r"(v.w) : "l"(p) : "memory");
    return v;
}
__device__ __forceinline__ void st_relaxed128(uint4* p, const uint4& v) {
    asm volatile("{\n.reg .b128 t;\n.reg .b64 lo, hi;\nmov.b64 lo, {%1, %2};\nmov.b64 hi, {%3, %4};\nmov.b128 t, {lo, hi};\n"
                 "st.relaxed.gpu.global.b128 [%0], t;\n}"
                 ::"l"(p), "r"(v.x), "r"(v.y), "r"(v.z), "r"(v.w) : "memory");
}
__device__ __forceinline__ void st_relaxed64(unsigned long long* p, unsigned long long v) {
    asm volatile("st.relaxed.gpu.global.u64 [%0], %1;" ::"l"(p), "l"(v) : "memory");
}
__device__ __forceinline__ void st_release8(void* p, unsigned v) {
    asm volatile("st.release.gpu.global.u8 [%0], %1;" ::"l"(p), "r"(v) : "memory");
}
__device__ __forceinline__ uint64_t policy_evict_first() {
    uint64_t pol;
    asm("createpolicy.fractional.L2::evict_first.b64 %0, 1.0;" : "=l"(pol));
    return pol;
}
__device__ __forceinline__ uint4 ldg_stream(const void* p, uint64_t pol) {
    uint4 v;
    asm volatile("ld.global.nc.L1::no_allocate.L2::cache_hint.v4.u32 {%0,%1,%2,%3}, [%4], %5;"
                 : "=r"(v.x), "=r"(v.y), "=r"(v.z), "=r"(v.w) : "l"(p), "l"(pol));
    return v;
}
__device__ __forceinline__ uint4 ldg_stream_ord(const void* p, uint64_t pol) {
    uint4 v;
    asm volatile("ld.relaxed.gpu.global.L1::no_allocate.L2::cache_hint.v4.u32 {%0,%1,%2,%3}, [%4], %5;"
                 : "=r"(v.x), "=r"(v.y), "=r"(v.z), "=r"(v.w) : "l"(p), "l"(pol) : "memory");
    return v;
}
template <int ID, int N> __device__ __forceinline__ void named_arrive() { asm volatile("bar.arrive %0, %1;" ::"n"(ID), "n"(N) : "memory"); }
template <int ID, int N> __device__ __forceinline__ void named_bar() { asm volatile("bar.sync %0, %1;" ::"n"(ID), "n"(N) : "memory"); }

__device__ __forceinline__ float bf_lo(uint32_t u) { return __uint_as_float(u << 16); }
__device__ __forceinline__ float bf_hi(uint32_t u) { return __uint_as_float(u & 0xffff0000u); }
__device__ __forceinline__ uint32_t pack_bf(float lo, float hi) {
    uint32_t r; asm("cvt.rn.bf16x2.f32 %0, %1, %2;" : "=r"(r) : "f"(hi), "f"(lo)); return r;
}
__device__ __forceinline__ float rbf(float v) { return __uint_as_float(pack_bf(0.f, v)); }
__device__ __forceinline__ float sqrt_f(float v) { float r; asm("sqrt.approx.f32 %0, %1;" : "=f"(r) : "f"(v)); return r; }
__device__ __forceinline__ float rcp_f(float v) { float r; asm("rcp.approx.f32 %0, %1;" : "=f"(r) : "f"(v)); return r; }
__device__ __forceinline__ float silu_f(float z) { return __fdividef(z, 1.0f + __expf(-z)); }
__device__ __forceinline__ uint32_t bsub2(uint32_t a, uint32_t b) {
    uint32_t r; asm("sub.rn.bf16x2 %0, %1, %2;" : "=r"(r) : "r"(a), "r"(b)); return r;
}
__device__ __forceinline__ uint32_t bfma2(uint32_t a, uint32_t b, uint32_t c) {
    uint32_t r; asm("fma.rn.bf16x2 %0, %1, %2, %3;" : "=r"(r) : "r"(a), "r"(b), "r"(c)); return r;
}
__device__ __forceinline__ uint32_t norm2(uint32_t xv, float m, float rinv) {
    uint32_t t = pack_bf(bf_lo(xv) - m, bf_hi(xv) - m);
    return pack_bf(bf_lo(t) * rinv, bf_hi(t) * rinv);
}
__device__ __forceinline__ float gate1(float z) {
    float t;
    const float h = 0.5f * z;
    asm("tanh.approx.f32 %0, %1;" : "=f"(t) : "f"(h));
    return fmaf(h, t, h);
}
__device__ __forceinline__ uint32_t gate2(uint32_t xv, uint32_t mean2, float r0, float r1) {
    const uint32_t t = bsub2(xv, mean2);
    return pack_bf(gate1(bf_lo(t) * r0), gate1(bf_hi(t) * r1));
}
__device__ __forceinline__ uint32_t silu2(uint32_t z) { return pack_bf(silu_f(bf_lo(z)), silu_f(bf_hi(z))); }

__device__ __forceinline__ void stmatrix4(uint32_t addr, uint32_t r0, uint32_t r1, uint32_t r2, uint32_t r3) {
    asm volatile("stmatrix.sync.aligned.m8n8.x4.shared.b16 [%0], {%1,%2,%3,%4};"
                 ::"r"(addr), "r"(r0), "r"(r1), "r"(r2), "r"(r3));
}
__device__ __forceinline__ void stmatrix4t(uint32_t addr, uint32_t r0, uint32_t r1, uint32_t r2, uint32_t r3) {
    asm volatile("stmatrix.sync.aligned.m8n8.x4.trans.shared.b16 [%0], {%1,%2,%3,%4};"
                 ::"r"(addr), "r"(r0), "r"(r1), "r"(r2), "r"(r3));
}
__device__ __forceinline__ void ldmatrix4t(uint32_t addr, uint32_t& r0, uint32_t& r1, uint32_t& r2, uint32_t& r3) {
    asm volatile("ldmatrix.sync.aligned.m8n8.x4.trans.shared.b16 {%0,%1,%2,%3}, [%4];"
                 : "=r"(r0), "=r"(r1), "=r"(r2), "=r"(r3) : "r"(addr));
}

__device__ __forceinline__ void wg_fence() { asm volatile("wgmma.fence.sync.aligned;" ::: "memory"); }
__device__ __forceinline__ void wg_commit() { asm volatile("wgmma.commit_group.sync.aligned;" ::: "memory"); }
template <int N> __device__ __forceinline__ void wg_wait() { asm volatile("wgmma.wait_group.sync.aligned %0;" ::"n"(N) : "memory"); }

__host__ __device__ constexpr uint32_t desc_lo(uint32_t addr, uint32_t lbo) { return ((addr & 0x3FFFF) >> 4) | ((lbo >> 4) << 16); }
#define DESC_HI "0x40000040"

#define R8(a, o) "+f"(a[(o) + 0]), "+f"(a[(o) + 1]), "+f"(a[(o) + 2]), "+f"(a[(o) + 3]), \
                 "+f"(a[(o) + 4]), "+f"(a[(o) + 5]), "+f"(a[(o) + 6]), "+f"(a[(o) + 7])
#define R64(a, o) R8(a, (o) + 0), R8(a, (o) + 8), R8(a, (o) + 16), R8(a, (o) + 24), \
                  R8(a, (o) + 32), R8(a, (o) + 40), R8(a, (o) + 48), R8(a, (o) + 56)

template <int O, int TA>
__device__ __forceinline__ void wgmma128(float (&a)[128], uint32_t da, uint32_t db, int scale_d) {
    asm volatile(
        "{\n.reg .pred p;\n.reg .b64 da, db;\nsetp.ne.b32 p, %66, 0;\n"
        "mov.b64 da, {%64, " DESC_HI "};\nmov.b64 db, {%65, " DESC_HI "};\n"
        "wgmma.mma_async.sync.aligned.m64n128k16.f32.bf16.bf16 "
        "{%0,%1,%2,%3,%4,%5,%6,%7,%8,%9,%10,%11,%12,%13,%14,%15,"
        "%16,%17,%18,%19,%20,%21,%22,%23,%24,%25,%26,%27,%28,%29,%30,%31,"
        "%32,%33,%34,%35,%36,%37,%38,%39,%40,%41,%42,%43,%44,%45,%46,%47,"
        "%48,%49,%50,%51,%52,%53,%54,%55,%56,%57,%58,%59,%60,%61,%62,%63},"
        "da, db, p, 1, 1, %67, 0;\n}"
        : R64(a, O)
        : "r"(da), "r"(db), "r"(scale_d), "n"(TA));
}
template <int O>
__device__ __forceinline__ void wgmma128_rs(float (&a)[128], const uint32_t* f, uint32_t db) {
    asm volatile(
        "{\n.reg .b64 db;\nmov.b64 db, {%68, 8};\n"
        "wgmma.mma_async.sync.aligned.m64n128k16.f32.bf16.bf16 "
        "{%0,%1,%2,%3,%4,%5,%6,%7,%8,%9,%10,%11,%12,%13,%14,%15,"
        "%16,%17,%18,%19,%20,%21,%22,%23,%24,%25,%26,%27,%28,%29,%30,%31,"
        "%32,%33,%34,%35,%36,%37,%38,%39,%40,%41,%42,%43,%44,%45,%46,%47,"
        "%48,%49,%50,%51,%52,%53,%54,%55,%56,%57,%58,%59,%60,%61,%62,%63},"
        "{%64, %65, %66, %67}, db, 1, 1, 1, 0;\n}"
        : R64(a, O)
        : "r"(f[0]), "r"(f[1]), "r"(f[2]), "r"(f[3]), "r"(db));
}
template <int O>
__device__ __forceinline__ void fence_regs64(float (&a)[128]) {
    asm volatile("" : R64(a, O)::"memory");
}

struct Params {
    const __nv_bfloat16* x;
    const __nv_bfloat16* dre;
    const __nv_bfloat16* dim;
    const __nv_bfloat16* wr;
    const __nv_bfloat16* wg;
    const __nv_bfloat16* wu;
    const __nv_bfloat16* wd;
    uint32_t zero;
#define AB g_ab
};

__device__ __forceinline__ float warp_sum(float v) {
#pragma unroll
    for (int o = 16; o; o >>= 1) v += __shfl_xor_sync(0xffffffffu, v, o);
    return v;
}
__device__ __forceinline__ void fma8(float* acc, const uint4& w, float s) {
    acc[0] += s * bf_lo(w.x); acc[1] += s * bf_hi(w.x); acc[2] += s * bf_lo(w.y); acc[3] += s * bf_hi(w.y);
    acc[4] += s * bf_lo(w.z); acc[5] += s * bf_hi(w.z); acc[6] += s * bf_lo(w.w); acc[7] += s * bf_hi(w.w);
}
__device__ __forceinline__ int POS(int t) { return (t & ~15) | ((t & 6) << 1) | ((t & 8) >> 2) | (t & 1); }
__host__ __device__ constexpr int PSLOT(int j) { return j < 4 ? j : (j & 1) + ((j & 2) ? 0 : 4); }
__host__ __device__ constexpr int PPAR(int j) { return j < 4 ? 0 : ((j >> 2) ^ (j >> 1) ^ 1) & 1; }
__host__ __device__ constexpr int DSLOT(int it) { return (it & 3) + 2; }
__device__ __forceinline__ int SREC(int t) { return (t & ~15) | ((t & 3) << 2) | ((t >> 2) & 3); }
__device__ __forceinline__ int KO(int cl) { return ((cl & 1) << 1) | (cl >> 1); }

__global__ void __cluster_dims__(2, 1, 1) __launch_bounds__(NTHREADS, 1)
fnet_fused_kernel(const __grid_constant__ CUtensorMap tm_x, const __grid_constant__ CUtensorMap tm_dre,
                  const __grid_constant__ CUtensorMap tm_dim, const __grid_constant__ CUtensorMap tm_cre,
                  const __grid_constant__ CUtensorMap tm_cim, const __grid_constant__ CUtensorMap tm_out,
                  const __grid_constant__ CUtensorMap tm_x64,
                  const Params P) {
    extern __shared__ __align__(1024) uint8_t smem[];
    const unsigned long long tstart = clock64();
    const uint32_t sb = smem_u32(smem);
    const int tid = threadIdx.x, lane = tid & 31;
    const int pr = blockIdx.x >> 1, p7 = ((pr - 36) * 37) >> 8;
    const int c = blockIdx.x & 1;
    const bool upper = pr >= 36;
    const int col = upper ? pr - 36 - 7 * p7 + 8 : pr < 4 ? 15 : (pr - 4) & 7;
    const int gi = (int)(0x1eca8642fdb97530ull >> (4 * col)) & 15;
    const int g = gi & 7;
    const int r = (gi >> 3) * 4 + (upper ? p7 : pr < 4 ? pr : (pr - 4) >> 3);
#define BLK(n) ((n) - ((n) <= g))
    const int grp = 2 * r + c;
    const int b = g * 16 + grp;
    const uint32_t bar0 = sb + OFF_BAR;
    const uint32_t zero = P.zero;
#define BAR(i) (bar0 + 8u * (i))
#define XBAR(i) (sb + OFF_XB + 64 + 8u * (i))
#define CLUSTER_ARRIVE() asm volatile("barrier.cluster.arrive.relaxed.aligned;" ::: "memory")
#define CLUSTER_WAIT() asm volatile("barrier.cluster.wait.aligned;" ::: "memory")

#define LOAD0(it) do { \
            mbar_expect_tx(BAR(B_FS + DSLOT(it)), SLOT); tma_2d(sb + OFF_S + DSLOT(it) * SLOT, tmD, (it) * 64, r * 128, BAR(B_FS + DSLOT(it))); \
            mbar_expect_tx(BAR(B_FL + (it)), SLOT); tma_2d(sb + OFF_L + (it) * SLOT, &tm_x, (it) * 64, g * 256, BAR(B_FL + (it))); \
            mbar_expect_tx(BAR(B_FL + 4 + (it)), SLOT); tma_2d(sb + OFF_L + (4 + (it)) * SLOT, &tm_x, (it) * 64, g * 256 + 128, BAR(B_FL + 4 + (it))); \
        } while (0)
    if (tid < 32) {
        if (elect_one()) {
            const CUtensorMap* tmD = c ? &tm_dim : &tm_dre;
            prefetch_tmap(tmD); prefetch_tmap(&tm_x);
            mbar_init(BAR(B_FS + 2), 1); mbar_init(BAR(B_FL), 1); mbar_init(BAR(B_FL + 4), 1);
            asm volatile("fence.mbarrier_init.release.cluster;" ::: "memory");
            LOAD0(0);
        }
        __syncwarp();
    }
    const int warp = __shfl_sync(0xffffffffu, tid >> 5, 0);
    if (warp == 12) {
        if (elect_one()) {
#pragma unroll
            for (int i = 1; i < 4; i++) { mbar_init(BAR(B_FS + 2 + i), 1); mbar_init(BAR(B_FL + i), 1); mbar_init(BAR(B_FL + 4 + i), 1); }
#pragma unroll
            for (int i = 0; i < 4; i++) mbar_init(XBAR(i), 1);
            asm volatile("fence.mbarrier_init.release.cluster;" ::: "memory");
        }
        __syncwarp();
    }
    if (warp == 14) {
        if (elect_one()) {
#pragma unroll
            for (int i = 0; i < 8; i++) { mbar_init(BAR(B_EL + i), 1); mbar_init(XBAR(4 + i), 1); if (i < 6) mbar_init(BAR(B_ES + i), 2); }
            asm volatile("fence.mbarrier_init.release.cluster;" ::: "memory");
        }
        __syncwarp();
    }
    if (warp == 15) {
        if (elect_one()) {
            mbar_init(BAR(B_FS), 1); mbar_init(BAR(B_FS + 1), 1);
#pragma unroll
            for (int i = B_SRD; i < B_COUNT; i++) mbar_init(BAR(i), i == B_GO ? 2 : i == B_STATS || i == B_LST ? 4 : 1);
#pragma unroll
            for (int i = 0; i < 4; i++) mbar_expect_tx(BAR(B_RECV + i), SLOT / 2);
            mbar_expect_tx(BAR(B_PEER), 1024); mbar_expect_tx(BAR(B_H), 128);
            asm volatile("fence.mbarrier_init.release.cluster;" ::: "memory");
        }
        __syncwarp();
    }
    CLUSTER_ARRIVE();
    if ((sb & 0xffffffu) != SB0) return;

#define GATHER(ptr, cnt, valid) do { int n = 0; bool ok; _Pragma("unroll 1") do { ok = true; \
                _Pragma("unroll") for (int i = 0; i < (cnt); i++) { f[i] = ld_relaxed128((ptr) + i * 32); ok = ok && (valid); } \
                if (__all_sync(0xffffffffu, ok)) break; \
                __nanosleep(GSL); \
            } while (++n < SPIN_LIMIT); } while (0)
    if (warp >= 8 && warp < 12) {
        asm volatile("setmaxnreg.dec.sync.aligned.u32 %0;" ::"n"(512 - PROD_REGS - 2 * CONS_REGS));
        const int aw = warp - 8, mt = tid - 256;
        unsigned ep;
        {
            const uint8_t* rp = smem + OFF_S + aw * 2048 + lane * 16;
            const __nv_bfloat16* dp = at(c ? P.dim : P.dre, (r * 128 + g * 16 + aw * 4) * D_ * 2);
            float wf[32], sw = 0.f;
#pragma unroll
            for (int i = 0; i < 4; i++) {
                const uint4 w = __ldg(reinterpret_cast<const uint4*>(at(P.wr, lane * 16) + i * 256));
                const uint32_t wv[4] = {w.x, w.y, w.z, w.w};
#pragma unroll
                for (int e = 0; e < 4; e++) { wf[8 * i + 2 * e] = bf_lo(wv[e]); wf[8 * i + 2 * e + 1] = bf_hi(wv[e]); sw = (sw + bf_lo(wv[e])) + bf_hi(wv[e]); }
            }
            ep = load_epoch(b);
            sw = warp_sum(sw);
            CLUSTER_WAIT();
            float x0[4] = {}, s1[4] = {}, s2[4] = {}, sx[4] = {}, sd[4] = {};
#define PUSH(a, v) do { a[0] = a[1]; a[1] = a[2]; a[2] = a[3]; a[3] = v; } while (0)
#pragma unroll 1
            for (int k = 0; k < 4; k++) {
                mbar_wait(XBAR(k), 0);
                uint4 v[4];
#pragma unroll
                for (int i = 0; i < 4; i++) v[i] = *reinterpret_cast<const uint4*>(rp + k * 8192 + i * 512);
                uint32_t sh = v[0].x << 16;
                float a1s = 0.f, a2s = 0.f, axs = 0.f;
#pragma unroll
                for (int i = 0; i < 4; i++) {
                    sh = __shfl_sync(0xffffffffu, sh | (__float_as_uint(axs) & zero), 0);
                    const uint32_t xv[4] = {v[i].x, v[i].y, v[i].z, v[i].w};
#pragma unroll
                    for (int e = 0; e < 4; e++) {
                        const float a0 = bf_lo(xv[e]) - __uint_as_float(sh), a1 = bf_hi(xv[e]) - __uint_as_float(sh);
                        a1s += a0 + a1;
                        a2s = fmaf(a0, a0, fmaf(a1, a1, a2s));
                        axs = fmaf(a0, wf[8 * i + 2 * e], fmaf(a1, wf[8 * i + 2 * e + 1], axs));
                    }
                }
                PUSH(x0, __uint_as_float(sh)); PUSH(s1, a1s); PUSH(s2, a2s); PUSH(sx, axs);
                fence_async_smem();
                __syncwarp();
                if (elect_one()) {
                    const uint32_t db = XBAR(k == 3 ? 8 + aw : 4 + aw);
                    if (k == 0 || k == 3) mbar_expect_tx(db, k ? 2048 : 6144);
                    bulk_g2s(sb + OFF_S + k * 8192 + aw * 2048, dp + k * D_, 2048, db);
                }
            }
#define FOLD4(a) do { const bool u16 = lane & 16, u8 = lane & 8; \
                float p0 = (u16 ? a[2] : a[0]) + __shfl_xor_sync(0xffffffffu, u16 ? a[0] : a[2], 16); \
                float p1 = (u16 ? a[3] : a[1]) + __shfl_xor_sync(0xffffffffu, u16 ? a[1] : a[3], 16); \
                a[0] = (u8 ? p1 : p0) + __shfl_xor_sync(0xffffffffu, u8 ? p0 : p1, 8); \
                _Pragma("unroll") for (int o = 4; o; o >>= 1) a[0] += __shfl_xor_sync(0xffffffffu, a[0], o); } while (0)
#pragma unroll 1
            for (int k = 0; k < 4; k++) {
                mbar_wait(XBAR(k == 3 ? 8 + aw : 4 + aw), 0);
                float run = 0.f;
#pragma unroll
                for (int i = 0; i < 4; i++) {
                    const uint4 v = *reinterpret_cast<const uint4*>(rp + k * 8192 + i * 512);
                    const uint32_t dv[4] = {v.x, v.y, v.z, v.w};
#pragma unroll
                    for (int e = 0; e < 4; e++) run += bf_lo(dv[e]) + bf_hi(dv[e]);
                }
                PUSH(sd, run);
            }
            named_bar<4, 128>();
            if (mt < 12) asm volatile("mbarrier.inval.shared::cta.b64 [%0];" ::"r"(XBAR(mt)) : "memory");
            FOLD4(sd); FOLD4(s1); FOLD4(s2); FOLD4(sx);
            const float nb = __shfl_down_sync(0xffffffffu, sd[0], 8);
            if ((lane & 15) == 0)
                st_relaxed128(at(g_rs, (grp * 64 + g * 8 + aw * 2 + (lane >> 4)) * 16), make_uint4(__float_as_uint(sd[0]), ep, __float_as_uint(nb), ep));
            if (mt == 0) PROF_T(6);
            const int rr = lane >> 3;
            const float c0 = rr == 0 ? x0[0] : rr == 1 ? x0[1] : rr == 2 ? x0[2] : x0[3];
            const float dm = s1[0] * (1.0f / D_);
            const float mb = rbf(c0 + dm);
            const float rinv = rcp_f(rbf(sqrt_f(rbf(rbf(fmaxf(s2[0] * (1.0f / D_) - dm * dm, 0.f)) + 1e-5f))));
            if ((lane & 7) == 0) st_relaxed128(at(g_stat, (b * 16 + aw * 4 + rr) * 16), make_uint4(__float_as_uint(mb), __float_as_uint(rinv), ep, 0));
            unsigned u = __bfloat16_as_ushort(__float2bfloat16_rn((sx[0] + (c0 - mb) * sw) * rinv));
            u = (u & 0x8000u) ? (~u & 0xffffu) : (u | 0x8000u);
            u = (u << 16) | (0xffffu - (unsigned)(b * 16 + rr * 4 + aw));
            u = __reduce_max_sync(0xffffffffu, u);
            if (lane == 0) { *reinterpret_cast<unsigned*>(smem + OFF_XB + aw * 4) = u; mbar_arrive(BAR(B_LST)); }
            if (aw == 3) {
                mbar_wait(BAR(B_LST), 0);
                const uint4 k = *reinterpret_cast<const uint4*>(smem + OFF_XB);
                if (lane == 0) st_relaxed64(at(g_key, b * 8), ((unsigned long long)ep << 32) | max(max(k.x, k.y), max(k.z, k.w)));
            }
            if (mt == 0) PROF_T(2);
            uint4 f[4];
            if (aw < 2) {
                const int t = SREC(aw * 128 + lane);
                GATHER(at(g_stat, (g * 256 + aw * 128 + lane) * 16), 4, f[i].z == ep);
#pragma unroll
                for (int i = 0; i < 4; i++) {
                    *reinterpret_cast<uint32_t*>(smem + OFF_RSTD + (POS(t) + i * 32) * 4) = f[i].y;
                    *reinterpret_cast<uint16_t*>(smem + OFF_MEAN + (POS(t) + i * 32) * 2) = (uint16_t)(f[i].x >> 16);
                }
            } else {
                const int e2 = (aw - 2) * 32 + lane;
                GATHER(at(g_rs, (grp * 64 + e2) * 16), 1, f[i].y == ep && f[i].w == ep);
#pragma unroll
                for (int i = 0; i < 2; i++) {
                    const float v = __uint_as_float(i ? f[0].z : f[0].x);
                    const float hi = rbf(v), mid = rbf(v - hi), lo = v - hi - mid;
                    *reinterpret_cast<uint4*>(smem + OFF_RS + (e2 * 2 + i) * 16) = make_uint4(pack_bf(hi, mid), pack_bf(lo, 0.f), 0, 0);
                }
            }
            fence_async_smem();
            __syncwarp();
            if (lane == 0) mbar_arrive(BAR(B_STATS));
            if (mt == 127) PROF_T(9);
        }
        const bool moe = pr < 28 || pr >= 36;
        const int pair = pr < 28 ? pr : pr - 8;
        if (moe) {
            const uint64_t pol = policy_evict_first();
            const __nv_bfloat16* wp = at((aw & 1) ? P.wu : P.wg, ((c * 512 + (aw >> 1) * 256 + (lane >> 3) * 8) * F_ + pair * 64 + (lane & 7) * 8) * 2);
            uint4 b0[8], b1[8];
#define FILL(buf, str) do { _Pragma("unroll") for (int q = 0; q < 8; q++) buf[q] = ldg_stream(wp + q * (str), pol); } while (0)
#define PAUSE() do { if (mbar_test(BAR(B_QUIET), 0)) mbar_wait_sleep(BAR(B_GO), 0); } while (0)
#define FILLO(buf, row) do { _Pragma("unroll") for (int q = 0; q < 8; q++) buf[q] = ldg_stream_ord(wp + ((row) + q) * F_, pol); } while (0)
            FILLO(b0, 0);
            mbar_wait(BAR(B_SEL), 0);
            uint4 xn;
            {
                const int sel = ~*reinterpret_cast<volatile unsigned*>(smem + OFF_SEL) & (S_ - 1);
                xn = __ldg(reinterpret_cast<const uint4*>(at(P.x, (sel * D_ + c * 512 + (aw >> 1) * 256 + (lane & 7) * 32 + (lane >> 3) * 8) * 2)));
                uint4 f[1];
                GATHER(at(g_stat, SREC(sel) * 16), 1, f[i].z == ep);
                FILLO(b1, 32);
                PAUSE();
                const float m = __uint_as_float(f[0].x), ri = __uint_as_float(f[0].y);
                xn = make_uint4(norm2(xn.x, m, ri), norm2(xn.y, m, ri), norm2(xn.z, m, ri), norm2(xn.w, m, ri));
            }
            float ag[8];
#pragma unroll
            for (int i = 0; i < 8; i++) ag[i] = 0.f;
#define ROUND(cur, nxt, rd) do { \
                PAUSE(); \
                if (lane == 0) TRACE(192 + aw * 12 + (rd)); \
                if ((rd) == 7) wp = at(P.wd - 16 * D_, ((pair * 64 + (lane >> 4) * 8) * D_ + c * 512 + aw * 128 + (lane & 15) * 8) * 2); \
                wp = at(wp, ((rd) < 7 ? 64 * F_ : 32 * D_) + (cur[7].x & zero)); \
                if ((rd) & 7) { if ((rd) < 7) FILL(nxt, F_); else if ((rd) < 11) FILL(nxt, D_); } \
                _Pragma("unroll") for (int q = 0; q < 8; q += 2) { \
                    const uint32_t xw = __shfl_sync(0xffffffffu, q == 0 ? xn.x : q == 2 ? xn.y : q == 4 ? xn.z : xn.w, ((lane & 24) | ((rd) & 7)) | (__float_as_uint(ag[7]) & zero)); \
                    fma8(ag, cur[q], bf_lo(xw)); \
                    fma8(ag, cur[q + 1], bf_hi(xw)); \
                } } while (0)
#pragma unroll 1
            for (int rd = 0; rd < 12; rd += 2) {
                ROUND(b0, b1, rd);
                ROUND(b1, b0, rd + 1);
                if (rd == 6 || rd == 10) {
#pragma unroll
                    for (int i = 0; i < 8; i++) ag[i] += __shfl_xor_sync(0xffffffffu, ag[i], 16);
                }
                if (rd == 6) {
#pragma unroll
                    for (int i = 0; i < 8; i++) ag[i] += __shfl_xor_sync(0xffffffffu, ag[i], 8);
                    if (lane < 8) {
                        const uint32_t dst = mapa(sb + OFF_XB + (c * 4 + aw) * 128 + (lane & 3) * 32, lane >> 2), pb = mapa(BAR(B_PEER), lane >> 2);
                        st_async4(dst, __float_as_uint(ag[0]), __float_as_uint(ag[1]), __float_as_uint(ag[2]), __float_as_uint(ag[3]), pb);
                        st_async4(dst + 16, __float_as_uint(ag[4]), __float_as_uint(ag[5]), __float_as_uint(ag[6]), __float_as_uint(ag[7]), pb);
                    }
                    __syncwarp();
                    wp += 16 * D_; FILL(b1, D_); wp -= 16 * D_;
                    if (aw == 3) {
                        mbar_wait_cluster(BAR(B_PEER), 0);
                        const float* ps = reinterpret_cast<const float*>(smem + OFF_XB) + lane;
                        const float go = (ps[0] + ps[64]) + (ps[128] + ps[192]), uo = (ps[32] + ps[96]) + (ps[160] + ps[224]);
                        const float h = rbf(silu_f(rbf(go))) * rbf(uo), ho = __shfl_xor_sync(0xffffffffu, h, 1);
                        asm volatile("st.async.weak.shared::cluster.mbarrier::complete_tx::bytes.b32 [%0], %1, [%2];"
                                     ::"r"(mapa(sb + OFF_H + c * 64 + (lane >> 1) * 4, lane & 1)), "r"((lane & 1) ? pack_bf(ho, h) : pack_bf(h, ho)),
                                       "r"(mapa(BAR(B_H), lane & 1)) : "memory");
                    }
                    mbar_wait_cluster(BAR(B_H), 0);
                    xn = *reinterpret_cast<const uint4*>(smem + OFF_H + (lane & 3) * 32 + (lane >> 4) * 16);
#pragma unroll
                    for (int i = 0; i < 8; i++) ag[i] = 0.f;
                    if (mt == 0) PROF_T(10);
                }
            }
            const int hi = lane >> 4;
            st_relaxed128(at(g_part, pair * 4096 + (c * 8 + aw * 2 + ((lane >> 3) & 1)) * 256 + hi * 128 + (lane & 7) * 16),
                          make_uint4((__float_as_uint(hi ? ag[4] : ag[0]) & ~15u) | (ep & 15u), __float_as_uint(hi ? ag[5] : ag[1]),
                                     __float_as_uint(hi ? ag[6] : ag[2]), __float_as_uint(hi ? ag[7] : ag[3])));
            if (mt == 0) PROF_T(11);
        } else {
            mbar_wait_sleep(BAR(B_SEL), 0);
        }
        const int sel = ~*reinterpret_cast<volatile unsigned*>(smem + OFF_SEL) & (S_ - 1);
        if ((sel >> 8) == g) {
            const int col = (lane & 7) * 8 + ((lane >> 3) & 1) * 4;
            const uint2 xv = __ldg(reinterpret_cast<const uint2*>(at(P.x, (sel * D_ + grp * 64 + col) * 2)));
            uint4 f[1];
            GATHER(at(g_stat, SREC(sel) * 16), 1, f[i].z == ep);
            const uint4 rec = f[0];
            const uint4* src = at(g_part, (aw * 14 + (lane >> 4)) * 4096 + grp * 256 + (lane & 15) * 16);
            if (!moe) {
                int n = 0;
                while (((ld_relaxed(src) ^ ep) & 15u) != 0 && ++n < SPIN_LIMIT) __nanosleep(500);
            }
            uint4 t[7];
            int n = 0;
            bool ok;
            do {
                ok = true;
#pragma unroll
                for (int u = 0; u < 7; u++) { t[u] = ld_relaxed128(src + u * 512); ok = ok && ((t[u].x ^ ep) & 15u) == 0; }
            } while (!__all_sync(0xffffffffu, ok) && ++n < SPIN_LIMIT);
            float4 a = make_float4(0.f, 0.f, 0.f, 0.f);
#pragma unroll
            for (int u = 0; u < 7; u++) {
                a.x += __uint_as_float(t[u].x & ~15u); a.y += __uint_as_float(t[u].y); a.z += __uint_as_float(t[u].z); a.w += __uint_as_float(t[u].w);
            }
            a.x += __shfl_xor_sync(0xffffffffu, a.x, 16); a.y += __shfl_xor_sync(0xffffffffu, a.y, 16);
            a.z += __shfl_xor_sync(0xffffffffu, a.z, 16); a.w += __shfl_xor_sync(0xffffffffu, a.w, 16);
            float4* park = reinterpret_cast<float4*>(smem + OFF_XB) + (lane & 15);
            if (lane < 16) park[aw * 16] = a;
            named_bar<4, 128>();
            if (aw == 0) {
                const float4 p1 = park[16], p2 = park[32], p3 = park[48];
                a.x = (a.x + p1.x) + (p2.x + p3.x); a.y = (a.y + p1.y) + (p2.y + p3.y);
                a.z = (a.z + p1.z) + (p2.z + p3.z); a.w = (a.w + p1.w) + (p2.w + p3.w);
                unsigned u = *reinterpret_cast<volatile unsigned*>(smem + OFF_SEL) >> 16;
                u = (u & 0x8000u) ? (u & 0x7fffu) : (~u & 0xffffu);
                const float sg = rbf(__fdividef(1.0f, 1.0f + __expf(-__uint_as_float(u << 16))));
                const float m = __uint_as_float(rec.x), ri = __uint_as_float(rec.y);
                const uint32_t n0 = norm2(xv.x, m, ri), n1 = norm2(xv.y, m, ri);
                uint2 o;
                o.x = silu2(pack_bf(bf_lo(n0) + rbf(rbf(a.x) * sg), bf_hi(n0) + rbf(rbf(a.y) * sg)));
                o.y = silu2(pack_bf(bf_lo(n1) + rbf(rbf(a.z) * sg), bf_hi(n1) + rbf(rbf(a.w) * sg)));
                if (lane < 16) *reinterpret_cast<uint2*>(smem + OFF_H + col * 2) = o;
                __syncwarp();
                if (lane == 0) { mbar_arrive(BAR(B_UPD)); PROF_T(12); }
            }
        }
    } else if (warp < 8) {
        asm volatile("setmaxnreg.inc.sync.aligned.u32 %0;" ::"n"(CONS_REGS));
        CLUSTER_WAIT();
        const int wg = warp >> 2, wq = warp & 3;
        const int wt = tid & 127;
        float acc[128];
        const uint32_t fL = BAR(B_FL + 4 * wg), eL = BAR(B_EL + 4 * wg);
        const uint32_t dL = desc_lo(SB0 + OFF_L, 16) + wg * 4096;
        constexpr uint32_t dS = desc_lo(SB0 + OFF_S, 16);
        constexpr uint32_t SL = SLOT >> 4;
#define RELEASE(ls, ss) do { if (wt == 0) { mbar_arrive(eL + 8u * (ls)); mbar_arrive(BAR(B_ES + (ss))); } } while (0)
#define WAIT_FULL(ls, lph, ss, sph) do { mbar_wait(BAR(B_FS + (ss)), sph); mbar_wait(fL + 8u * (ls), lph); } while (0)
#define TURN() do { if (wg) named_bar<6, 256>(); else named_bar<5, 256>(); } while (0)
#define PASS() do { if (wg) named_arrive<5, 256>(); else named_arrive<6, 256>(); } while (0)
#define WG_BAR() do { if (wg) named_bar<2, 128>(); else named_bar<1, 128>(); } while (0)
        if (wg == 1) PASS();

#define MMA1_H(O, s, first) do { _Pragma("unroll") for (int kk = 0; kk < 4; kk++) \
            wgmma128<O, 0>(acc, dL + (s) * SL + kk * 2 + (O) * 8, dS + DSLOT(s) * SL + kk * 2, !((first) && kk == 0)); } while (0)
#define WAIT1(s, ph) WAIT_FULL(s, ph, DSLOT(s), ph)
#define PROBE(ls, lph, ss, sph) (mbar_test(BAR(B_FS + (ss)), sph) & mbar_test(fL + 8u * (ls), lph))
#define REL1(s) RELEASE(s, DSLOT(s))
#pragma unroll 1
        for (int it = 0; it < 12; it++) {
            const int s = it & 3;
            const bool ok = PROBE(s, (it >> 2) & 1, DSLOT(s), (it >> 2) & 1);
            if (it) { wg_wait<0>(); REL1((s + 3) & 3); }
            if (!ok) WAIT1(s, (it >> 2) & 1);
            TURN();
            wg_fence(); MMA1_H(0, s, it == 0); MMA1_H(64, s, it == 0); wg_commit();
            PASS();
            if (it == 0 && tid == 0) PROF_T(16);
        }
        TS(12);
        float rs[4] = {};
        uint32_t nm[8] = {};
#define GET_STATS() do { mbar_wait(BAR(B_STATS), 0); \
            const int p0 = POS(wg * 128 + wq * 16 + (lane >> 2));                   \
            const uint32_t msk = (lane & 3) == 0 ? 0xffffffffu : (lane & 3) == 1 ? 0x0000ffffu : 0u; \
            _Pragma("unroll") for (int i = 0; i < 4; i++) { \
                const int p = p0 + (i & 1) * 2 + (i >> 1) * 64; \
                rs[i] = *reinterpret_cast<const float*>(smem + OFF_RSTD + p * 4); \
                const uint32_t m = *reinterpret_cast<const uint16_t*>(smem + OFF_MEAN + p * 2) ^ 0x8000u; \
                nm[i + (i & 2)] = (m | (m << 16)) & msk; \
            } } while (0)
        const bool early = wg || __all_sync(0xffffffffu, mbar_test(BAR(B_STATS), 0));
        if (early && !wg) GET_STATS();
        WAIT1(0, 1);
        TS(13);
        wg_wait<0>(); REL1(3);
        if (wg) GET_STATS();
        TS(14);
        TURN();
        wg_fence();
        MMA1_H(0, 0, false);
        if (tid == 0) { mbar_arrive(BAR(B_QUIET)); PROF_T(15); }
        WAIT1(1, 1); wg_fence(); MMA1_H(0, 1, false);
        WAIT1(2, 1); wg_fence(); MMA1_H(0, 2, false); wg_commit();
        if (!early) GET_STATS();
        asm volatile("" : "+r"(nm[0]), "+r"(nm[1]), "+r"(nm[2]), "+r"(nm[3]), "+r"(nm[4]), "+r"(nm[5]), "+r"(nm[6]), "+r"(nm[7])::"memory");
        wg_fence();
        wgmma128_rs<64>(acc, nm + 4, (SB0 + OFF_RS) >> 4);
        wgmma128_rs<0>(acc, nm, (SB0 + OFF_RS) >> 4);
        WAIT1(3, 1); wg_fence(); MMA1_H(0, 3, false); wg_commit();
        PASS();
        const int mrow = wq * 16 + ((lane >> 3) & 1) * 8 + (lane & 7);
#define EPI1(O, slot, FREE) do { const uint32_t dst = sb + OFF_S + (slot) * SLOT + mrow * 128; \
            uint32_t pk[32]; \
            _Pragma("unroll") for (int i = 0; i < 32; i += 4) { \
                _Pragma("unroll") for (int k = 0; k < 4; k++) \
                    pk[i + k] = pack_bf(acc[(O) + 2 * (i + k)] * rs[(O) / 32 + (k & 1)], acc[(O) + 2 * (i + k) + 1] * rs[(O) / 32 + (k & 1)]); \
                if (i == EF) { FREE; } \
                if (i >= EF) { _Pragma("unroll") for (int v = (i == EF ? 0 : i); v <= i; v += 4) \
                    stmatrix4(dst + ((v >> 4) ^ c ^ 1) * 8192 + ((((v >> 1) & 7) + (lane >> 4)) ^ (lane & 7)) * 16, pk[v], pk[v + 1], pk[v + 2], pk[v + 3]); } } \
            WG_BAR(); \
            if (wt == 0) mbar_arrive(BAR(B_FS + (slot))); } while (0)
        TS(15);
        wg_wait<0>();
        fence_regs64<0>(acc);
        TS(16);
        {
            constexpr int EF = 0;
            EPI1(0, wg, if (wg) mbar_wait(BAR(B_FS), 0));
        }
        TS(17);
        TURN();
        wg_fence();
        MMA1_H(64, 0, false); wg_commit();
        MMA1_H(64, 1, false); wg_commit();
        MMA1_H(64, 2, false); wg_commit();
        wg_wait<2>(); REL1(0);
        MMA1_H(64, 3, false); wg_commit();
        PASS();
        TS(18);
        wg_wait<2>(); REL1(1);
        mbar_wait(BAR(B_FS), 0); mbar_wait(BAR(B_FS + 1), 0); fence_async_smem();
        wg_wait<1>(); REL1(2);
        wg_wait<0>(); REL1(3);
        fence_regs64<64>(acc);
        TS(19);
        {
            constexpr int EF = 16;
            EPI1(64, 2 + wg, mbar_wait(BAR(B_ES + 2 + wg), 1));
        }
        TS(20);

        float ac2[128];
#define MMA2_H(O, ls, ss, first) do { _Pragma("unroll") for (int kk = 0; kk < 4; kk++) \
            wgmma128<O, 1>(ac2, dS + (ss) * SL + kk * 128 + (O) * 8, dL + (ls) * SL + kk * 2, !((first) && kk == 0)); } while (0)
#define WAIT2(j) WAIT_FULL((j) & 3, ((j) >> 2) & 1, PSLOT(j), PPAR(j))
#define MMA2(j) do { wg_fence(); MMA2_H(0, (j) & 3, PSLOT(j), (j) == 0); MMA2_H(64, (j) & 3, PSLOT(j), (j) == 0); wg_commit(); } while (0)
#define REL2(j) RELEASE((j) & 3, PSLOT(j))
        WAIT2(0); TURN(); MMA2(0);
        WAIT2(1); MMA2(1); PASS();
        TS(21);
        wg_wait<1>(); REL2(0);
        mbar_wait(BAR(B_FS + 2), 0); mbar_wait(BAR(B_FS + 3), 0); fence_async_smem();
        TS(22);
        {
            uint32_t l2 = 2, s2 = 2, sp = 1, lph = 0, sph = 0;
#pragma unroll 1
            for (int j = 2; j < XJ; j += 2) {
#pragma unroll
                for (int h = 0; h < 2; h++) {
                    const bool ok = PROBE(l2 + h, lph, s2 + h, sph);
                    wg_wait<0>(); RELEASE(h ? l2 : 3 - l2, h ? s2 : sp);
                    if (!ok) WAIT_FULL(l2 + h, lph, s2 + h, sph);
                    TURN();
                    wg_fence(); MMA2_H(0, l2 + h, s2 + h, false); MMA2_H(64, l2 + h, s2 + h, false); wg_commit();
                    PASS();
                    if (h == (GOJ & 1) && j == (GOJ & ~1) && wt == 0) { mbar_arrive(BAR(B_GO)); if (wg == 0) PROF_T(19); }
                }
                sp = s2 + 1; s2 = 2 * l2; sph = lph; l2 ^= 2;
                lph ^= l2 == 0;
            }
        }
        if (tid == 0) PROF_T(20);
        uint32_t gt[32];
        const uint32_t xrow = sb + OFF_S + 2 * SLOT + wg * 8192 + ((lane >> 4) * 8 + (lane & 7)) * 128 + (((2 * wq + ((lane >> 3) & 1)) ^ (lane & 7)) << 4);
        const uint32_t gsign = c ? 0x80008000u : 0u;
#define XOFF(v) (((v) >> 2) * SLOT + ((v) & 3) * 2048)
        int sel = 0;
        bool own = false;
#define PATCH() do { own = false; \
            const uint32_t v0 = *reinterpret_cast<const uint16_t*>(smem + OFF_H + (wq * 16 + (lane >> 2)) * 2) ^ gsign; \
            const uint32_t v1 = *reinterpret_cast<const uint16_t*>(smem + OFF_H + (wq * 16 + (lane >> 2)) * 2 + 16) ^ gsign; \
            const uint32_t pick = (lane & 3) != ((sel >> 1) & 3) ? 0x3210u : (sel & 1) ? 0x5410u : 0x3254u; \
            _Pragma("unroll") for (int i = 0; i < 16; i++) { \
                const uint32_t m = ((sel >> 3) & 15) == i ? pick : 0x3210u; \
                gt[2 * i] = __byte_perm(gt[2 * i], v0, m); \
                gt[2 * i + 1] = __byte_perm(gt[2 * i + 1], v1, m); \
            } } while (0)
#pragma unroll
        for (int u = 0; u < 8; u++) {
            if (u) { WAIT2(XJ + u - 1); wg_wait<0>(); REL2(XJ + u - 2); TURN(); MMA2(XJ + u - 1); PASS(); }
            uint32_t* o = &gt[4 * u];
            if (!(u & 3)) mbar_wait(BAR(B_FS + 2 + (u >> 2)), 1);
            ldmatrix4t(xrow + XOFF(u), o[0], o[1], o[2], o[3]);
            const float4 r4 = *reinterpret_cast<const float4*>(smem + OFF_RSTD + (wg * 128 + u * 16 + (lane & 3) * 4) * 4);
            const uint2 m2 = *reinterpret_cast<const uint2*>(smem + OFF_MEAN + (wg * 128 + u * 16 + (lane & 3) * 4) * 2);
            o[0] = gate2(o[0], m2.x, r4.x, r4.y) ^ gsign;
            o[1] = gate2(o[1], m2.x, r4.x, r4.y) ^ gsign;
            o[2] = gate2(o[2], m2.y, r4.z, r4.w) ^ gsign;
            o[3] = gate2(o[3], m2.y, r4.z, r4.w) ^ gsign;
            if (u == 2) {
                mbar_wait(BAR(B_SEL), 0);
                sel = ~*reinterpret_cast<volatile unsigned*>(smem + OFF_SEL) & (S_ - 1);
                own = (sel >> 7) == 2 * g + wg;
            }
            asm volatile("st.shared.v2.u32 [%0], {%1,%2};" ::"r"(sb + OFF_SEL + 16), "r"(o[0] ^ o[1]), "r"(o[2] ^ o[3]) : "memory");
        }
        if (tid == 0) PROF_T(21);
        WAIT2(27);
        wg_wait<0>(); REL2(26);
        if (own) {
            const uint32_t t0 = clock32();
            bool ok;
            while (!(ok = mbar_test(BAR(B_UPD), 0)) && clock32() - t0 < wg * 1900u) __nanosleep(50);
            if (__all_sync(0xffffffffu, ok)) PATCH();
        }
        TS(0);
        TURN();
        MMA2(27);
        WAIT2(28); wg_fence(); MMA2_H(0, 0, PSLOT(28), false); wg_commit();
        if (wg == 0) { wg_fence(); MMA2_H(64, 0, PSLOT(28), false); wg_commit(); }
        constexpr uint32_t dL0 = desc_lo(SB0 + OFF_L, 16);
        const uint32_t ct[3] = {wg ? 3u : 1u, wg ? 1u : 2u, wg ? 2u : 5u};
#define TMMA(O, i) wgmma128<O, 1>(ac2, ((i) < 8 ? dS + PSLOT(29 + ((i) >> 2)) * SL : dL0 + 6 * SL) + ((i) & 3) * 128 + (O) * 8, \
                                  dL0 + ct[(i) >> 2] * SL + ((i) & 3) * 2, 1)
#define KEEP(i) TMMA(64, i)
#pragma unroll
        for (int k = 0; k < 3; k++) {
            if (k < 2) mbar_wait(BAR(B_FS + PSLOT(29 + k)), PPAR(29 + k)); else mbar_wait(BAR(B_FL + 6), 1);
            mbar_wait(BAR(B_FL + ct[k]), k == 0 || wg == 0);
            wg_fence();
#pragma unroll
            for (int i = 4 * k; i < 4 * k + 4; i++) TMMA(0, i);
            wg_commit();
            if (k < 2) wg_wait<2>();
            if (k == 0 && tid == 0) mbar_arrive(BAR(B_R27));
            if (k == 1 && tid == 0) mbar_arrive_cluster(mapa(BAR(B_RDY), c ^ 1));
        }
        TS(1);
        wg_fence();
#pragma unroll
        for (int i = 0; i < KQ; i++) KEEP(i);
        wg_commit();
        mbar_wait(BAR(B_RDY + wg), 0);
        wg_wait<1>();
        fence_regs64<0>(ac2);
        TS(2);
        wg_fence();
        {
            const uint32_t dst = mapa(sb + OFF_L + wg * 5 * SLOT + wt * 16, c ^ 1), rb = mapa(BAR(B_RECV + 2 * wg), c ^ 1);
#pragma unroll
            for (int v = 0; v < 8; v++) {
                if (KQ + v < 12) KEEP(KQ + v);
                if (KQ + v == 7) wg_commit();
                if (KQ + v == 11) { wg_commit(); if (wg == 0) PASS(); }
                st_async4(dst + v * 2048, pack_bf(ac2[8 * v + 0], ac2[8 * v + 1]), pack_bf(ac2[8 * v + 2], ac2[8 * v + 3]),
                          pack_bf(ac2[8 * v + 4], ac2[8 * v + 5]), pack_bf(ac2[8 * v + 6], ac2[8 * v + 7]), rb + (v >> 2) * 8);
            }
        }
        if (wg == 1) { wg_fence(); MMA2_H(64, 0, PSLOT(28), false); wg_commit(); }
        TS(3);
        uint32_t xr[32];
#define LDX(v) ldmatrix4t(xrow + XOFF(v), xr[4 * (v)], xr[4 * (v) + 1], xr[4 * (v) + 2], xr[4 * (v) + 3])
        if (wg == 0) {
            wg_wait<2>();
            if (wt == 0) mbar_arrive(BAR(B_SRD));
            wg_wait<1>();
            if (wt == 0) mbar_arrive(BAR(B_SRD + 1));
        }
#pragma unroll
        for (int v = 0; v < XE; v++) LDX(v);
        if (wg == 0) {
            wg_wait<0>();
            if (wt == 0) mbar_arrive_cluster(mapa(BAR(B_RDY + 1), c ^ 1));
        }
        TS(4);
        if (own) { mbar_wait(BAR(B_UPD), 0); PATCH(); }
        TS(5);
        uint4 rv[8];
#define FETCH(v0) do { if ((v0) == 0 || (v0) == 4) mbar_wait_cluster(BAR(B_RECV + 2 * wg + (v0) / 4), 0); \
            _Pragma("unroll") for (int v = (v0); v < (v0) + 2; v++) { \
                asm volatile("ld.shared.v4.u32 {%0,%1,%2,%3}, [%4];" : "=r"(rv[v].x), "=r"(rv[v].y), "=r"(rv[v].z), "=r"(rv[v].w) \
                             : "r"(sb + OFF_L + wg * 5 * SLOT + v * 2048 + wt * 16) : "memory"); \
                if (v >= XE) LDX(v); } } while (0)
        FETCH(0);
        TS(6);
        wg_wait<0>();
        fence_regs64<64>(ac2);
        TS(7);
#pragma unroll
        for (int v0 = 0; v0 < 8; v0 += 2) {
#pragma unroll
            for (int v = v0; v < v0 + 2; v++) {
                const float* a = &ac2[64 + 8 * v];
                stmatrix4t(xrow + XOFF(v),
                           bfma2(bsub2(pack_bf(a[0], a[1]), rv[v].x), gt[4 * v + 0], xr[4 * v + 0]),
                           bfma2(bsub2(pack_bf(a[2], a[3]), rv[v].y), gt[4 * v + 1], xr[4 * v + 1]),
                           bfma2(bsub2(pack_bf(a[4], a[5]), rv[v].z), gt[4 * v + 2], xr[4 * v + 2]),
                           bfma2(bsub2(pack_bf(a[6], a[7]), rv[v].w), gt[4 * v + 3], xr[4 * v + 3]));
            }
            WG_BAR();
            if (wt == 0) mbar_arrive(eL + 4 * v0);
            if (v0 + 2 < 8) FETCH(v0 + 2);
            if (v0 == 0) TS(8);
        }
        TS(9);
    } else {
        asm volatile("setmaxnreg.dec.sync.aligned.u32 %0;" ::"n"(PROD_REGS));
#define XROWS(k) do { mbar_expect_tx(XBAR(k), 8192); bulk_g2s(sb + OFF_S + (k) * 8192, at(P.x, (b * 16 + (k) * 4) * D_ * 2), 8192, XBAR(k)); } while (0)
        if (warp == 12) {
            if (elect_one()) {
                const CUtensorMap* tmD = c ? &tm_dim : &tm_dre;
#pragma unroll 1
                for (int it = 1; it < 4; it++) {
                    while (clock32() - (uint32_t)tstart < LDEL + (it - 1) * LGAP) {}
                    LOAD0(it);
                    if (it >= X0) XROWS(it - X0);
                }
            }
            __syncwarp();
        }
        CLUSTER_WAIT();
        if (warp == 12) {
            if (elect_one()) {
                const CUtensorMap* tmD = c ? &tm_dim : &tm_dre;
#pragma unroll 1
                for (int it = 4; it < 16; it++) {
                    const int s = DSLOT(it);
                    mbar_wait(BAR(B_ES + s), ((it >> 2) & 1) ^ 1);
                    TRACE(it);
                    mbar_expect_tx(BAR(B_FS + s), SLOT);
                    tma_2d(sb + OFF_S + s * SLOT, tmD, it * 64, r * 128, BAR(B_FS + s));
                    if (it < 4 + X0) XROWS(it - X0);
                }
                const unsigned ep = load_epoch(b), e8 = ep & 0xffu;
                const uint8_t* abg = at(AB, grp * 32 * SLOT);
                const unsigned long long* fl = at(g_flag, grp * 128);
                unsigned long long rdy = ld_acquire64(fl);
                mbar_wait(BAR(B_SRD), 0);
                st_release8(at(g_flag, grp * 128 + g), e8);
                PROF_T(7);
                int j = 4;
#pragma unroll 1
                for (int cl = 0; cl < 4; cl++) {
                    if (cl) rdy = ld_acquire64(++fl);
                    fence_async_global();
#pragma unroll 1
                    for (int n = 1; n < 8; n++, j++) {
                        const int q = BLK(n), s = (j & 1) + ((j & 2) ? 0 : 4);
                        const uint32_t fb = BAR(j == 31 ? B_FL + 6 : B_FS + s);
                        if (j == 31) mbar_wait(BAR(B_EL + 6), 0); else mbar_wait(BAR(B_ES + s), ((j >> 2) ^ (j >> 1)) & 1);
                        if (j == 7) mbar_wait(BAR(B_SRD + 1), 0);
                        if (((unsigned)(rdy >> (8 * q)) & 0xffu) != e8) {
                            int m = 0;
                            do { rdy = ld_acquire64(fl); } while (((unsigned)(rdy >> (8 * q)) & 0xffu) != e8 && ++m < SPIN_LIMIT);
                            fence_async_global();
                        }
                        TRACE(16 + j);
                        mbar_expect_tx(fb, SLOT);
                        bulk_g2s(sb + (j == 31 ? OFF_L + 6 * SLOT : OFF_S + s * SLOT), at(abg, (4 * q + KO(cl)) * SLOT), SLOT, fb);
                    }
                }
                *at(g_epoch, b * 4) = ep;
            }
        } else if (warp < 15) {
            if (elect_one()) {
                const int w = warp - 13, row0 = g * 256 + w * 128;
                const CUtensorMap* tmC = c ? &tm_cim : &tm_cre;
                const uint32_t fb = BAR(B_FL + 4 * w), eb = BAR(B_EL + 4 * w), dst = sb + OFF_L + w * 4 * SLOT;
                [[maybe_unused]] unsigned long long mk = 0, mg = 0;
                int n = 0, cl = 0;
#pragma unroll 1
                for (int it = 4; it < 47 - 2 * w; it++) {
                    const int s = it & 3;
                    mbar_wait(eb + 8 * s, ((it >> 2) & 1) ^ 1);
                    TRACE(64 + w * 64 + it - 4);
                    MARK(it);
                    mbar_expect_tx(fb + 8 * s, SLOT);
                    tma_2d(dst + s * SLOT, it < 16 ? &tm_x : tmC, (it < 16 ? it : 4 * (n ? BLK(n) : g) + KO(cl)) * 64, row0, fb + 8 * s);
                    if (it == PTJ) prefetch_tmap(w ? &tm_x64 : tmC);
                    if (it == PTJ && w) prefetch_tmap(&tm_out);
                    if (it >= 16) {
                        if (it == 19) { n = 1; cl = 0; } else if (it < 19) cl++; else if (++n == 8) { n = 1; cl++; }
                    }
                }
#pragma unroll 1
                for (int i = 2 * w; i < 3; i++) {
                    const int s = w ? 1 : i ? i : 3;
                    mbar_wait(w ? eb + 8 : BAR(i ? B_SRD - 1 + i : B_R27), w == 0 && i);
                    mbar_expect_tx(fb + 8 * s, SLOT);
                    tma_2d(dst + s * SLOT, tmC, (4 * BLK(5 + i) + 3) * 64, row0 ^ 128, fb + 8 * s);
                }
                if (w && (r & 3) < 2) tma_2d_prefetch(tmC, (4 * BLK(6 + (r & 1)) + 3) * 64, row0);
#pragma unroll 1
                for (int h = 0; h < 4; h++) {
                    mbar_wait(eb + 8 * h, h < 3);
                    fence_async_smem();
                    tma_2d_store(&tm_out, grp * 64, row0 + h * 32, sb + OFF_S + (2 + (h >> 1)) * SLOT + w * 8192 + (h & 1) * 4096);
                    bulk_commit();
                }
                FINISH(w);
            }
        } else {
            const unsigned ep = load_epoch(b);
            uint4 f[4];
            {
                sleep_until<400>((uint32_t)tstart + RDEL);
                GATHER(at(reinterpret_cast<const uint4*>(g_key), lane * 16), 2, f[i].y == ep && f[i].w == ep);
                const unsigned key = __reduce_max_sync(0xffffffffu, max(max(f[0].x, f[0].z), max(f[1].x, f[1].z)));
                if (lane == 0) { *reinterpret_cast<unsigned*>(smem + OFF_SEL) = key; mbar_arrive(BAR(B_SEL)); PROF_T(8); }
            }
            if (elect_one()) {
#pragma unroll 1
                for (int cl = 0; cl < 4; cl++) {
                    uint8_t* dst = at(AB, (grp * 32 + 4 * g + KO(cl)) * SLOT);
                    const uint32_t src = sb + OFF_S + cl * SLOT, chunk = cl ? 1024 : SLOT;
                    mbar_wait(BAR(B_FS + cl), 0);
                    fence_async_smem();
                    if (cl == 0) PROF_T(3);
                    uint32_t t0 = clock32() + (cl == 1 ? PDEL : 0);
#pragma unroll 1
                    for (uint32_t o = 0; o < SLOT; o += chunk) {
                        sleep_until<50>(t0);
                        bulk_s2g(dst + o, src + o, chunk);
                        bulk_commit();
                        t0 += cl == 1 ? PGAP1 : cl == 2 ? PGAP2 : PGAP3;
                    }
                    bulk_wait<0>();
                    fence_async_global();
                    TRACE(252 + cl);
                    if (cl < 2) mbar_arrive(BAR(B_SRD + cl));
                    else {
                        mbar_wait(BAR(B_ES + cl), 0);
                        mbar_expect_tx(BAR(B_FS + cl), SLOT);
                        tma_2d(src, &tm_x64, grp * 64, g * 256 + (cl - 2) * 64, BAR(B_FS + cl));
                        tma_2d(src + 8192, &tm_x64, grp * 64, g * 256 + (cl - 2) * 64 + 128, BAR(B_FS + cl));
                    }
                    if (cl) st_release8(at(g_flag, grp * 128 + cl * 8 + g), ep & 0xffu);
                    if (cl == 1) PROF_T(5);
                    if (cl == 3) PROF_T(4);
                }
            }
        }
    }
}

typedef CUresult (*EncodeFn)(CUtensorMap*, CUtensorMapDataType, cuuint32_t, void*, const cuuint64_t*, const cuuint64_t*,
                             const cuuint32_t*, const cuuint32_t*, CUtensorMapInterleave, CUtensorMapSwizzle,
                             CUtensorMapL2promotion, CUtensorMapFloatOOBfill);

void make_map(EncodeFn fn, CUtensorMap* tm, const void* p, uint64_t rows, uint64_t cols, uint32_t box_rows) {
    cuuint64_t dims[2] = {cols, rows};
    cuuint64_t strides[1] = {cols * 2};
    cuuint32_t box[2] = {64, box_rows};
    cuuint32_t es[2] = {1, 1};
    fn(tm, CU_TENSOR_MAP_DATA_TYPE_BFLOAT16, 2, const_cast<void*>(p), dims, strides, box, es, CU_TENSOR_MAP_INTERLEAVE_NONE,
       CU_TENSOR_MAP_SWIZZLE_128B, CU_TENSOR_MAP_L2_PROMOTION_L2_128B, CU_TENSOR_MAP_FLOAT_OOB_FILL_NONE);
}

}

extern "C" void kernel_launch(void* const* d_in, const int* in_sizes, int n_in, void* d_out, int out_size) {
    (void)in_sizes; (void)n_in; (void)out_size;
    static EncodeFn fn = nullptr;
    if (!fn) {
        void* p = nullptr;
        cudaDriverEntryPointQueryResult q;
        cudaGetDriverEntryPoint("cuTensorMapEncodeTiled", &p, cudaEnableDefault, &q);
        fn = (EncodeFn)p;
        cudaFuncSetAttribute(fnet_fused_kernel, cudaFuncAttributeMaxDynamicSharedMemorySize, SMEM_BYTES);
    }
    CUtensorMap tx, tdre, tdim, tcre, tcim, tout, tx64;
    make_map(fn, &tx, d_in[0], S_, D_, 128);
    make_map(fn, &tcre, d_in[1], S_, S_, 128);
    make_map(fn, &tcim, d_in[2], S_, S_, 128);
    make_map(fn, &tdre, d_in[3], D_, D_, 128);
    make_map(fn, &tdim, d_in[4], D_, D_, 128);
    make_map(fn, &tx64, d_in[0], S_, D_, 64);
    make_map(fn, &tout, d_out, S_, D_, 32);
    Params P;
    P.x = (const __nv_bfloat16*)d_in[0];
    P.dre = (const __nv_bfloat16*)d_in[3];
    P.dim = (const __nv_bfloat16*)d_in[4];
    P.wr = (const __nv_bfloat16*)d_in[6];
    P.wg = (const __nv_bfloat16*)d_in[7];
    P.wu = (const __nv_bfloat16*)d_in[8];
    P.wd = (const __nv_bfloat16*)d_in[9];
    P.zero = 0;
    fnet_fused_kernel<<<NCTA, NTHREADS, SMEM_BYTES, cudaStreamPerThread>>>(tx, tdre, tdim, tcre, tcim, tout, tx64, P);
}
```
